```python
import torch

def _softmax(x, axis=-1):
    return torch.softmax(x, dim=axis)

def _gelu(x):
    return torch.nn.functional.gelu(x, approximate='tanh')

def _silu(x):
    return torch.nn.functional.silu(x)

def _sigmoid(x):
    return torch.sigmoid(x)

def _layernorm(x, axis=-1, eps=1e-05):
    m = x.mean(dim=axis, keepdim=True)
    v = x.var(dim=axis, keepdim=True, unbiased=False)
    return (x - m) / torch.sqrt(v + eps)

def _scatter_add(tgt, idx, src, axis=0):
    return tgt.clone().index_add_(axis, idx, src)

def _segment_sum(src, seg, n):
    out = torch.zeros((n,) + src.shape[1:], dtype=src.dtype)
    return out.index_add_(0, seg, src)

def _pad(x, pw):
    flat = tuple((v for pair in reversed(pw) for v in pair))
    return torch.nn.functional.pad(x, flat)
kernel_name = 'standalone__neighborhood_nat__vision'

def setup_inputs():

    _w = lambda a: (lambda t: t.to(torch.bfloat16) if t.is_floating_point() else t)(torch.as_tensor(a))
    H = W = 224
    C = 192
    return {'x': _w((lambda *s: torch.randn(*s, dtype=torch.bfloat16) * 0.2)(1, H, W, C)), 'wqkv': _w((lambda *s: torch.randn(*s, dtype=torch.bfloat16) * 0.2)(C, 3 * C)), 'wo': _w((lambda *s: torch.randn(*s, dtype=torch.bfloat16) * 0.05)(C, C))}

def reference(x, wqkv, wo):
    B, H, W, C = x.shape
    ks, dil = (7, 2)
    qkv = x @ wqkv
    q, k, v = (qkv[..., :C].clone(), qkv[..., C:2 * C].clone(), qkv[..., 2 * C:].clone())
    half = (ks - 1) // 2 * dil
    ir = torch.arange(H)
    ic = torch.arange(W)
    off = torch.arange(ks) * dil
    r0 = torch.clip(ir - half, 0, H - 1 - (ks - 1) * dil)
    c0 = torch.clip(ic - half, 0, W - 1 - (ks - 1) * dil)
    ri = r0[:, None] + off[None, :]
    ci = c0[:, None] + off[None, :]
    nidx = (ri[:, None, :, None] * W + ci[None, :, None, :]).reshape(1, H * W * ks * ks, 1)
    kf = k.reshape(B, H * W, C)
    vf = v.reshape(B, H * W, C)
    kn = (lambda x, i, axis: torch.take_along_dim(x, i, dim=axis))(kf, nidx, 1).reshape(B, H * W, ks * ks, C)
    vn = (lambda x, i, axis: torch.take_along_dim(x, i, dim=axis))(vf, nidx, 1).reshape(B, H * W, ks * ks, C)
    qf = q.reshape(B, H * W, C)
    scale = C ** (-0.5)
    logits = torch.einsum('bnc,bnkc->bnk', qf, kn) * scale
    p = _softmax(logits, axis=-1)
    o = torch.einsum('bnk,bnkc->bnc', p, vn) @ wo
    return o.reshape(B, H, W, C)
```

```cpp
#include <cuda_runtime.h>
#include <cuda_bf16.h>
#include <cuda.h>
#include <stdint.h>
#include <type_traits>

#define LDGPOS 0
#define PREFETCH 1

namespace {

constexpr int kC          = 192;
constexpr int kHW         = 224;
constexpr int kPixBytes   = kC * 2;
constexpr int kSlotBytes  = 84 * 128;
constexpr int kMidBytes   = 28 * 128;
constexpr int kOffMid     = 88 * 128;
constexpr int kSlotStride = 120 * 128;
constexpr int kRingChunk  = 208 * 128;
constexpr int kWChunk     = 192 * 128;
constexpr int kWBytes     = 3 * kWChunk;
constexpr uint32_t kSmemBase = 1024;
constexpr uint32_t s_ring = kSmemBase, s_m = s_ring + 3 * kRingChunk, s_wv = s_m + kWBytes, s_bar = s_wv + kWBytes;
constexpr uint32_t bar_b = s_bar, bar_m = s_bar + 24, bar_wv = s_bar + 48, bar_wop = s_bar + 56, bar_redo = s_bar + 64, bar_a = s_bar + 72, bar_q = s_bar + 80;
constexpr uint32_t s_zero = s_ring + 84 * 128, s_par = s_bar + 96, s_trace = s_bar + 256;
constexpr int kSmemBytes  = s_trace + 2048 - kSmemBase;
constexpr int kThreads    = 256;
constexpr int kGrid       = 132;
constexpr int kMPieces    = 144;
constexpr int kWPieces    = 72;
constexpr float kScaleLog2e = 0.07216878364870322f * 1.4426950408889634f;

struct Maps {
    CUtensorMap m[6];
    CUtensorMap wqkv;
    CUtensorMap wo;
};

__device__ __align__(1024) uint8_t g_wimg[2][2][kWBytes];
__device__ __align__(128) uint32_t g_cnt[2];

#define WO4(i) "=f"(d[i]), "=f"(d[i + 1]), "=f"(d[i + 2]), "=f"(d[i + 3])
#define RW4(i) "+f"(d[i]), "+f"(d[i + 1]), "+f"(d[i + 2]), "+f"(d[i + 3])

template <bool FIRST>
__device__ __forceinline__ void wgmma_n192(float (&d)[96], uint32_t a0, uint32_t a1, uint32_t a2, uint32_t a3, uint64_t descb) {
    if constexpr (FIRST) {
        asm volatile(
            "wgmma.mma_async.sync.aligned.m64n192k16.f32.bf16.bf16 "
            "{%0, %1, %2, %3, %4, %5, %6, %7, %8, %9, %10, %11, %12, %13, %14, %15, %16, %17, %18, %19, %20, %21, %22, %23, "
            "%24, %25, %26, %27, %28, %29, %30, %31, %32, %33, %34, %35, %36, %37, %38, %39, %40, %41, %42, %43, %44, %45, %46, %47, "
            "%48, %49, %50, %51, %52, %53, %54, %55, %56, %57, %58, %59, %60, %61, %62, %63, %64, %65, %66, %67, %68, %69, %70, %71, "
            "%72, %73, %74, %75, %76, %77, %78, %79, %80, %81, %82, %83, %84, %85, %86, %87, %88, %89, %90, %91, %92, %93, %94, %95}, "
            "{%96, %97, %98, %99}, %100, 0, 1, 1, 0;"
            : WO4(0), WO4(4), WO4(8), WO4(12), WO4(16), WO4(20), WO4(24), WO4(28), WO4(32), WO4(36), WO4(40), WO4(44),
              WO4(48), WO4(52), WO4(56), WO4(60), WO4(64), WO4(68), WO4(72), WO4(76), WO4(80), WO4(84), WO4(88), WO4(92)
            : "r"(a0), "r"(a1), "r"(a2), "r"(a3), "l"(descb));
    } else {
        asm volatile(
            "wgmma.mma_async.sync.aligned.m64n192k16.f32.bf16.bf16 "
            "{%0, %1, %2, %3, %4, %5, %6, %7, %8, %9, %10, %11, %12, %13, %14, %15, %16, %17, %18, %19, %20, %21, %22, %23, "
            "%24, %25, %26, %27, %28, %29, %30, %31, %32, %33, %34, %35, %36, %37, %38, %39, %40, %41, %42, %43, %44, %45, %46, %47, "
            "%48, %49, %50, %51, %52, %53, %54, %55, %56, %57, %58, %59, %60, %61, %62, %63, %64, %65, %66, %67, %68, %69, %70, %71, "
            "%72, %73, %74, %75, %76, %77, %78, %79, %80, %81, %82, %83, %84, %85, %86, %87, %88, %89, %90, %91, %92, %93, %94, %95}, "
            "{%96, %97, %98, %99}, %100, 1, 1, 1, 0;"
            : RW4(0), RW4(4), RW4(8), RW4(12), RW4(16), RW4(20), RW4(24), RW4(28), RW4(32), RW4(36), RW4(40), RW4(44),
              RW4(48), RW4(52), RW4(56), RW4(60), RW4(64), RW4(68), RW4(72), RW4(76), RW4(80), RW4(84), RW4(88), RW4(92)
            : "r"(a0), "r"(a1), "r"(a2), "r"(a3), "l"(descb));
    }
}

template <bool FIRST>
__device__ __forceinline__ void wgmma_n88(float (&d)[44], uint32_t a0, uint32_t a1, uint32_t a2, uint32_t a3, uint64_t descb) {
    if constexpr (FIRST) {
        asm volatile(
            "wgmma.mma_async.sync.aligned.m64n88k16.f32.bf16.bf16 "
            "{%0, %1, %2, %3, %4, %5, %6, %7, %8, %9, %10, %11, %12, %13, %14, %15, %16, %17, %18, %19, %20, %21, %22, %23, "
            "%24, %25, %26, %27, %28, %29, %30, %31, %32, %33, %34, %35, %36, %37, %38, %39, %40, %41, %42, %43}, "
            "{%44, %45, %46, %47}, %48, 0, 1, 1, 0;"
            : WO4(0), WO4(4), WO4(8), WO4(12), WO4(16), WO4(20), WO4(24), WO4(28), WO4(32), WO4(36), WO4(40)
            : "r"(a0), "r"(a1), "r"(a2), "r"(a3), "l"(descb));
    } else {
        asm volatile(
            "wgmma.mma_async.sync.aligned.m64n88k16.f32.bf16.bf16 "
            "{%0, %1, %2, %3, %4, %5, %6, %7, %8, %9, %10, %11, %12, %13, %14, %15, %16, %17, %18, %19, %20, %21, %22, %23, "
            "%24, %25, %26, %27, %28, %29, %30, %31, %32, %33, %34, %35, %36, %37, %38, %39, %40, %41, %42, %43}, "
            "{%44, %45, %46, %47}, %48, 1, 1, 1, 0;"
            : RW4(0), RW4(4), RW4(8), RW4(12), RW4(16), RW4(20), RW4(24), RW4(28), RW4(32), RW4(36), RW4(40)
            : "r"(a0), "r"(a1), "r"(a2), "r"(a3), "l"(descb));
    }
}

template <bool FIRST>
__device__ __forceinline__ void wgmma_n32(float (&d)[16], uint32_t a0, uint32_t a1, uint32_t a2, uint32_t a3, uint64_t descb) {
    if constexpr (FIRST) {
        asm volatile(
            "wgmma.mma_async.sync.aligned.m64n32k16.f32.bf16.bf16 "
            "{%0, %1, %2, %3, %4, %5, %6, %7, %8, %9, %10, %11, %12, %13, %14, %15}, "
            "{%16, %17, %18, %19}, %20, 0, 1, 1, 0;"
            : WO4(0), WO4(4), WO4(8), WO4(12)
            : "r"(a0), "r"(a1), "r"(a2), "r"(a3), "l"(descb));
    } else {
        asm volatile(
            "wgmma.mma_async.sync.aligned.m64n32k16.f32.bf16.bf16 "
            "{%0, %1, %2, %3, %4, %5, %6, %7, %8, %9, %10, %11, %12, %13, %14, %15}, "
            "{%16, %17, %18, %19}, %20, 1, 1, 1, 0;"
            : RW4(0), RW4(4), RW4(8), RW4(12)
            : "r"(a0), "r"(a1), "r"(a2), "r"(a3), "l"(descb));
    }
}

template <bool FIRST, int SEL>
__device__ __forceinline__ void wgmma_sp_n192_tb(float (&d)[96], uint32_t a0, uint32_t a1, uint32_t a2, uint32_t a3, uint64_t descb, uint32_t meta) {
    if constexpr (FIRST) {
        asm volatile(
            "wgmma.mma_async.sp.sync.aligned.m64n192k32.f32.bf16.bf16 "
            "{%0, %1, %2, %3, %4, %5, %6, %7, %8, %9, %10, %11, %12, %13, %14, %15, %16, %17, %18, %19, %20, %21, %22, %23, "
            "%24, %25, %26, %27, %28, %29, %30, %31, %32, %33, %34, %35, %36, %37, %38, %39, %40, %41, %42, %43, %44, %45, %46, %47, "
            "%48, %49, %50, %51, %52, %53, %54, %55, %56, %57, %58, %59, %60, %61, %62, %63, %64, %65, %66, %67, %68, %69, %70, %71, "
            "%72, %73, %74, %75, %76, %77, %78, %79, %80, %81, %82, %83, %84, %85, %86, %87, %88, %89, %90, %91, %92, %93, %94, %95}, "
            "{%96, %97, %98, %99}, %100, %101, %102, 0, 1, 1, 1;"
            : WO4(0), WO4(4), WO4(8), WO4(12), WO4(16), WO4(20), WO4(24), WO4(28), WO4(32), WO4(36), WO4(40), WO4(44),
              WO4(48), WO4(52), WO4(56), WO4(60), WO4(64), WO4(68), WO4(72), WO4(76), WO4(80), WO4(84), WO4(88), WO4(92)
            : "r"(a0), "r"(a1), "r"(a2), "r"(a3), "l"(descb), "r"(meta), "n"(SEL));
    } else {
        asm volatile(
            "wgmma.mma_async.sp.sync.aligned.m64n192k32.f32.bf16.bf16 "
            "{%0, %1, %2, %3, %4, %5, %6, %7, %8, %9, %10, %11, %12, %13, %14, %15, %16, %17, %18, %19, %20, %21, %22, %23, "
            "%24, %25, %26, %27, %28, %29, %30, %31, %32, %33, %34, %35, %36, %37, %38, %39, %40, %41, %42, %43, %44, %45, %46, %47, "
            "%48, %49, %50, %51, %52, %53, %54, %55, %56, %57, %58, %59, %60, %61, %62, %63, %64, %65, %66, %67, %68, %69, %70, %71, "
            "%72, %73, %74, %75, %76, %77, %78, %79, %80, %81, %82, %83, %84, %85, %86, %87, %88, %89, %90, %91, %92, %93, %94, %95}, "
            "{%96, %97, %98, %99}, %100, %101, %102, 1, 1, 1, 1;"
            : RW4(0), RW4(4), RW4(8), RW4(12), RW4(16), RW4(20), RW4(24), RW4(28), RW4(32), RW4(36), RW4(40), RW4(44),
              RW4(48), RW4(52), RW4(56), RW4(60), RW4(64), RW4(68), RW4(72), RW4(76), RW4(80), RW4(84), RW4(88), RW4(92)
            : "r"(a0), "r"(a1), "r"(a2), "r"(a3), "l"(descb), "r"(meta), "n"(SEL));
    }
}

#define TR(slot)
#define TRW(slot)
#define TRG(slot)
#define TRDUMP()

__device__ __forceinline__ void wg_fence() { asm volatile("wgmma.fence.sync.aligned;" ::: "memory"); }
__device__ __forceinline__ void wg_commit() { asm volatile("wgmma.commit_group.sync.aligned;" ::: "memory"); }
template <int N>
__device__ __forceinline__ void wg_wait() { asm volatile("wgmma.wait_group.sync.aligned %0;" ::"n"(N) : "memory"); }

template <int N>
__device__ __forceinline__ void pin(float (&d)[N]) {
#pragma unroll
    for (int i = 0; i < N; i++) asm volatile("" : "+f"(d[i])::"memory");
}
template <int N>
__device__ __forceinline__ void pin(uint32_t (&d)[N]) {
#pragma unroll
    for (int i = 0; i < N; i++) asm volatile("" : "+r"(d[i])::"memory");
}

__device__ __forceinline__ constexpr uint32_t desc_lo(uint32_t addr, uint32_t lbo) { return (addr >> 4) | ((lbo >> 4) << 16); }
__device__ __forceinline__ uint64_t desc_at(uint32_t lo, uint32_t byte_off) {
    return ((uint64_t)((1u << 30) | (1024u >> 4)) << 32) | (uint64_t)(lo + (byte_off >> 4));
}

__device__ __forceinline__ void mbar_init(uint32_t bar, uint32_t count) {
    asm volatile("mbarrier.init.shared::cta.b64 [%0], %1;" ::"r"(bar), "r"(count) : "memory");
}
__device__ __forceinline__ void mbar_expect_tx(uint32_t bar, uint32_t bytes) {
    asm volatile("mbarrier.arrive.expect_tx.shared::cta.b64 _, [%0], %1;" ::"r"(bar), "r"(bytes) : "memory");
}
__device__ __forceinline__ void mbar_arrive(uint32_t bar) {
    asm volatile("mbarrier.arrive.shared::cta.b64 _, [%0];" ::"r"(bar) : "memory");
}
__device__ __forceinline__ void mbar_wait(uint32_t bar, uint32_t parity) {
    asm volatile(
        "{\n.reg .pred p;\n"
        "W: mbarrier.try_wait.parity.shared::cta.b64 p, [%0], %1;\n"
        "@!p bra W;\n}\n"
        ::"r"(bar), "r"(parity) : "memory");
}
__device__ __forceinline__ bool elect() {
    uint32_t ok;
    asm volatile("{\n.reg .pred p;\nelect.sync _|p, 0xffffffff;\nselp.u32 %0, 1, 0, p;\n}\n" : "=r"(ok));
    return ok != 0;
}
__device__ __forceinline__ void turn_wait(int wg) { asm volatile("bar.sync %0, 256;" ::"r"(1 + wg) : "memory"); }
__device__ __forceinline__ void turn_pass(int wg) { asm volatile("bar.arrive %0, 256;" ::"r"(2 - wg) : "memory"); }
__device__ __forceinline__ void wg_sync(int wg) { asm volatile("bar.sync %0, 128;" ::"r"(3 + wg) : "memory"); }

__device__ __forceinline__ void tma_box(uint32_t dst, const CUtensorMap* map, uint32_t bar, int c0, int c2, int c3, int c4) {
    asm volatile(
        "cp.async.bulk.tensor.5d.shared::cluster.global.mbarrier::complete_tx::bytes [%0], [%1, {%3, %4, %5, %6, %7}], [%2];"
        ::"r"(dst), "l"(map), "r"(bar), "r"(c0), "r"(0), "r"(c2), "r"(c3), "r"(c4)
        : "memory");
}
__device__ __forceinline__ void tma_2d(uint32_t dst, const CUtensorMap* map, uint32_t bar, int c0, int c1) {
    asm volatile("cp.async.bulk.tensor.2d.shared::cluster.global.mbarrier::complete_tx::bytes [%0], [%1, {%3, %4}], [%2];"
                 ::"r"(dst), "l"(map), "r"(bar), "r"(c0), "r"(c1)
                 : "memory");
}
__device__ __forceinline__ void tma_3d(uint32_t dst, const CUtensorMap* map, uint32_t bar, int c0, int c1, int c2) {
    asm volatile("cp.async.bulk.tensor.3d.shared::cluster.global.mbarrier::complete_tx::bytes [%0], [%1, {%3, %4, %5}], [%2];"
                 ::"r"(dst), "l"(map), "r"(bar), "r"(c0), "r"(c1), "r"(c2)
                 : "memory");
}
__device__ __forceinline__ void tma_prefetch(const CUtensorMap* map, int c0, int c2, int c3, int c4) {
    asm volatile("cp.async.bulk.prefetch.tensor.5d.L2.global [%0, {%1, %2, %3, %4, %5}];"
                 ::"l"(map), "r"(c0), "r"(0), "r"(c2), "r"(c3), "r"(c4)
                 : "memory");
}
__device__ __forceinline__ void prefetch_map(const CUtensorMap* map) {
    asm volatile("prefetch.tensormap [%0];" ::"l"(map) : "memory");
}
__device__ __forceinline__ uint4 ldg_nc(const void* p) {
    uint4 v;
    asm volatile("ld.global.nc.v4.u32 {%0, %1, %2, %3}, [%4];" : "=r"(v.x), "=r"(v.y), "=r"(v.z), "=r"(v.w) : "l"(p));
    return v;
}
__device__ __forceinline__ uint4 ldg(const void* p) {
    uint4 v;
    asm volatile("ld.global.v4.u32 {%0, %1, %2, %3}, [%4];" : "=r"(v.x), "=r"(v.y), "=r"(v.z), "=r"(v.w) : "l"(p) : "memory");
    return v;
}
__device__ __forceinline__ void stg128(void* p, uint32_t a, uint32_t b, uint32_t c, uint32_t d) {
    asm volatile("st.global.v4.u32 [%0], {%1, %2, %3, %4};" ::"l"(p), "r"(a), "r"(b), "r"(c), "r"(d) : "memory");
}
__device__ __forceinline__ uint32_t pack_bf16(float lo, float hi) {
    uint32_t r;
    asm("cvt.rn.bf16x2.f32 %0, %1, %2;" : "=r"(r) : "f"(hi), "f"(lo));
    return r;
}
__device__ __forceinline__ float ex2(float x) {
    float y;
    asm("ex2.approx.ftz.f32 %0, %1;" : "=f"(y) : "f"(x));
    return y;
}
__device__ __forceinline__ float rcp(float x) {
    float y;
    asm("rcp.approx.ftz.f32 %0, %1;" : "=f"(y) : "f"(x));
    return y;
}
__device__ __forceinline__ void mma16816(float (&d)[4], uint32_t a0, uint32_t a1, uint32_t a2, uint32_t a3, uint32_t b0, uint32_t b1) {
    asm volatile("mma.sync.aligned.m16n8k16.row.col.f32.bf16.bf16.f32 {%0, %1, %2, %3}, {%4, %5, %6, %7}, {%8, %9}, {%0, %1, %2, %3};"
                 : "+f"(d[0]), "+f"(d[1]), "+f"(d[2]), "+f"(d[3])
                 : "r"(a0), "r"(a1), "r"(a2), "r"(a3), "r"(b0), "r"(b1));
}
__device__ __forceinline__ uint32_t lds_volatile(uint32_t addr) {
    uint32_t v;
    asm volatile("ld.volatile.shared.u32 %0, [%1];" : "=r"(v) : "r"(addr) : "memory");
    return v;
}

__device__ __forceinline__ int window_start(int i_shifted) { return min(max(i_shifted, 0), 105); }

struct Work {
    int cu, cv;
    uint32_t su, sv;
    int iu, iv;
    int corner, ntiles;
    const CUtensorMap* map;
    int c0, c3;
    __device__ __forceinline__ int origin_u(int u) const { return min(max(u + cu, 0), 98); }
    __device__ __forceinline__ void pixel_offsets(int u, int v, int j, uint32_t& o0, uint32_t& o1) const {
        const uint32_t base = (u + window_start(u + cu) + (cu ? 0 : 7)) * su + j * 16 + (v + (cv ? 0 : 7)) * sv;
        o0 = base + window_start(v + cv) * sv;
        o1 = base + (window_start(v + 1 + cv) + 1) * sv;
    }
    __device__ __forceinline__ void load_first(int u, int v, int c) const {
        mbar_expect_tx(bar_a, kSlotBytes);
        tma_box(s_ring + c * kRingChunk, map, bar_a, c0 + 64 * c, origin_u(u), c3, v + cv);
    }
    __device__ __forceinline__ void load_rest(int u, int v, int slot, int c) const {
        mbar_expect_tx(bar_b + 8 * c, kSlotBytes + kMidBytes);
        tma_box(s_ring + c * kRingChunk + slot * kSlotStride, map, bar_b + 8 * c, c0 + 64 * c, origin_u(u), c3, v + cv + 8);
        tma_box(s_ring + c * kRingChunk + kOffMid + 512, map + 1, bar_b + 8 * c, c0 + 64 * c, origin_u(u), c3, v + cv + 6);
    }
    __device__ __forceinline__ void prefetch_rows(int u, int v) const { tma_prefetch(map + 2, c0, u, c3, v + cv); }
};

__device__ __forceinline__ Work decode_work(const Maps& maps, int c) {
    Work w;
    const int idx = c >> 2, ypar = (c >> 1) & 1, xpar = c & 1;
    const bool transposed = (idx >> 2) == 7;
    w.corner = idx == 32;
    w.cu = 6 * (transposed ? ypar : xpar) - 6;
    w.cv = 6 * (transposed ? xpar : ypar) - 6;
    w.su = transposed ? kHW * kPixBytes : kPixBytes;
    w.sv = transposed ? kPixBytes : kHW * kPixBytes;
    w.iu = idx < 28 ? 8 * (idx >> 1) : 96 + 4 * (idx & 2);
    w.iv = w.corner ? 96 : 48 * (idx & 1);
    w.ntiles = w.corner ? 4 : 6;
    w.map = &maps.m[transposed ? 3 : 0];
    w.c0 = xpar * kC;
    w.c3 = ypar;
    return w;
}

struct RawX { uint4 a[6], b[6]; };
__device__ __forceinline__ void load_raw(RawX& r, const uint8_t* base, uint32_t o0, uint32_t o1) {
    __syncwarp();
#pragma unroll
    for (int c = 0; c < 6; c++) { r.a[c] = ldg(base + o0 + c * 64); r.b[c] = ldg(base + o1 + c * 64); }
    __syncwarp();
}
__device__ __forceinline__ void raw_to_frags(const RawX& r, uint32_t zero, uint32_t (&f)[48]) {
#pragma unroll
    for (int c = 0; c < 6; c++) {
        f[8 * c + 0] = r.a[c].x ^ zero; f[8 * c + 2] = r.a[c].z ^ zero; f[8 * c + 4] = r.a[c].y ^ zero; f[8 * c + 6] = r.a[c].w ^ zero;
        f[8 * c + 1] = r.b[c].x ^ zero; f[8 * c + 3] = r.b[c].z ^ zero; f[8 * c + 5] = r.b[c].y ^ zero; f[8 * c + 7] = r.b[c].w ^ zero;
    }
}
__device__ __forceinline__ void acc_to_frags(const float (&d)[96], uint32_t (&f)[48]) {
#pragma unroll
    for (int i = 0; i < 48; i++) f[i] = pack_bf16(d[2 * i], d[2 * i + 1]);
}

template <int NBARS, int GROUPS, class F>
__device__ __forceinline__ void proj_gemm(float (&d)[96], const uint32_t (&a)[48], uint32_t wdesc, uint32_t wbar, F after) {
#pragma unroll
    for (int c = 0; c < 3; c++) {
        if (c < NBARS) { mbar_wait(wbar + 8 * c, 0); wg_fence(); }
#pragma unroll
        for (int s = 4 * c; s < 4 * c + 4; s++) {
            if (s == 0) wgmma_n192<true>(d, a[4 * s], a[4 * s + 1], a[4 * s + 2], a[4 * s + 3], desc_at(wdesc, c * kWChunk + (s & 3) * 32));
            else wgmma_n192<false>(d, a[4 * s], a[4 * s + 1], a[4 * s + 2], a[4 * s + 3], desc_at(wdesc, c * kWChunk + (s & 3) * 32));
            if (s >= 12 - GROUPS) wg_commit();
            after(s);
        }
    }
}
__device__ __forceinline__ void pack_out(const float (&acc)[96], float i0, float i1, uint32_t (&po)[48]) {
#pragma unroll
    for (int g = 0; g < 6; g++)
#pragma unroll
        for (int q = 0; q < 4; q++) {
            po[8 * g + q] = pack_bf16(acc[16 * g + 4 * q] * i0, acc[16 * g + 4 * q + 1] * i0);
            po[8 * g + 4 + q] = pack_bf16(acc[16 * g + 4 * q + 2] * i1, acc[16 * g + 4 * q + 3] * i1);
        }
}
__device__ __forceinline__ void store_one(bool on, uint8_t* p0, uint8_t* p1, const uint32_t (&po)[48], int n) {
    asm volatile("{\n.reg .pred p;\nsetp.ne.u32 p, %5, 0;\nbar.warp.sync 0xffffffff;\n@p st.global.v4.u32 [%0], {%1, %2, %3, %4};\n}\n"
                 ::"l"(((n & 1) ? p1 : p0) + (n >> 1) * 64), "r"(po[4 * n]), "r"(po[4 * n + 1]), "r"(po[4 * n + 2]), "r"(po[4 * n + 3]), "r"((uint32_t)on) : "memory");
}
__device__ __forceinline__ void store_out(uint8_t* out, uint32_t o0, uint32_t o1, const uint32_t (&po)[48]) {
#pragma unroll
    for (int g = 0; g < 6; g++) {
        stg128(out + o0 + g * 64, po[8 * g], po[8 * g + 1], po[8 * g + 2], po[8 * g + 3]);
        stg128(out + o1 + g * 64, po[8 * g + 4], po[8 * g + 5], po[8 * g + 6], po[8 * g + 7]);
    }
}

struct Masks {
    uint32_t h;
    uint32_t meta[2];
};

__device__ __forceinline__ void make_u_masks(Masks& m, int offu, int j) {
    m.h = (((1u << offu) - 1u) * 0x4081u) >> j;
    uint32_t y = __byte_perm(m.h, 0, 0x4140);
    y = (y | (y << 4)) & 0x0f0f0f0fu;
    y = (y | (y << 2)) & 0x33333333u;
    y = (y | (y << 1)) & 0x55555555u;
    m.meta[0] = __byte_perm(y | 0x8888u, 0, 0x1010);
    m.meta[1] = __byte_perm((y >> (8 - (j & 2))) | 0x8888u, 0, 0x1010);
}

template <int N>
__device__ __forceinline__ float tree_max(const float (&v)[N]) {
    float t[N];
#pragma unroll
    for (int i = 0; i < N; i++) t[i] = v[i];
#pragma unroll
    for (int w = 1; w < N; w *= 2)
#pragma unroll
        for (int i = 0; i + w < N; i += 2 * w) t[i] = fmaxf(t[i], t[i + w]);
    return t[0];
}
template <int N>
__device__ __forceinline__ float tree_sum(const float (&v)[N]) {
    float t[N];
#pragma unroll
    for (int i = 0; i < N; i++) t[i] = v[i];
#pragma unroll
    for (int w = 1; w < N; w *= 2)
#pragma unroll
        for (int i = 0; i + w < N; i += 2 * w) t[i] += t[i + w];
    return t[0];
}

template <int B, int LO, int HI>
__device__ __forceinline__ void pick(uint32_t h, int t0, int t1, bool on, const float* s, float& v0, float& v1) {
    asm("{\n.reg .pred p, q0, q1;\n.reg .b32 t;\nand.b32 t, %6, %7;\nsetp.ne.u32 p, t, 0;\n"
        "setp.ne.u32 q0, %8, 0;\nsetp.ne.u32 q1, %9, 0;\n"
        "@q0 selp.f32 %0, %3, %2, p;\n@q1 selp.f32 %1, %5, %4, p;\n}\n"
        : "+f"(v0), "+f"(v1)
        : "f"(s[0]), "f"(s[1]), "f"(s[2]), "f"(s[3]), "r"(h), "n"(1 << ((4 * B) % 7)),
          "r"((uint32_t)(on && (LO < -3 || t0 > LO) && (HI >= 49 || t0 <= HI))),
          "r"((uint32_t)(on && (LO < -3 || t1 > LO) && (HI >= 49 || t1 <= HI))));
}
template <int B, class F>
__device__ __forceinline__ void for_blocks(F f) {
    if constexpr (B > 0) { for_blocks<B - 1>(f); f(std::integral_constant<int, B - 1>{}); }
}
__device__ __forceinline__ void gather_first(const float (&sA)[44], uint32_t h, int t0, int t1, float (&v0)[14], float (&v1)[14]) {
#pragma unroll
    for (int b = 0; b < 14; b++) v0[b] = v1[b] = __int_as_float(0xff800000);
    for_blocks<11>([&](auto B) {
        constexpr int b = B.value < 8 ? (B.value >> 1) + 7 * (B.value & 1) : B.value - 4;
        pick<b, -4, 4 * b>(h, t0, t1, true, &sA[4 * b], v0[b], v1[b]);
    });
}
__device__ __forceinline__ void gather_last(const float (&sB)[44], uint32_t h, int t0, int t1, float (&v0)[14], float (&v1)[14]) {
    for_blocks<11>([&](auto B) {
        constexpr int b = B.value < 8 ? (B.value >> 1) + 7 * (B.value & 1) : B.value - 4;
        pick<b, 4 * b + 7, 49>(h, t0, t1, true, &sB[4 * b], v0[b], v1[b]);
    });
}
__device__ __forceinline__ void gather_mid(const float (&sE)[16], uint32_t h, int t0, int t1, int j, float (&v0)[14], float (&v1)[14]) {
    for_blocks<4>([&](auto B) {
        constexpr int b = 10 + B.value;
        pick<b, 4 * b - 49, 4 * b>(h, t0, t1, b > 10 || j >= 2, &sE[4 * B.value], v0[b], v1[b]);
    });
}
__device__ __forceinline__ float quad_max(float m) {
    m = fmaxf(m, __shfl_xor_sync(0xffffffffu, m, 1));
    return fmaxf(m, __shfl_xor_sync(0xffffffffu, m, 2));
}
__device__ __forceinline__ float quad_sum(float s) {
    s += __shfl_xor_sync(0xffffffffu, s, 1);
    return s + __shfl_xor_sync(0xffffffffu, s, 2);
}
__device__ __forceinline__ void exp_scatter(float (&v0)[14], float (&v1)[14], float m0, float m1, int tw, int lane, uint32_t (&pa)[28]) {
    const int j = lane & 3;
    const int src1 = (lane & ~3) | ((j & 1) << 1) | (j >> 1);
    const int src2 = src1 ^ 1;
    const uint32_t selr = j < 2 ? 0x5410u : 0x1054u;
    const uint32_t selr8 = j < 2 ? 0x7632u : 0x3276u;
    const bool even = (j & 1) == 0;
#pragma unroll
    for (int b = 0; b < 14; b++) { v0[b] = ex2(v0[b] - m0); v1[b] = ex2(v1[b] - m1); }
#pragma unroll
    for (int b = 0; b < 14; b += 2) {
        const uint32_t x0 = pack_bf16(v0[b], v1[b]), x1 = pack_bf16(v0[b + 1], v1[b + 1]);
        const uint32_t u = __shfl_sync(0xffffffffu, even ? x0 : x1, src1);
        const uint32_t w = __shfl_sync(0xffffffffu, even ? x1 : x0, src2);
        if (b < 12)
            asm("{\n.reg .pred p, q;\nsetp.ne.u32 p, %8, 0;\nsetp.ne.u32 q, %9, 0;\n"
                "@p prmt.b32 %0, %4, %5, %6;\n@p prmt.b32 %1, %4, %5, %7;\n"
                "@q prmt.b32 %2, %4, %5, %6;\n@q prmt.b32 %3, %4, %5, %7;\n}\n"
                : "+r"(pa[b]), "+r"(pa[b + 1]), "+r"(pa[16 + b]), "+r"(pa[17 + b])
                : "r"(u), "r"(w), "r"(selr), "r"(selr8), "r"((uint32_t)(4 * b >= tw && (b < 10 || j == 0))), "r"((uint32_t)(4 * b < tw)));
        if (b >= 10) { pa[b + 2] = __byte_perm(u, w, selr); pa[b + 3] = __byte_perm(u, w, selr8); }
    }
}

__device__ __forceinline__ uint32_t wimg_offset(uint32_t row, uint32_t s, uint32_t j) {
    return (s >> 2) * kWChunk + row * 128 + (((2 * (s & 3) + (j >> 1)) ^ (row & 7)) << 4) + (j & 1) * 8;
}

struct MPiece { uint4 A[2][6], B[2][6]; };
__device__ __forceinline__ void m_piece_load(MPiece& m, const uint8_t* wqkv, uint32_t pc, uint32_t lane) {
    const uint32_t r8 = lane >> 2, j = lane & 3, s = pc % 12;
    const uint8_t* pa = wqkv + (16 * (pc / 12) + r8) * 1152 + j * 16;
    const uint8_t* pb = wqkv + (32 * (s >> 1) + 2 * (s & 1) + 8 * (r8 & 2) + (r8 & 5)) * 1152 + j * 16;
#pragma unroll
    for (int c = 0; c < 6; c++)
#pragma unroll
        for (int h = 0; h < 2; h++) { m.A[h][c] = ldg_nc(pa + 384 + h * 8 * 1152 + c * 64); m.B[h][c] = ldg_nc(pb + h * 8 * 1152 + c * 64); }
}
__device__ __forceinline__ void st_pair(uint32_t par, uint32_t off, uint32_t a, uint32_t b) {
    asm volatile("st.relaxed.gpu.global.v2.u32 [%0], {%1, %2};" ::"l"(g_wimg[par][0] + off), "r"(a ? a : 0x8000u), "r"(b) : "memory");
    asm volatile("st.relaxed.gpu.global.v2.u32 [%0], {%1, %1};" ::"l"(g_wimg[par ^ 1][0] + off), "r"(0) : "memory");
}
__device__ __forceinline__ void m_piece_finish(const MPiece& m, uint32_t pc, uint32_t lane, uint32_t par) {
    float d[2][4];
#pragma unroll
    for (int i = 0; i < 8; i++) (&d[0][0])[i] = 0.f;
#pragma unroll
    for (int c = 0; c < 6; c++)
#pragma unroll
        for (int nb = 0; nb < 2; nb++) {
            mma16816(d[nb], m.A[0][c].x, m.A[1][c].x, m.A[0][c].y, m.A[1][c].y, m.B[nb][c].x, m.B[nb][c].y);
            mma16816(d[nb], m.A[0][c].z, m.A[1][c].z, m.A[0][c].w, m.A[1][c].w, m.B[nb][c].z, m.B[nb][c].w);
        }
    const uint32_t off = wimg_offset(16 * (pc / 12) + (lane >> 2), pc % 12, lane & 3);
#pragma unroll
    for (int hf = 0; hf < 2; hf++)
        st_pair(par, off + hf * 1024, pack_bf16(d[0][2 * hf] * kScaleLog2e, d[0][2 * hf + 1] * kScaleLog2e),
                pack_bf16(d[1][2 * hf] * kScaleLog2e, d[1][2 * hf + 1] * kScaleLog2e));
}

__device__ __forceinline__ void ldsm4(uint32_t (&r)[4], uint32_t addr) {
    asm volatile("ldmatrix.sync.aligned.m8n8.x4.shared.b16 {%0, %1, %2, %3}, [%4];" : "=r"(r[0]), "=r"(r[1]), "=r"(r[2]), "=r"(r[3]) : "r"(addr) : "memory");
}
__device__ __forceinline__ void ldsm4_t(uint32_t (&r)[4], uint32_t addr) {
    asm volatile("ldmatrix.sync.aligned.m8n8.x4.trans.shared.b16 {%0, %1, %2, %3}, [%4];" : "=r"(r[0]), "=r"(r[1]), "=r"(r[2]), "=r"(r[3]) : "r"(addr) : "memory");
}
__device__ __forceinline__ void w_piece(uint32_t s_wo, uint32_t s_wvr, uint32_t pw, uint32_t lane, uint32_t par) {
    float d[2][2][4];
#pragma unroll
    for (int i = 0; i < 16; i++) (&d[0][0][0])[i] = 0.f;
    const uint32_t rr = lane & 7, mi = lane >> 3;
    const uint32_t kr = 4 * (rr >> 1) + (mi & 2) + (rr & 1);
    const uint32_t pb = s_wvr + kr * 128 + (((mi & 1) ^ (kr & 7)) << 4);
    uint32_t pa = s_wo + (4 * (mi & 2) + rr) * 64 + (((mi & 1) ^ (rr >> 1)) << 4);
#pragma unroll 1
    for (uint32_t s = 0; s < 12; s++, pa += 1024) {
        uint32_t bq[4];
        ldsm4(bq, (pb + (s >> 2) * 2048) ^ ((s & 3) << 5));
#pragma unroll
        for (int mt = 0; mt < 2; mt++) {
            uint32_t aq[4];
            ldsm4_t(aq, pa ^ (mt << 5));
            mma16816(d[mt][0], aq[0], aq[1], aq[2], aq[3], bq[0], bq[1]);
            mma16816(d[mt][1], aq[0], aq[1], aq[2], aq[3], bq[2], bq[3]);
        }
    }
    const uint32_t r8 = lane >> 2;
    const uint32_t off = wimg_offset(32 * (pw / 12) + 8 * (r8 >> 1) + (r8 & 1), pw % 12, lane & 3);
#pragma unroll
    for (int mt = 0; mt < 2; mt++)
#pragma unroll
        for (int hf = 0; hf < 2; hf++)
            st_pair(par, kWBytes + (off ^ ((4 * mt + 2 * hf) * 144)), pack_bf16(d[mt][0][2 * hf], d[mt][0][2 * hf + 1]),
                    pack_bf16(d[mt][1][2 * hf], d[mt][1][2 * hf + 1]));
}

__device__ __forceinline__ uint32_t ld_relaxed(const uint32_t* p) {
    uint32_t v;
    asm volatile("ld.relaxed.gpu.global.u32 %0, [%1];" : "=r"(v) : "l"(p) : "memory");
    return v;
}
__device__ __forceinline__ void count_up(uint32_t* p) {
    asm volatile("red.relaxed.gpu.global.add.u32 [%0], %1;" ::"l"(p), "r"(1) : "memory");
}
__device__ __forceinline__ void await_count(const uint32_t* p, uint32_t target) {
#pragma unroll 1
    for (uint32_t spins = 0; spins < (1u << 20); spins++)
        if (ld_relaxed(p) >= target) break;
}
__device__ __forceinline__ bool image_complete(uint32_t img, int wg) {
    uint32_t addr = img + (threadIdx.x & 127) * 32 + (threadIdx.x & 12) * 2, lo = 1;
#pragma unroll 1
    for (int c = 0; c < 3; c++, addr += kWChunk)
#pragma unroll
        for (int q = 0; q < 6; q++) lo = min(lo, lds_volatile(addr + q * 4096));
    uint32_t ok;
    asm volatile("{\n.reg .pred p;\nsetp.ne.u32 p, %1, 0;\nbarrier.cta.red.and.aligned.pred p, %2, 128, p;\nselp.u32 %0, 1, 0, p;\n}\n"
                 : "=r"(ok) : "r"(lo), "r"(3 + wg) : "memory");
    return ok != 0;
}
__device__ __forceinline__ void bulk_g2s(uint32_t dst, const void* src, uint32_t bytes, uint32_t bar) {
    asm volatile("cp.async.bulk.shared::cluster.global.mbarrier::complete_tx::bytes [%0], [%1], %2, [%3];"
                 ::"r"(dst), "l"(src), "r"(bytes), "r"(bar)
                 : "memory");
}

__global__ void __launch_bounds__(kThreads, 1)
nat_fused_kernel(const __grid_constant__ Maps maps, const uint8_t* __restrict__ x, const uint8_t* __restrict__ wqkv, uint8_t* __restrict__ out) {
    extern __shared__ __align__(1024) uint8_t smem_raw[];
    const int tid = threadIdx.x, lane = tid & 31;
    const int warp = __shfl_sync(0xffffffffu, tid >> 5, 0);
    const int wg = warp >> 2, wq = warp & 3, r8 = lane >> 2, j = lane & 3;
    const int cta = blockIdx.x;
    TRG(0); TR(0);
    const bool has_piece = warp == 4 || (warp == 6 && cta >= kGrid - (kMPieces - kGrid));
    const int pc = warp == 4 ? cta : cta + (kMPieces - kGrid);
    MPiece mp;
    if (has_piece) m_piece_load(mp, wqkv, pc, lane);
    uint32_t launch = 0;
    if (warp == 4 || warp == 6) launch = ld_relaxed(&g_cnt[has_piece ? 0 : 1]);
    const Work w = decode_work(maps, cta);
    if (warp == 7) {
        if (elect()) {
#pragma unroll 1
            for (int i = 0; i < 11; i++) mbar_init(s_bar + 8 * i, i < 9 ? 1 : i - 6);
            asm volatile("fence.mbarrier_init.release.cluster;" ::: "memory");
            if ((uint32_t)__cvta_generic_to_shared(smem_raw) != kSmemBase) __trap();
        }
    } else if (warp < 3) {
#pragma unroll
        for (int r = 0; r < 3; r++)
            asm volatile("st.shared.v4.u32 [%0], {%1, %1, %1, %1};" ::"r"(s_ring + warp * kRingChunk + (r == 0 ? 84 : r == 1 ? 88 : 204) * 128 + lane * 16), "r"(0) : "memory");
        asm volatile("fence.proxy.async.shared::cta;" ::: "memory");
        prefetch_map(w.map + warp);
    }
    int tu = w.iu, tv = w.iv + 8 * wg;
    const int du1 = w.corner ? 8 * wg : 0, dv1 = 8 - 2 * du1, du2 = w.corner ? 8 : 0, dv2 = 16 - 2 * du2;
    uint32_t o0, o1;
    w.pixel_offsets(tu + r8, tv + 2 * wq, j, o0, o1);
    __syncthreads();
    TR(1);

    if (wg == 1) {
        if (has_piece) {
            launch /= kMPieces;
            m_piece_finish(mp, pc, lane, launch & 1);
            __syncwarp();
            if (warp == 4) TRW(0);
            if (elect()) {
                count_up(&g_cnt[0]);
                if (warp == 4) {
                    asm volatile("st.shared.u32 [%0], %1;" ::"r"(s_par), "r"(launch & 1) : "memory");
                    await_count(&g_cnt[0], (launch + 1) * kMPieces);
                    TRW(5);
#pragma unroll 1
                    for (int c = 0; c < 3; c++) {
                        mbar_expect_tx(bar_m + 8 * c, kWChunk);
                        bulk_g2s(s_m + c * kWChunk, g_wimg[launch & 1][0] + c * kWChunk, kWChunk, bar_m + 8 * c);
                    }
                }
            }
        } else if (warp == 6) {
            if (cta < kWPieces) {
                const uint32_t s_wo = s_wv, s_wvr = s_wv + 12288;
                if (elect()) {
                    mbar_expect_tx(bar_wop, 12288 + 6144);
                    tma_2d(s_wo, &maps.wo, bar_wop, 32 * (cta / 12), 0);
                    tma_3d(s_wvr, &maps.wqkv, bar_wop, 0, 16 * (cta % 12), 6);
                }
                mbar_wait(bar_wop, 0);
                TRW(2);
                w_piece(s_wo, s_wvr, cta, lane, (launch / kWPieces) & 1);
                __syncwarp();
                if (elect()) count_up(&g_cnt[1]);
                TRW(3);
            }
        } else if (warp == 5) {
            mbar_wait(bar_q, 0);
            TRW(6);
            if (elect()) {
#pragma unroll 1
                for (int c = 0; c < 3; c++) w.load_first(w.iu, w.iv, c);
            }
            mbar_wait(bar_a, 0);
            TRW(7);
            if (elect()) {
#pragma unroll 1
                for (int c = 0; c < 3; c++) w.load_rest(w.iu, w.iv, 1, c);
            }
            TRW(8);
        }
        __syncwarp();
        mbar_wait(bar_b, 0);
    }
    uint32_t fa[48];
    {
        RawX raw;
        load_raw(raw, x, o0, o1);
        if (warp == 4 && elect()) {
            await_count(&g_cnt[1], (launch + 1) * kWPieces);
            mbar_wait(bar_b + 16, 0);
            mbar_expect_tx(bar_wv, kWBytes);
            bulk_g2s(s_wv, g_wimg[launch & 1][1], kWBytes, bar_wv);
            TRW(9);
            if (PREFETCH) w.prefetch_rows(w.iu + du2, w.iv + dv2 + 3);
        }
        __syncwarp();
        raw_to_frags(raw, lds_volatile(s_zero), fa);
        pin(fa);
        if (wg == 0 && lane == 0) mbar_arrive(bar_q);
    }
    TR(2);

    constexpr uint32_t mdesc = desc_lo(s_m, 16), wdesc = desc_lo(s_wv, 16);
    constexpr uint32_t kdE = desc_lo(s_ring + kOffMid, 16), vdE = desc_lo(s_ring + kOffMid, kRingChunk);
    const uint32_t kdA = desc_lo(s_ring, 16) + wg * (kSlotStride >> 4), kdB = desc_lo(s_ring + kSlotStride, 16) - wg * (kSlotStride >> 4);
    constexpr uint32_t kToV = desc_lo(0, kRingChunk) - desc_lo(0, 16);

    float acc[96];
    uint32_t po[48];
    uint32_t c0, c1;
    asm volatile("" : "=r"(c0), "=r"(c1));
#pragma unroll
    for (int q = 0; q < 48; q++) asm volatile("" : "=r"(po[q]));
#pragma unroll 1
    for (int i = wg; i < w.ntiles; i += 2) {
        const bool first = i == 0, last = i == w.ntiles - 1;

        TR(8 + 16 * k);
        uint8_t *p0 = out + c0, *p1 = out + c1;
        const bool on = i >= 2;
        store_one(on, p0, p1, po, 0);
#pragma unroll 1
        for (uint32_t redo = 0;; redo++) {
            if (!first && !redo) turn_wait(wg);
            proj_gemm<3, 7>(acc, fa, mdesc, bar_m, [&](int s) { if (s >= 7 && s < 11) store_one(on, p0, p1, po, s - 6); });
            if (!first && !redo) turn_pass(wg);
            TR(9 + 16 * k);
            if (on) break;
            if (i == 1) mbar_wait(bar_wv, 0);
            if (image_complete(s_m + i * kWBytes, wg) || redo == 4096) break;
            wg_wait<0>();
            wg_sync(wg);
            if (wq == 0 && elect()) {
                mbar_expect_tx(bar_redo - 8 * wg, kWBytes);
                bulk_g2s(s_m + i * kWBytes, g_wimg[lds_volatile(s_par)][i], kWBytes, bar_redo - 8 * wg);
            }
            mbar_wait(bar_redo - 8 * wg, (redo + (wg && cta < kWPieces)) & 1);
        }
        store_one(on, p0, p1, po, 5);
        wg_wait<6>(); store_one(on, p0, p1, po, 6);
        wg_wait<5>(); store_one(on, p0, p1, po, 7);
        wg_wait<4>(); store_one(on, p0, p1, po, 8);
        wg_wait<3>(); store_one(on, p0, p1, po, 9);
        wg_wait<2>(); store_one(on, p0, p1, po, 10);
        wg_wait<1>(); store_one(on, p0, p1, po, 11);
        TR(10 + 16 * k);
        c0 = o0; c1 = o1;
        w.pixel_offsets(tu + du2 + r8, tv + dv2 + 2 * wq, j, o0, o1);
        if (i + 2 >= w.ntiles) o0 = o1 = 0;
        wg_wait<0>();
        pin(acc);
        TR(11 + 16 * k);
        acc_to_frags(acc, fa);
        pin(fa);

        float sA[44], sE[16], sB[44];
        RawX nxt;
        if (!first) turn_wait(wg);
        mbar_wait(bar_a, w.corner ? i >> 1 : 0);
        wg_fence();
#pragma unroll
        for (int s = 0; s < 12; s++)
            if (s == 0) wgmma_n88<true>(sA, fa[4 * s], fa[4 * s + 1], fa[4 * s + 2], fa[4 * s + 3], desc_at(kdA, (s >> 2) * kRingChunk + (s & 3) * 32));
            else wgmma_n88<false>(sA, fa[4 * s], fa[4 * s + 1], fa[4 * s + 2], fa[4 * s + 3], desc_at(kdA, (s >> 2) * kRingChunk + (s & 3) * 32));
        wg_commit();
        if (!first) turn_pass(wg);
        TR(12 + 16 * k);
        if (LDGPOS == 0) load_raw(nxt, x, o0, o1);
        const int vq = tv + w.cv + 2 * wq;
        const int off0 = window_start(vq) - (tv + w.cv), off1 = window_start(vq + 1) - (tv + w.cv);
        const int t0 = 7 * off0 - j, t1 = 7 * off1 - j, tw = 7 * (off0 & ~1) - 2 * j;
        Masks mk;
        make_u_masks(mk, window_start(tu + w.cu + r8) - w.origin_u(tu), j);
        float v0[14], v1[14];
        uint32_t pa[28];
#pragma unroll
        for (int q = 0; q < 28; q++) pa[q] = 0;
        wg_wait<0>();
        pin(sA);
        gather_first(sA, mk.h, t0, t1, v0, v1);
        pin(v0); pin(v1);
        if (!first) turn_wait(wg);
#pragma unroll
        for (int c = 0; c < 3; c++) {
            mbar_wait(bar_b + 8 * c, wg);
            TR(64 + 4 * k + c);
            wg_fence();
#pragma unroll
            for (int s = 4 * c; s < 4 * c + 4; s++)
                if (s == 0) wgmma_n88<true>(sB, fa[4 * s], fa[4 * s + 1], fa[4 * s + 2], fa[4 * s + 3], desc_at(kdB, c * kRingChunk + (s & 3) * 32));
                else wgmma_n88<false>(sB, fa[4 * s], fa[4 * s + 1], fa[4 * s + 2], fa[4 * s + 3], desc_at(kdB, c * kRingChunk + (s & 3) * 32));
        }
        wg_commit();
#pragma unroll
        for (int s = 0; s < 12; s++)
            if (s == 0) wgmma_n32<true>(sE, fa[4 * s], fa[4 * s + 1], fa[4 * s + 2], fa[4 * s + 3], desc_at(kdE, (s >> 2) * kRingChunk + (s & 3) * 32));
            else wgmma_n32<false>(sE, fa[4 * s], fa[4 * s + 1], fa[4 * s + 2], fa[4 * s + 3], desc_at(kdE, (s >> 2) * kRingChunk + (s & 3) * 32));
        wg_commit();
        if (!last) turn_pass(wg);
        TR(13 + 16 * k);
        if (LDGPOS == 1) load_raw(nxt, x, o0, o1);
        wg_wait<1>();
        pin(sB);
        gather_last(sB, mk.h, t0, t1, v0, v1);
        wg_wait<0>();
        pin(sE);
        TR(14 + 16 * k);
        gather_mid(sE, mk.h, t0, t1, j, v0, v1);
        const float m0 = quad_max(tree_max(v0)), m1 = quad_max(tree_max(v1));

        exp_scatter(v0, v1, m0, m1, tw, lane, pa);
        pin(pa);
        TR(15 + 16 * k);
        if (LDGPOS == 2) load_raw(nxt, x, o0, o1);

        if (!last) turn_wait(wg + (pa[12] >> 31));
        wg_fence();
        wgmma_sp_n192_tb<true, 0>(acc, pa[0], pa[1], pa[2], pa[3], desc_at(kdA + kToV, 0), mk.meta[0]);
        wgmma_sp_n192_tb<false, 1>(acc, pa[4], pa[5], pa[6], pa[7], desc_at(kdA + kToV, 4096), mk.meta[0]);
        wgmma_sp_n192_tb<false, 0>(acc, pa[8], pa[9], pa[10], pa[11], desc_at(kdA + kToV, 8192), mk.meta[1]);
        wgmma_sp_n192_tb<false, 1>(acc, pa[12], pa[13], pa[14], pa[15], desc_at(vdE, 0), mk.meta[1]);
        wg_commit();
        wgmma_sp_n192_tb<false, 0>(acc, pa[16], pa[17], pa[18], pa[19], desc_at(kdB + kToV, 0), mk.meta[0]);
        wgmma_sp_n192_tb<false, 1>(acc, pa[20], pa[21], pa[22], pa[23], desc_at(kdB + kToV, 4096), mk.meta[0]);
        wgmma_sp_n192_tb<false, 0>(acc, pa[24], pa[25], pa[26], pa[27], desc_at(kdB + kToV, 8192), mk.meta[1]);
        wg_commit();
        if (!last) turn_pass(wg);
        TR(16 + 16 * k);
        const float s0 = tree_sum(v0), s1 = tree_sum(v1);
        if (LDGPOS == 3) load_raw(nxt, x, o0, o1);
        wg_wait<1>();
        wg_sync(wg);
        if (!last && elect()) {
            if (wq < 3) w.load_rest(tu + du1, tv + dv1, wg, wq);
            else if (PREFETCH) w.prefetch_rows(tu + du1 + du2, tv + dv1 + dv2 + 3);
        }
        __syncwarp();
        TR(17 + 16 * k);
        wg_wait<0>();
        pin(acc);
        TR(18 + 16 * k);
        if (w.corner && i == 1) {
            wg_sync(wg);
            if (wq < 3 && elect()) w.load_first(tu + du1, tv + dv1, wq);
            __syncwarp();
        }

        acc_to_frags(acc, po);
        pin(po);
        if (!last) turn_wait(wg);
        wg_fence();
        proj_gemm<0, 1>(acc, po, wdesc, 0, [](int) {});
        if (!last) turn_pass(wg);
        TR(19 + 16 * k);
        if (LDGPOS == 4) load_raw(nxt, x, o0, o1);
        const uint32_t zero = lds_volatile(s_zero);
        const float inv0 = rcp(quad_sum(s0 + __uint_as_float(zero))), inv1 = rcp(quad_sum(s1 + __uint_as_float(zero)));
        raw_to_frags(nxt, zero, fa);
        pin(fa);
        TR(20 + 16 * k);
        tu += du2; tv += dv2;
        wg_wait<0>();
        pin(acc);
        TR(21 + 16 * k);
        pack_out(acc, inv0, inv1, po);
        pin(po);
    }
    store_out(out, c0, c1, po);
    TR(7);
    TRG(1);
    TRDUMP();
}

typedef CUresult (*EncodeTiledFn)(CUtensorMap*, CUtensorMapDataType, cuuint32_t, void*, const cuuint64_t*, const cuuint64_t*,
                                  const cuuint32_t*, const cuuint32_t*, CUtensorMapInterleave, CUtensorMapSwizzle,
                                  CUtensorMapL2promotion, CUtensorMapFloatOOBfill);

bool make_maps(EncodeTiledFn fn, Maps* maps, void* x, void* wqkv, void* wo) {
    const cuuint64_t pix2 = 2 * kPixBytes, row = (cuuint64_t)kHW * kPixBytes;
    const cuuint32_t estr[5] = {1, 1, 1, 1, 1};
    bool ok = true;
    for (int tr = 0; tr < 2; tr++)
        for (int b = 0; b < 3; b++) {
            const cuuint64_t su = tr ? 2 * row : pix2, sv = tr ? pix2 : 2 * row;
            const cuuint64_t dims[5] = {2 * kC, b < 2 ? 2u : 1u, b < 2 ? 105u : 112u, 2, 112};
            const cuuint64_t strides[4] = {7 * su, su, row, sv};
            const cuuint32_t keys[5] = {64, 2, 7, 1, b ? 2u : 6u}, pixels[5] = {kC, 1, 8, 1, 8};
            ok = ok && fn(&maps->m[3 * tr + b], CU_TENSOR_MAP_DATA_TYPE_BFLOAT16, 5, x, dims, strides, b < 2 ? keys : pixels, estr,
                          CU_TENSOR_MAP_INTERLEAVE_NONE, b < 2 ? CU_TENSOR_MAP_SWIZZLE_128B : CU_TENSOR_MAP_SWIZZLE_NONE,
                          CU_TENSOR_MAP_L2_PROMOTION_L2_128B, CU_TENSOR_MAP_FLOAT_OOB_FILL_NONE) == CUDA_SUCCESS;
        }
    {
        const cuuint64_t dims[3] = {64, kC, 9}, strides[2] = {3 * kPixBytes, 128};
        const cuuint32_t box[3] = {64, 16, 3};
        ok = ok && fn(&maps->wqkv, CU_TENSOR_MAP_DATA_TYPE_BFLOAT16, 3, wqkv, dims, strides, box, estr, CU_TENSOR_MAP_INTERLEAVE_NONE,
                      CU_TENSOR_MAP_SWIZZLE_128B, CU_TENSOR_MAP_L2_PROMOTION_L2_128B, CU_TENSOR_MAP_FLOAT_OOB_FILL_NONE) == CUDA_SUCCESS;
    }
    {
        const cuuint64_t dims[2] = {kC, kC}, strides[1] = {kPixBytes};
        const cuuint32_t box[2] = {32, kC};
        ok = ok && fn(&maps->wo, CU_TENSOR_MAP_DATA_TYPE_BFLOAT16, 2, wo, dims, strides, box, estr, CU_TENSOR_MAP_INTERLEAVE_NONE,
                      CU_TENSOR_MAP_SWIZZLE_64B, CU_TENSOR_MAP_L2_PROMOTION_L2_128B, CU_TENSOR_MAP_FLOAT_OOB_FILL_NONE) == CUDA_SUCCESS;
    }
    return ok;
}

}

extern "C" void kernel_launch(void* const* d_in, const int* in_sizes, int n_in, void* d_out, int out_size) {
    static EncodeTiledFn encode = nullptr;
    if (!encode) {
        void* fn = nullptr;
        cudaDriverEntryPointQueryResult st;
        cudaGetDriverEntryPoint("cuTensorMapEncodeTiled", &fn, cudaEnableDefault, &st);
        encode = (EncodeTiledFn)fn;
        cudaFuncSetAttribute(nat_fused_kernel, cudaFuncAttributeMaxDynamicSharedMemorySize, kSmemBytes);
    }
    Maps maps;
    if (!encode || !make_maps(encode, &maps, d_in[0], d_in[1], d_in[2])) return;
    nat_fused_kernel<<<kGrid, kThreads, kSmemBytes>>>(maps, (const uint8_t*)d_in[0], (const uint8_t*)d_in[1], (uint8_t*)d_out);
}
```

```cpp
#include <cuda_runtime.h>
#include <cuda_bf16.h>
#include <cuda.h>
#include <stdint.h>
#include <type_traits>
#include <stdlib.h>

#define LDGPOS 0
#define PREFETCH 1

namespace {

constexpr int kC          = 192;
constexpr int kHW         = 224;
constexpr int kPixBytes   = kC * 2;
constexpr int kSlotBytes  = 84 * 128;
constexpr int kMidBytes   = 28 * 128;
constexpr int kOffMid     = 88 * 128;
constexpr int kSlotStride = 120 * 128;
constexpr int kRingChunk  = 208 * 128;
constexpr int kWChunk     = 192 * 128;
constexpr int kWBytes     = 3 * kWChunk;
constexpr uint32_t kSmemBase = 1024;
constexpr uint32_t s_ring = kSmemBase, s_m = s_ring + 3 * kRingChunk, s_wv = s_m + kWBytes, s_bar = s_wv + kWBytes;
constexpr uint32_t bar_b = s_bar, bar_m = s_bar + 24, bar_wv = s_bar + 48, bar_wop = s_bar + 56, bar_redo = s_bar + 64, bar_a = s_bar + 72;
constexpr uint32_t s_zero = s_ring + 84 * 128, s_par = s_bar + 96, s_trace = s_bar + 256;
constexpr int kSmemBytes  = s_trace + 2048 - kSmemBase;
constexpr int kThreads    = 256;
constexpr int kGrid       = 132;
constexpr int kMPieces    = 144;
constexpr int kWPieces    = 72;
constexpr float kScaleLog2e = 0.07216878364870322f * 1.4426950408889634f;

struct Maps {
    CUtensorMap m[8];
    CUtensorMap wqkv;
    CUtensorMap wo;
};
#define TN(i, dflt) (dflt)

struct Scratch {
    uint8_t img[2][2][kWBytes];
    uint32_t cnt[2];
};
__device__ __align__(1024) Scratch g_scratch;

#define WO4(i) "=f"(d[i]), "=f"(d[i + 1]), "=f"(d[i + 2]), "=f"(d[i + 3])
#define RW4(i) "+f"(d[i]), "+f"(d[i + 1]), "+f"(d[i + 2]), "+f"(d[i + 3])

template <bool FIRST>
__device__ __forceinline__ void wgmma_n192(float (&d)[96], uint32_t a0, uint32_t a1, uint32_t a2, uint32_t a3, uint64_t descb) {
    if constexpr (FIRST) {
        asm volatile(
            "wgmma.mma_async.sync.aligned.m64n192k16.f32.bf16.bf16 "
            "{%0, %1, %2, %3, %4, %5, %6, %7, %8, %9, %10, %11, %12, %13, %14, %15, %16, %17, %18, %19, %20, %21, %22, %23, "
            "%24, %25, %26, %27, %28, %29, %30, %31, %32, %33, %34, %35, %36, %37, %38, %39, %40, %41, %42, %43, %44, %45, %46, %47, "
            "%48, %49, %50, %51, %52, %53, %54, %55, %56, %57, %58, %59, %60, %61, %62, %63, %64, %65, %66, %67, %68, %69, %70, %71, "
            "%72, %73, %74, %75, %76, %77, %78, %79, %80, %81, %82, %83, %84, %85, %86, %87, %88, %89, %90, %91, %92, %93, %94, %95}, "
            "{%96, %97, %98, %99}, %100, 0, 1, 1, 0;"
            : WO4(0), WO4(4), WO4(8), WO4(12), WO4(16), WO4(20), WO4(24), WO4(28), WO4(32), WO4(36), WO4(40), WO4(44),
              WO4(48), WO4(52), WO4(56), WO4(60), WO4(64), WO4(68), WO4(72), WO4(76), WO4(80), WO4(84), WO4(88), WO4(92)
            : "r"(a0), "r"(a1), "r"(a2), "r"(a3), "l"(descb));
    } else {
        asm volatile(
            "wgmma.mma_async.sync.aligned.m64n192k16.f32.bf16.bf16 "
            "{%0, %1, %2, %3, %4, %5, %6, %7, %8, %9, %10, %11, %12, %13, %14, %15, %16, %17, %18, %19, %20, %21, %22, %23, "
            "%24, %25, %26, %27, %28, %29, %30, %31, %32, %33, %34, %35, %36, %37, %38, %39, %40, %41, %42, %43, %44, %45, %46, %47, "
            "%48, %49, %50, %51, %52, %53, %54, %55, %56, %57, %58, %59, %60, %61, %62, %63, %64, %65, %66, %67, %68, %69, %70, %71, "
            "%72, %73, %74, %75, %76, %77, %78, %79, %80, %81, %82, %83, %84, %85, %86, %87, %88, %89, %90, %91, %92, %93, %94, %95}, "
            "{%96, %97, %98, %99}, %100, 1, 1, 1, 0;"
            : RW4(0), RW4(4), RW4(8), RW4(12), RW4(16), RW4(20), RW4(24), RW4(28), RW4(32), RW4(36), RW4(40), RW4(44),
              RW4(48), RW4(52), RW4(56), RW4(60), RW4(64), RW4(68), RW4(72), RW4(76), RW4(80), RW4(84), RW4(88), RW4(92)
            : "r"(a0), "r"(a1), "r"(a2), "r"(a3), "l"(descb));
    }
}

template <bool FIRST>
__device__ __forceinline__ void wgmma_n88(float (&d)[44], uint32_t a0, uint32_t a1, uint32_t a2, uint32_t a3, uint64_t descb) {
    if constexpr (FIRST) {
        asm volatile(
            "wgmma.mma_async.sync.aligned.m64n88k16.f32.bf16.bf16 "
            "{%0, %1, %2, %3, %4, %5, %6, %7, %8, %9, %10, %11, %12, %13, %14, %15, %16, %17, %18, %19, %20, %21, %22, %23, "
            "%24, %25, %26, %27, %28, %29, %30, %31, %32, %33, %34, %35, %36, %37, %38, %39, %40, %41, %42, %43}, "
            "{%44, %45, %46, %47}, %48, 0, 1, 1, 0;"
            : WO4(0), WO4(4), WO4(8), WO4(12), WO4(16), WO4(20), WO4(24), WO4(28), WO4(32), WO4(36), WO4(40)
            : "r"(a0), "r"(a1), "r"(a2), "r"(a3), "l"(descb));
    } else {
        asm volatile(
            "wgmma.mma_async.sync.aligned.m64n88k16.f32.bf16.bf16 "
            "{%0, %1, %2, %3, %4, %5, %6, %7, %8, %9, %10, %11, %12, %13, %14, %15, %16, %17, %18, %19, %20, %21, %22, %23, "
            "%24, %25, %26, %27, %28, %29, %30, %31, %32, %33, %34, %35, %36, %37, %38, %39, %40, %41, %42, %43}, "
            "{%44, %45, %46, %47}, %48, 1, 1, 1, 0;"
            : RW4(0), RW4(4), RW4(8), RW4(12), RW4(16), RW4(20), RW4(24), RW4(28), RW4(32), RW4(36), RW4(40)
            : "r"(a0), "r"(a1), "r"(a2), "r"(a3), "l"(descb));
    }
}

template <bool FIRST>
__device__ __forceinline__ void wgmma_n32(float (&d)[16], uint32_t a0, uint32_t a1, uint32_t a2, uint32_t a3, uint64_t descb) {
    if constexpr (FIRST) {
        asm volatile(
            "wgmma.mma_async.sync.aligned.m64n32k16.f32.bf16.bf16 "
            "{%0, %1, %2, %3, %4, %5, %6, %7, %8, %9, %10, %11, %12, %13, %14, %15}, "
            "{%16, %17, %18, %19}, %20, 0, 1, 1, 0;"
            : WO4(0), WO4(4), WO4(8), WO4(12)
            : "r"(a0), "r"(a1), "r"(a2), "r"(a3), "l"(descb));
    } else {
        asm volatile(
            "wgmma.mma_async.sync.aligned.m64n32k16.f32.bf16.bf16 "
            "{%0, %1, %2, %3, %4, %5, %6, %7, %8, %9, %10, %11, %12, %13, %14, %15}, "
            "{%16, %17, %18, %19}, %20, 1, 1, 1, 0;"
            : RW4(0), RW4(4), RW4(8), RW4(12)
            : "r"(a0), "r"(a1), "r"(a2), "r"(a3), "l"(descb));
    }
}

template <bool FIRST, int SEL>
__device__ __forceinline__ void wgmma_sp_n192_tb(float (&d)[96], uint32_t a0, uint32_t a1, uint32_t a2, uint32_t a3, uint64_t descb, uint32_t meta) {
    if constexpr (FIRST) {
        asm volatile(
            "wgmma.mma_async.sp.sync.aligned.m64n192k32.f32.bf16.bf16 "
            "{%0, %1, %2, %3, %4, %5, %6, %7, %8, %9, %10, %11, %12, %13, %14, %15, %16, %17, %18, %19, %20, %21, %22, %23, "
            "%24, %25, %26, %27, %28, %29, %30, %31, %32, %33, %34, %35, %36, %37, %38, %39, %40, %41, %42, %43, %44, %45, %46, %47, "
            "%48, %49, %50, %51, %52, %53, %54, %55, %56, %57, %58, %59, %60, %61, %62, %63, %64, %65, %66, %67, %68, %69, %70, %71, "
            "%72, %73, %74, %75, %76, %77, %78, %79, %80, %81, %82, %83, %84, %85, %86, %87, %88, %89, %90, %91, %92, %93, %94, %95}, "
            "{%96, %97, %98, %99}, %100, %101, %102, 0, 1, 1, 1;"
            : WO4(0), WO4(4), WO4(8), WO4(12), WO4(16), WO4(20), WO4(24), WO4(28), WO4(32), WO4(36), WO4(40), WO4(44),
              WO4(48), WO4(52), WO4(56), WO4(60), WO4(64), WO4(68), WO4(72), WO4(76), WO4(80), WO4(84), WO4(88), WO4(92)
            : "r"(a0), "r"(a1), "r"(a2), "r"(a3), "l"(descb), "r"(meta), "n"(SEL));
    } else {
        asm volatile(
            "wgmma.mma_async.sp.sync.aligned.m64n192k32.f32.bf16.bf16 "
            "{%0, %1, %2, %3, %4, %5, %6, %7, %8, %9, %10, %11, %12, %13, %14, %15, %16, %17, %18, %19, %20, %21, %22, %23, "
            "%24, %25, %26, %27, %28, %29, %30, %31, %32, %33, %34, %35, %36, %37, %38, %39, %40, %41, %42, %43, %44, %45, %46, %47, "
            "%48, %49, %50, %51, %52, %53, %54, %55, %56, %57, %58, %59, %60, %61, %62, %63, %64, %65, %66, %67, %68, %69, %70, %71, "
            "%72, %73, %74, %75, %76, %77, %78, %79, %80, %81, %82, %83, %84, %85, %86, %87, %88, %89, %90, %91, %92, %93, %94, %95}, "
            "{%96, %97, %98, %99}, %100, %101, %102, 1, 1, 1, 1;"
            : RW4(0), RW4(4), RW4(8), RW4(12), RW4(16), RW4(20), RW4(24), RW4(28), RW4(32), RW4(36), RW4(40), RW4(44),
              RW4(48), RW4(52), RW4(56), RW4(60), RW4(64), RW4(68), RW4(72), RW4(76), RW4(80), RW4(84), RW4(88), RW4(92)
            : "r"(a0), "r"(a1), "r"(a2), "r"(a3), "l"(descb), "r"(meta), "n"(SEL));
    }
}

#define TR(slot)
#define TRW(slot)
#define TRG(slot)
#define TRDUMP()

__device__ __forceinline__ void wg_fence() { asm volatile("wgmma.fence.sync.aligned;" ::: "memory"); }
__device__ __forceinline__ void wg_commit() { asm volatile("wgmma.commit_group.sync.aligned;" ::: "memory"); }
template <int N>
__device__ __forceinline__ void wg_wait() { asm volatile("wgmma.wait_group.sync.aligned %0;" ::"n"(N) : "memory"); }

template <int N>
__device__ __forceinline__ void pin(float (&d)[N]) {
#pragma unroll
    for (int i = 0; i < N; i++) asm volatile("" : "+f"(d[i])::"memory");
}
template <int N>
__device__ __forceinline__ void pin(uint32_t (&d)[N]) {
#pragma unroll
    for (int i = 0; i < N; i++) asm volatile("" : "+r"(d[i])::"memory");
}

__device__ __forceinline__ constexpr uint32_t desc_lo(uint32_t addr, uint32_t lbo) { return (addr >> 4) | ((lbo >> 4) << 16); }
__device__ __forceinline__ uint64_t desc_at(uint32_t lo, uint32_t byte_off) {
    return ((uint64_t)((1u << 30) | (1024u >> 4)) << 32) | (uint64_t)(lo + (byte_off >> 4));
}

__device__ __forceinline__ void mbar_init(uint32_t bar, uint32_t count) {
    asm volatile("mbarrier.init.shared::cta.b64 [%0], %1;" ::"r"(bar), "r"(count) : "memory");
}
__device__ __forceinline__ void mbar_expect_tx(uint32_t bar, uint32_t bytes) {
    asm volatile("mbarrier.arrive.expect_tx.shared::cta.b64 _, [%0], %1;" ::"r"(bar), "r"(bytes) : "memory");
}
__device__ __forceinline__ void mbar_arrive(uint32_t bar) {
    asm volatile("mbarrier.arrive.shared::cta.b64 _, [%0];" ::"r"(bar) : "memory");
}
__device__ __forceinline__ void mbar_wait(uint32_t bar, uint32_t parity) {
    asm volatile(
        "{\n.reg .pred p;\n"
        "W: mbarrier.try_wait.parity.shared::cta.b64 p, [%0], %1;\n"
        "@!p bra W;\n}\n"
        ::"r"(bar), "r"(parity) : "memory");
}
__device__ __forceinline__ uint32_t clock_now() {
    uint32_t c;
    asm volatile("mov.u32 %0, %%clock;" : "=r"(c)::"memory");
    return c;
}
__device__ __forceinline__ void wait_until(uint32_t t0, int t) {
    while ((int)(clock_now() - t0) < t) {}
}
__device__ __forceinline__ bool elect() {
    uint32_t ok;
    asm volatile("{\n.reg .pred p;\nelect.sync _|p, 0xffffffff;\nselp.u32 %0, 1, 0, p;\n}\n" : "=r"(ok));
    return ok != 0;
}
__device__ __forceinline__ void turn_wait(int wg) { asm volatile("bar.sync %0, 256;" ::"r"(1 + wg) : "memory"); }
__device__ __forceinline__ void turn_pass(int wg) { asm volatile("bar.arrive %0, 256;" ::"r"(2 - wg) : "memory"); }
__device__ __forceinline__ void wg_sync(int wg) { asm volatile("bar.sync %0, 128;" ::"r"(3 + wg) : "memory"); }

__device__ __forceinline__ void tma_box(uint32_t dst, const CUtensorMap* map, uint32_t bar, int c0, int c2, int c3, int c4) {
    asm volatile(
        "cp.async.bulk.tensor.5d.shared::cluster.global.mbarrier::complete_tx::bytes [%0], [%1, {%3, %4, %5, %6, %7}], [%2];"
        ::"r"(dst), "l"(map), "r"(bar), "r"(c0), "r"(0), "r"(c2), "r"(c3), "r"(c4)
        : "memory");
}
__device__ __forceinline__ void tma_2d(uint32_t dst, const CUtensorMap* map, uint32_t bar, int c0, int c1) {
    asm volatile("cp.async.bulk.tensor.2d.shared::cluster.global.mbarrier::complete_tx::bytes [%0], [%1, {%3, %4}], [%2];"
                 ::"r"(dst), "l"(map), "r"(bar), "r"(c0), "r"(c1)
                 : "memory");
}
__device__ __forceinline__ void tma_3d(uint32_t dst, const CUtensorMap* map, uint32_t bar, int c0, int c1, int c2) {
    asm volatile("cp.async.bulk.tensor.3d.shared::cluster.global.mbarrier::complete_tx::bytes [%0], [%1, {%3, %4, %5}], [%2];"
                 ::"r"(dst), "l"(map), "r"(bar), "r"(c0), "r"(c1), "r"(c2)
                 : "memory");
}
__device__ __forceinline__ void tma_prefetch(const CUtensorMap* map, int c0, int c2, int c3, int c4) {
    asm volatile("cp.async.bulk.prefetch.tensor.5d.L2.global [%0, {%1, %2, %3, %4, %5}];"
                 ::"l"(map), "r"(c0), "r"(0), "r"(c2), "r"(c3), "r"(c4)
                 : "memory");
}
__device__ __forceinline__ void prefetch_map(const CUtensorMap* map) {
    asm volatile("prefetch.tensormap [%0];" ::"l"(map) : "memory");
}
__device__ __forceinline__ uint4 ldg_nc(const void* p) {
    uint4 v;
    asm volatile("ld.global.nc.v4.u32 {%0, %1, %2, %3}, [%4];" : "=r"(v.x), "=r"(v.y), "=r"(v.z), "=r"(v.w) : "l"(p));
    return v;
}
__device__ __forceinline__ uint4 ldg(const void* p) {
    uint4 v;
    asm volatile("ld.global.v4.u32 {%0, %1, %2, %3}, [%4];" : "=r"(v.x), "=r"(v.y), "=r"(v.z), "=r"(v.w) : "l"(p) : "memory");
    return v;
}
__device__ __forceinline__ void stg128(void* p, uint32_t a, uint32_t b, uint32_t c, uint32_t d) {
    asm volatile("st.global.v4.u32 [%0], {%1, %2, %3, %4};" ::"l"(p), "r"(a), "r"(b), "r"(c), "r"(d) : "memory");
}
__device__ __forceinline__ uint32_t pack_bf16(float lo, float hi) {
    uint32_t r;
    asm("cvt.rn.bf16x2.f32 %0, %1, %2;" : "=r"(r) : "f"(hi), "f"(lo));
    return r;
}
__device__ __forceinline__ float ex2(float x) {
    float y;
    asm("ex2.approx.ftz.f32 %0, %1;" : "=f"(y) : "f"(x));
    return y;
}
__device__ __forceinline__ float rcp(float x) {
    float y;
    asm("rcp.approx.ftz.f32 %0, %1;" : "=f"(y) : "f"(x));
    return y;
}
__device__ __forceinline__ void mma16816(float (&d)[4], uint32_t a0, uint32_t a1, uint32_t a2, uint32_t a3, uint32_t b0, uint32_t b1) {
    asm volatile("mma.sync.aligned.m16n8k16.row.col.f32.bf16.bf16.f32 {%0, %1, %2, %3}, {%4, %5, %6, %7}, {%8, %9}, {%0, %1, %2, %3};"
                 : "+f"(d[0]), "+f"(d[1]), "+f"(d[2]), "+f"(d[3])
                 : "r"(a0), "r"(a1), "r"(a2), "r"(a3), "r"(b0), "r"(b1));
}
__device__ __forceinline__ uint32_t lds_volatile(uint32_t addr) {
    uint32_t v;
    asm volatile("ld.volatile.shared.u32 %0, [%1];" : "=r"(v) : "r"(addr) : "memory");
    return v;
}

__device__ __forceinline__ int window_start(int i_shifted) { return min(max(i_shifted, 0), 105); }

struct Work {
    int cu, cv;
    uint32_t su, sv;
    int iu, iv;
    int corner, ntiles;
    int rev;
    const CUtensorMap* map;
    int c0, c3;
    __device__ __forceinline__ int origin_u(int u) const { return min(max(u + cu, 0), 98); }
    __device__ __forceinline__ void pixel_offsets(int u, int v, int j, uint32_t& o0, uint32_t& o1) const {
        const uint32_t base = (u + window_start(u + cu) + (cu ? 0 : 7)) * su + j * 16 + (v + (cv ? 0 : 7)) * sv;
        o0 = base + window_start(v + cv) * sv;
        o1 = base + (window_start(v + 1 + cv) + 1) * sv;
    }
    __device__ __forceinline__ void load_first(int u, int v, int c) const {
        mbar_expect_tx(bar_a, kSlotBytes);
        tma_box(s_ring + c * kRingChunk, map, bar_a, c0 + 64 * c, origin_u(u), c3, v + cv + rev);
    }
    __device__ __forceinline__ void load_rest(int u, int v, int slot, int c) const {
        mbar_expect_tx(bar_b + 8 * c, kSlotBytes + kMidBytes);
        tma_box(s_ring + c * kRingChunk + slot * kSlotStride, map, bar_b + 8 * c, c0 + 64 * c, origin_u(u), c3, v + cv + 8 - rev);
        tma_box(s_ring + c * kRingChunk + kOffMid + 512, map + 1, bar_b + 8 * c, c0 + 64 * c, origin_u(u), c3, v + cv + 6);
    }
    __device__ __forceinline__ void prefetch_rows(int u, int v) const { tma_prefetch(map + 2, c0, u, c3, v + cv); }
};

__device__ __forceinline__ Work decode_work(const Maps& maps, int c) {
    Work w;
    const int idx = c >> 2, ypar = (c >> 1) & 1, xpar = c & 1;
    const bool transposed = (idx >> 2) == 7;
    w.corner = idx == 32;
    w.cu = 6 * (transposed ? ypar : xpar) - 6;
    w.cv = 6 * (transposed ? xpar : ypar) - 6;
    w.su = transposed ? kHW * kPixBytes : kPixBytes;
    w.sv = transposed ? kPixBytes : kHW * kPixBytes;
    w.iu = idx < 28 ? 8 * (idx >> 1) : 96 + 4 * (idx & 2);
    w.rev = w.corner ? 0 : 8 * (idx & 1);
    w.iv = w.corner ? 96 : 48 - w.rev;
    w.ntiles = w.corner ? 4 : 6;
    w.map = &maps.m[transposed ? 4 : 0];
    w.c0 = xpar * kC;
    w.c3 = ypar;
    return w;
}

struct RawX { uint4 a[6], b[6]; };
__device__ __forceinline__ void load_raw(RawX& r, const uint8_t* base, uint32_t o0, uint32_t o1) {
    __syncwarp();
#pragma unroll
    for (int c = 0; c < 6; c++) { r.a[c] = ldg(base + o0 + c * 64); r.b[c] = ldg(base + o1 + c * 64); }
    __syncwarp();
}
__device__ __forceinline__ void raw_to_frags(const RawX& r, uint32_t zero, uint32_t (&f)[48]) {
#pragma unroll
    for (int c = 0; c < 6; c++) {
        f[8 * c + 0] = r.a[c].x ^ zero; f[8 * c + 2] = r.a[c].z ^ zero; f[8 * c + 4] = r.a[c].y ^ zero; f[8 * c + 6] = r.a[c].w ^ zero;
        f[8 * c + 1] = r.b[c].x ^ zero; f[8 * c + 3] = r.b[c].z ^ zero; f[8 * c + 5] = r.b[c].y ^ zero; f[8 * c + 7] = r.b[c].w ^ zero;
    }
}
__device__ __forceinline__ void acc_to_frags(const float (&d)[96], uint32_t (&f)[48]) {
#pragma unroll
    for (int i = 0; i < 48; i++) f[i] = pack_bf16(d[2 * i], d[2 * i + 1]);
}

template <int NBARS, int GROUPS, class F>
__device__ __forceinline__ void proj_gemm(float (&d)[96], const uint32_t (&a)[48], uint32_t wdesc, uint32_t wbar, F after) {
#pragma unroll
    for (int c = 0; c < 3; c++) {
        if (c < NBARS) { mbar_wait(wbar + 8 * c, 0); wg_fence(); }
#pragma unroll
        for (int s = 4 * c; s < 4 * c + 4; s++) {
            if (s == 0) wgmma_n192<true>(d, a[4 * s], a[4 * s + 1], a[4 * s + 2], a[4 * s + 3], desc_at(wdesc, c * kWChunk + (s & 3) * 32));
            else wgmma_n192<false>(d, a[4 * s], a[4 * s + 1], a[4 * s + 2], a[4 * s + 3], desc_at(wdesc, c * kWChunk + (s & 3) * 32));
            if (s >= 12 - GROUPS) wg_commit();
            after(s);
        }
    }
}
__device__ __forceinline__ void pack_out(const float (&acc)[96], float i0, float i1, uint32_t (&po)[48]) {
#pragma unroll
    for (int g = 0; g < 6; g++)
#pragma unroll
        for (int q = 0; q < 4; q++) {
            po[8 * g + q] = pack_bf16(acc[16 * g + 4 * q] * i0, acc[16 * g + 4 * q + 1] * i0);
            po[8 * g + 4 + q] = pack_bf16(acc[16 * g + 4 * q + 2] * i1, acc[16 * g + 4 * q + 3] * i1);
        }
}
__device__ __forceinline__ void store_one(bool on, uint8_t* p0, uint8_t* p1, const uint32_t (&po)[48], int n) {
    asm volatile("{\n.reg .pred p;\nsetp.ne.u32 p, %5, 0;\nbar.warp.sync 0xffffffff;\n@p st.global.v4.u32 [%0], {%1, %2, %3, %4};\n}\n"
                 ::"l"(((n & 1) ? p1 : p0) + (n >> 1) * 64), "r"(po[4 * n]), "r"(po[4 * n + 1]), "r"(po[4 * n + 2]), "r"(po[4 * n + 3]), "r"((uint32_t)on) : "memory");
}
__device__ __forceinline__ void store_out(uint8_t* out, uint32_t o0, uint32_t o1, const uint32_t (&po)[48]) {
#pragma unroll
    for (int g = 0; g < 6; g++) {
        stg128(out + o0 + g * 64, po[8 * g], po[8 * g + 1], po[8 * g + 2], po[8 * g + 3]);
        stg128(out + o1 + g * 64, po[8 * g + 4], po[8 * g + 5], po[8 * g + 6], po[8 * g + 7]);
    }
}

struct Masks {
    uint32_t h;
    uint32_t meta[2];
};

__device__ __forceinline__ void make_u_masks(Masks& m, int offu, int j) {
    m.h = (((1u << offu) - 1u) * 0x4081u) >> j;
    uint32_t y = __byte_perm(m.h, 0, 0x4140);
    y = (y | (y << 4)) & 0x0f0f0f0fu;
    y = (y | (y << 2)) & 0x33333333u;
    y = (y | (y << 1)) & 0x55555555u;
    m.meta[0] = __byte_perm(y | 0x8888u, 0, 0x1010);
    m.meta[1] = __byte_perm((y >> (8 - (j & 2))) | 0x8888u, 0, 0x1010);
}

template <int N>
__device__ __forceinline__ float tree_max(const float (&v)[N]) {
    float t[N];
#pragma unroll
    for (int i = 0; i < N; i++) t[i] = v[i];
#pragma unroll
    for (int w = 1; w < N; w *= 2)
#pragma unroll
        for (int i = 0; i + w < N; i += 2 * w) t[i] = fmaxf(t[i], t[i + w]);
    return t[0];
}
template <int N>
__device__ __forceinline__ float tree_sum(const float (&v)[N]) {
    float t[N];
#pragma unroll
    for (int i = 0; i < N; i++) t[i] = v[i];
#pragma unroll
    for (int w = 1; w < N; w *= 2)
#pragma unroll
        for (int i = 0; i + w < N; i += 2 * w) t[i] += t[i + w];
    return t[0];
}

template <int B>
__device__ __forceinline__ void pick(uint32_t h, bool ok0, bool ok1, const float* s, float& v0, float& v1) {
    asm("{\n.reg .pred p, q0, q1;\n.reg .b32 t;\nand.b32 t, %6, %7;\nsetp.ne.u32 p, t, 0;\n"
        "setp.ne.u32 q0, %8, 0;\nsetp.ne.u32 q1, %9, 0;\n"
        "@q0 selp.f32 %0, %3, %2, p;\n@q1 selp.f32 %1, %5, %4, p;\n}\n"
        : "+f"(v0), "+f"(v1)
        : "f"(s[0]), "f"(s[1]), "f"(s[2]), "f"(s[3]), "r"(h), "n"(1 << ((4 * B) % 7)), "r"((uint32_t)ok0), "r"((uint32_t)ok1));
}
template <int B, class F>
__device__ __forceinline__ void for_blocks(F f) {
    if constexpr (B > 0) { for_blocks<B - 1>(f); f(std::integral_constant<int, B - 1>{}); }
}
__device__ __forceinline__ void gather_outer(const float (&s)[44], uint32_t h, int t0, int t1, bool late, float (&v0)[14], float (&v1)[14]) {
    for_blocks<11>([&](auto B) {
        constexpr int b = B.value < 8 ? (B.value >> 1) + 7 * (B.value & 1) : B.value - 4;
        pick<b>(h, (t0 <= 4 * b) != late, (t1 <= 4 * b) != late, &s[4 * b], v0[b], v1[b]);
    });
}
__device__ __forceinline__ void gather_mid(const float (&sE)[16], uint32_t h, int t0, int t1, int j, float (&v0)[14], float (&v1)[14]) {
    for_blocks<4>([&](auto B) {
        constexpr int b = 10 + B.value;
        pick<b>(h, (b > 10 || j >= 2) && (b < 12 || t0 > 4 * b - 49) && (b > 12 || t0 <= 4 * b),
                   (b > 10 || j >= 2) && (b < 12 || t1 > 4 * b - 49) && (b > 12 || t1 <= 4 * b), &sE[4 * B.value], v0[b], v1[b]);
    });
}
__device__ __forceinline__ float quad_max(float m) {
    m = fmaxf(m, __shfl_xor_sync(0xffffffffu, m, 1));
    return fmaxf(m, __shfl_xor_sync(0xffffffffu, m, 2));
}
__device__ __forceinline__ float quad_sum(float s) {
    s += __shfl_xor_sync(0xffffffffu, s, 1);
    return s + __shfl_xor_sync(0xffffffffu, s, 2);
}
__device__ __forceinline__ void exp_scatter(float (&v0)[14], float (&v1)[14], float m0, float m1, int tw, bool rev, int lane, uint32_t (&pa)[28]) {
    const int j = lane & 3;
    const int src1 = (lane & ~3) | ((j & 1) << 1) | (j >> 1);
    const int src2 = src1 ^ 1;
    const uint32_t selr = j < 2 ? 0x5410u : 0x1054u;
    const uint32_t selr8 = j < 2 ? 0x7632u : 0x3276u;
    const bool even = (j & 1) == 0;
#pragma unroll
    for (int b = 0; b < 14; b++) { v0[b] = ex2(v0[b] - m0); v1[b] = ex2(v1[b] - m1); }
#pragma unroll
    for (int b = 0; b < 14; b += 2) {
        const uint32_t x0 = pack_bf16(v0[b], v1[b]), x1 = pack_bf16(v0[b + 1], v1[b + 1]);
        const uint32_t u = __shfl_sync(0xffffffffu, even ? x0 : x1, src1);
        const uint32_t w = __shfl_sync(0xffffffffu, even ? x1 : x0, src2);
        if (b < 12)
            asm("{\n.reg .pred p, q;\nsetp.ne.u32 p, %8, 0;\nsetp.ne.u32 q, %9, 0;\n"
                "@p prmt.b32 %0, %4, %5, %6;\n@p prmt.b32 %1, %4, %5, %7;\n"
                "@q prmt.b32 %2, %4, %5, %6;\n@q prmt.b32 %3, %4, %5, %7;\n}\n"
                : "+r"(pa[b]), "+r"(pa[b + 1]), "+r"(pa[16 + b]), "+r"(pa[17 + b])
                : "r"(u), "r"(w), "r"(selr), "r"(selr8), "r"((uint32_t)((4 * b >= tw) != rev && (b < 10 || j == 0))),
                  "r"((uint32_t)((4 * b >= tw) == rev && (b < 10 || j == 0))));
        if (b >= 10) { pa[b + 2] = __byte_perm(u, w, selr); pa[b + 3] = __byte_perm(u, w, selr8); }
    }
}

__device__ __forceinline__ uint32_t wimg_offset(uint32_t row, uint32_t s, uint32_t j) {
    return (s >> 2) * kWChunk + row * 128 + (((2 * (s & 3) + (j >> 1)) ^ (row & 7)) << 4) + (j & 1) * 8;
}

struct MPiece { uint4 A[2][6], B[2][6]; };
__device__ __forceinline__ void m_piece_load(MPiece& m, const uint8_t* wqkv, uint32_t pc, uint32_t lane) {
    const uint32_t r8 = lane >> 2, j = lane & 3, s = pc % 12;
    const uint8_t* pa = wqkv + (16 * (pc / 12) + r8) * 1152 + j * 16;
    const uint8_t* pb = wqkv + (32 * (s >> 1) + 2 * (s & 1) + 8 * (r8 & 2) + (r8 & 5)) * 1152 + j * 16;
#pragma unroll
    for (int c = 0; c < 6; c++)
#pragma unroll
        for (int h = 0; h < 2; h++) { m.A[h][c] = ldg_nc(pa + 384 + h * 8 * 1152 + c * 64); m.B[h][c] = ldg_nc(pb + h * 8 * 1152 + c * 64); }
}
__device__ __forceinline__ void st_pair(Scratch* g, uint32_t par, uint32_t off, uint32_t a, uint32_t b) {
    asm volatile("st.relaxed.gpu.global.v2.u32 [%0], {%1, %2};" ::"l"(g->img[par][0] + off), "r"(a ? a : 0x8000u), "r"(b) : "memory");
    asm volatile("st.relaxed.gpu.global.v2.u32 [%0], {%1, %1};" ::"l"(g->img[par ^ 1][0] + off), "r"(0) : "memory");
}
__device__ __forceinline__ void m_piece_finish(const MPiece& m, uint32_t pc, uint32_t lane, Scratch* g, uint32_t par) {
    float d[2][4], e[2][4];
#pragma unroll
    for (int i = 0; i < 8; i++) (&d[0][0])[i] = (&e[0][0])[i] = 0.f;
#pragma unroll
    for (int c = 0; c < 6; c++)
#pragma unroll
        for (int nb = 0; nb < 2; nb++) {
            mma16816(d[nb], m.A[0][c].x, m.A[1][c].x, m.A[0][c].y, m.A[1][c].y, m.B[nb][c].x, m.B[nb][c].y);
            mma16816(e[nb], m.A[0][c].z, m.A[1][c].z, m.A[0][c].w, m.A[1][c].w, m.B[nb][c].z, m.B[nb][c].w);
        }
#pragma unroll
    for (int i = 0; i < 8; i++) (&d[0][0])[i] += (&e[0][0])[i];
    const uint32_t off = wimg_offset(16 * (pc / 12) + (lane >> 2), pc % 12, lane & 3);
#pragma unroll
    for (int hf = 0; hf < 2; hf++)
        st_pair(g, par, off + hf * 1024, pack_bf16(d[0][2 * hf] * kScaleLog2e, d[0][2 * hf + 1] * kScaleLog2e),
                pack_bf16(d[1][2 * hf] * kScaleLog2e, d[1][2 * hf + 1] * kScaleLog2e));
}

__device__ __forceinline__ void ldsm4(uint32_t (&r)[4], uint32_t addr) {
    asm volatile("ldmatrix.sync.aligned.m8n8.x4.shared.b16 {%0, %1, %2, %3}, [%4];" : "=r"(r[0]), "=r"(r[1]), "=r"(r[2]), "=r"(r[3]) : "r"(addr) : "memory");
}
__device__ __forceinline__ void ldsm4_t(uint32_t (&r)[4], uint32_t addr) {
    asm volatile("ldmatrix.sync.aligned.m8n8.x4.trans.shared.b16 {%0, %1, %2, %3}, [%4];" : "=r"(r[0]), "=r"(r[1]), "=r"(r[2]), "=r"(r[3]) : "r"(addr) : "memory");
}
__device__ __forceinline__ void w_piece(uint32_t s_wo, uint32_t s_wvr, uint32_t pw, uint32_t lane, Scratch* g, uint32_t par) {
    float d[2][2][4];
#pragma unroll
    for (int i = 0; i < 16; i++) (&d[0][0][0])[i] = 0.f;
    const uint32_t rr = lane & 7, mi = lane >> 3;
    const uint32_t kr = 4 * (rr >> 1) + (mi & 2) + (rr & 1);
    const uint32_t pb = s_wvr + kr * 128 + (((mi & 1) ^ (kr & 7)) << 4);
    uint32_t pa = s_wo + (4 * (mi & 2) + rr) * 64 + (((mi & 1) ^ (rr >> 1)) << 4);
#pragma unroll 1
    for (uint32_t s = 0; s < 12; s++, pa += 1024) {
        uint32_t bq[4];
        ldsm4(bq, (pb + (s >> 2) * 2048) ^ ((s & 3) << 5));
#pragma unroll
        for (int mt = 0; mt < 2; mt++) {
            uint32_t aq[4];
            ldsm4_t(aq, pa ^ (mt << 5));
            mma16816(d[mt][0], aq[0], aq[1], aq[2], aq[3], bq[0], bq[1]);
            mma16816(d[mt][1], aq[0], aq[1], aq[2], aq[3], bq[2], bq[3]);
        }
    }
    const uint32_t r8 = lane >> 2;
    const uint32_t off = wimg_offset(32 * (pw / 12) + 8 * (r8 >> 1) + (r8 & 1), pw % 12, lane & 3);
#pragma unroll
    for (int mt = 0; mt < 2; mt++)
#pragma unroll
        for (int hf = 0; hf < 2; hf++)
            st_pair(g, par, kWBytes + (off ^ ((4 * mt + 2 * hf) * 144)), pack_bf16(d[mt][0][2 * hf], d[mt][0][2 * hf + 1]),
                    pack_bf16(d[mt][1][2 * hf], d[mt][1][2 * hf + 1]));
}

__device__ __forceinline__ uint32_t ld_relaxed(const uint32_t* p) {
    uint32_t v;
    asm volatile("ld.relaxed.gpu.global.u32 %0, [%1];" : "=r"(v) : "l"(p) : "memory");
    return v;
}
__device__ __forceinline__ void count_up(uint32_t* p) {
    asm volatile("red.relaxed.gpu.global.add.u32 [%0], %1;" ::"l"(p), "r"(1) : "memory");
}
__device__ __forceinline__ void await_count(const uint32_t* p, uint32_t target) {
#pragma unroll 1
    for (uint32_t spins = 0; spins < (1u << 20); spins++)
        if (ld_relaxed(p) >= target) break;
}
__device__ __forceinline__ bool image_complete(uint32_t img, int wg) {
    uint32_t addr = img + (threadIdx.x & 127) * 32 + (threadIdx.x & 12) * 2, lo = 1;
#pragma unroll 1
    for (int c = 0; c < 3; c++, addr += kWChunk)
#pragma unroll
        for (int q = 0; q < 6; q++) lo = min(lo, lds_volatile(addr + q * 4096));
    uint32_t ok;
    asm volatile("{\n.reg .pred p;\nsetp.ne.u32 p, %1, 0;\nbarrier.cta.red.and.aligned.pred p, %2, 128, p;\nselp.u32 %0, 1, 0, p;\n}\n"
                 : "=r"(ok) : "r"(lo), "r"(3 + wg) : "memory");
    return ok != 0;
}
__device__ __forceinline__ void bulk_g2s(uint32_t dst, const void* src, uint32_t bytes, uint32_t bar) {
    asm volatile("cp.async.bulk.shared::cluster.global.mbarrier::complete_tx::bytes [%0], [%1], %2, [%3];"
                 ::"r"(dst), "l"(src), "r"(bytes), "r"(bar)
                 : "memory");
}

__global__ void __launch_bounds__(kThreads, 1)
nat_fused_kernel(const uint8_t* __restrict__ x, const uint8_t* __restrict__ wqkv, uint8_t* __restrict__ out, Scratch* g,
                 const __grid_constant__ Maps maps) {
    extern __shared__ __align__(1024) uint8_t smem_raw[];
    const int tid = threadIdx.x, lane = tid & 31;
    const int warp = __shfl_sync(0xffffffffu, tid >> 5, 0);
    const int wg = warp >> 2, wq = warp & 3, r8 = lane >> 2, j = lane & 3;
    const int cta = blockIdx.x;
    const uint32_t t_start = clock_now();
    const int order = (cta & 4) && cta < 128 ? warp ^ 3 : warp;
    const bool has_piece = order == 5 || (order == 7 && cta >= kGrid - (kMPieces - kGrid));
    const int pc = order == 5 ? cta : cta + (kMPieces - kGrid);
    MPiece mp;
    if (has_piece) m_piece_load(mp, wqkv, pc, lane);
    uint32_t launch = 0;
    if (order == 5 || order == 7) launch = ld_relaxed(&g->cnt[has_piece ? 0 : 1]);
    const Work w = decode_work(maps, cta);
    int tu = w.iu, tv = w.iv + (8 - 2 * w.rev) * wg;
    const int du1 = w.corner ? 8 * wg : 0, dv1 = 8 - 2 * du1 - 2 * w.rev, du2 = w.corner ? 8 : 0, dv2 = 16 - 2 * du2 - 4 * w.rev;
    uint32_t o0, o1;
    w.pixel_offsets(tu + r8, tv + 2 * wq, j, o0, o1);

    if (wg == 1) {
        if (order == 6) {
            if (elect()) {
#pragma unroll
                for (int i = 0; i < 10; i++) mbar_init(s_bar + 8 * i, i < 9 ? 1 : 3);
                asm volatile("fence.mbarrier_init.release.cluster;" ::: "memory");
                if ((uint32_t)__cvta_generic_to_shared(smem_raw) != kSmemBase) __trap();
            }
        } else if (order == 4) {
#pragma unroll
            for (int r = 0; r < 9; r++)
                asm volatile("st.shared.v4.u32 [%0], {%1, %1, %1, %1};" ::"r"(s_ring + (r / 3) * kRingChunk + (r % 3 == 0 ? 84 : r % 3 == 1 ? 88 : 204) * 128 + lane * 16), "r"(0) : "memory");
            asm volatile("fence.proxy.async.shared::cta;" ::: "memory");
#pragma unroll
            for (int r = 0; r < 3; r++) prefetch_map(w.map + r);
        }
        asm volatile("bar.arrive 0, 256;" ::: "memory");
        wg_sync(1);
        if (has_piece) {
            launch /= kMPieces;
            m_piece_finish(mp, pc, lane, g, launch & 1);
            __syncwarp();
            if (order == 5) TRW(0);
            if (elect()) {
                count_up(&g->cnt[0]);
                if (order == 5) {
                    asm volatile("st.shared.u32 [%0], %1;" ::"r"(s_par), "r"(launch) : "memory");
                    await_count(&g->cnt[0], (launch + 1) * kMPieces);
                    TRW(5);
#pragma unroll 1
                    for (int c = 0; c < 3; c++) {
                        mbar_expect_tx(bar_m + 8 * c, kWChunk);
                        bulk_g2s(s_m + c * kWChunk, g->img[launch & 1][0] + c * kWChunk, kWChunk, bar_m + 8 * c);
                    }
                }
            }
        } else if (order == 7) {
            if (cta < kWPieces) {
                const uint32_t s_wo = s_wv, s_wvr = s_wv + 12288;
                wait_until(t_start, TN(4, 0));
                if (elect()) {
                    mbar_expect_tx(bar_wop, 12288 + 6144);
                    tma_2d(s_wo, &maps.wo, bar_wop, 32 * (cta / 12), 0);
                    tma_3d(s_wvr, &maps.wqkv, bar_wop, 0, 16 * (cta % 12), 6);
                }
                mbar_wait(bar_wop, 0);
                TRW(2);
                w_piece(s_wo, s_wvr, cta, lane, g, (launch / kWPieces) & 1);
                __syncwarp();
                if (elect()) count_up(&g->cnt[1]);
                TRW(3);
            }
        } else if (order == 4 && elect()) {
#pragma unroll 1
            for (int c = 0; c < 3; c++) { wait_until(t_start, TN(1, 0) + c * TN(11, 0)); w.load_first(w.iu, w.iv, c); }
        }
        __syncwarp();
    }
    wait_until(t_start, TN(0, 0) + order * TN(3, 0));
    uint32_t fa[48];
    {
        RawX raw;
        load_raw(raw, x, o0, o1);
        if (order == 6 && elect()) {
#pragma unroll 1
            for (int c = 0; c < 3; c++) { wait_until(t_start, TN(2, 0) + c * TN(12, 0)); w.load_rest(w.iu, w.iv, 1, c); }
        }
        if (order == 5 && elect()) {
            wait_until(t_start, TN(5, 0));
            await_count(&g->cnt[1], (launch + 1) * kWPieces);
            mbar_expect_tx(bar_wv, kWBytes);
            bulk_g2s(s_wv, g->img[launch & 1][1], kWBytes, bar_wv);
            TRW(9);
        }
        if (order == 7 && elect()) {
            wait_until(t_start, TN(6, 0));
            if (TN(7, 0)) w.prefetch_rows(w.iu + du2, w.iv + dv2 + 3);
        }
        if (wg == 0) asm volatile("bar.sync 0, 256;" ::: "memory");
        raw_to_frags(raw, lds_volatile(s_zero), fa);
        pin(fa);
    }
    TR(2);

    constexpr uint32_t mdesc = desc_lo(s_m, 16), wdesc = desc_lo(s_wv, 16);
    constexpr uint32_t kdE = desc_lo(s_ring + kOffMid, 16), vdE = desc_lo(s_ring + kOffMid, kRingChunk);
    const uint32_t kdA = desc_lo(s_ring, 16) + wg * (kSlotStride >> 4), kdB = desc_lo(s_ring + kSlotStride, 16) - wg * (kSlotStride >> 4);
    constexpr uint32_t kToV = desc_lo(0, kRingChunk) - desc_lo(0, 16);

    float acc[96];
    uint32_t po[48];
    uint32_t c0, c1;
    asm volatile("" : "=r"(c0), "=r"(c1));
#pragma unroll
    for (int q = 0; q < 48; q++) asm volatile("" : "=r"(po[q]));
#pragma unroll 1
    for (int i = wg; i < w.ntiles; i += 2) {
        const bool first = i == 0, last = i == w.ntiles - 1;

        TR(8 + 16 * k);
        uint8_t *p0 = out + c0, *p1 = out + c1;
        const bool on = i >= 2;
        store_one(on, p0, p1, po, 0);
#pragma unroll 1
        for (uint32_t redo = 0;; redo++) {
            if (!first && !redo) turn_wait(wg);
            proj_gemm<3, 7>(acc, fa, mdesc, bar_m, [&](int s) { if (s >= 7 && s < 11) store_one(on, p0, p1, po, s - 6); });
            if (!first && !redo) turn_pass(wg);
            TR(9 + 16 * k);
            if (on) break;
            if (i == 1) mbar_wait(bar_wv, 0);
            if (image_complete(s_m + i * kWBytes, wg) || redo == 4096) break;
            wg_wait<0>();
            wg_sync(wg);
            if (wq == 0 && elect()) {
                mbar_expect_tx(bar_redo - 8 * wg, kWBytes);
                bulk_g2s(s_m + i * kWBytes, g->img[lds_volatile(s_par) & 1][i], kWBytes, bar_redo - 8 * wg);
            }
            mbar_wait(bar_redo - 8 * wg, (redo + (wg && cta < kWPieces)) & 1);
        }
        store_one(on, p0, p1, po, 5);
        wg_wait<6>(); store_one(on, p0, p1, po, 6);
        wg_wait<5>(); store_one(on, p0, p1, po, 7);
        wg_wait<4>(); store_one(on, p0, p1, po, 8);
        wg_wait<3>(); store_one(on, p0, p1, po, 9);
        wg_wait<2>(); store_one(on, p0, p1, po, 10);
        wg_wait<1>(); store_one(on, p0, p1, po, 11);
        TR(10 + 16 * k);
        c0 = o0; c1 = o1;
        w.pixel_offsets(tu + du2 + r8, tv + dv2 + 2 * wq, j, o0, o1);
        if (i + 2 >= w.ntiles) o0 = o1 = 0;
        wg_wait<0>();
        pin(acc);
        TR(11 + 16 * k);
        acc_to_frags(acc, fa);
        pin(fa);

        float sA[44], sE[16], sB[44];
        RawX nxt;
        if (!first) turn_wait(wg);
        mbar_wait(bar_a, w.corner ? i >> 1 : 0);
        wg_fence();
#pragma unroll
        for (int s = 0; s < 12; s++)
            if (s == 0) wgmma_n88<true>(sA, fa[4 * s], fa[4 * s + 1], fa[4 * s + 2], fa[4 * s + 3], desc_at(kdA, (s >> 2) * kRingChunk + (s & 3) * 32));
            else wgmma_n88<false>(sA, fa[4 * s], fa[4 * s + 1], fa[4 * s + 2], fa[4 * s + 3], desc_at(kdA, (s >> 2) * kRingChunk + (s & 3) * 32));
        wg_commit();
        if (!first) turn_pass(wg);
        TR(12 + 16 * k);
        if (LDGPOS == 0) load_raw(nxt, x, o0, o1);
        const int vq = tv + w.cv + 2 * wq;
        const int off0 = window_start(vq) - (tv + w.cv), off1 = window_start(vq + 1) - (tv + w.cv);
        const int t0 = 7 * off0 - j, t1 = 7 * off1 - j, tw = 7 * (off0 & ~1) - 2 * j;
        Masks mk;
        make_u_masks(mk, window_start(tu + w.cu + r8) - w.origin_u(tu), j);
        float v0[14], v1[14];
        uint32_t pa[28];
#pragma unroll
        for (int q = 0; q < 28; q++) pa[q] = 0;
        wg_wait<0>();
        pin(sA);
#pragma unroll
        for (int b = 0; b < 14; b++) v0[b] = v1[b] = __int_as_float(0xff800000);
        const int r7 = w.rev ? 7 : 0;
        gather_outer(sA, mk.h, t0 - r7, t1 - r7, w.rev, v0, v1);
        pin(v0); pin(v1);
        if (!first) turn_wait(wg);
#pragma unroll
        for (int c = 0; c < 3; c++) {
            mbar_wait(bar_b + 8 * c, wg);
            TR(64 + 4 * k + c);
            wg_fence();
#pragma unroll
            for (int s = 4 * c; s < 4 * c + 4; s++)
                if (s == 0) wgmma_n88<true>(sB, fa[4 * s], fa[4 * s + 1], fa[4 * s + 2], fa[4 * s + 3], desc_at(kdB, c * kRingChunk + (s & 3) * 32));
                else wgmma_n88<false>(sB, fa[4 * s], fa[4 * s + 1], fa[4 * s + 2], fa[4 * s + 3], desc_at(kdB, c * kRingChunk + (s & 3) * 32));
        }
        wg_commit();
#pragma unroll
        for (int s = 0; s < 12; s++)
            if (s == 0) wgmma_n32<true>(sE, fa[4 * s], fa[4 * s + 1], fa[4 * s + 2], fa[4 * s + 3], desc_at(kdE, (s >> 2) * kRingChunk + (s & 3) * 32));
            else wgmma_n32<false>(sE, fa[4 * s], fa[4 * s + 1], fa[4 * s + 2], fa[4 * s + 3], desc_at(kdE, (s >> 2) * kRingChunk + (s & 3) * 32));
        wg_commit();
        if (!last) turn_pass(wg);
        TR(13 + 16 * k);
        if (LDGPOS == 1) load_raw(nxt, x, o0, o1);
        wg_wait<1>();
        pin(sB);
        gather_outer(sB, mk.h, t0 - 7 + r7, t1 - 7 + r7, !w.rev, v0, v1);
        wg_wait<0>();
        pin(sE);
        TR(14 + 16 * k);
        gather_mid(sE, mk.h, t0, t1, j, v0, v1);
        const float m0 = quad_max(tree_max(v0)), m1 = quad_max(tree_max(v1));

        exp_scatter(v0, v1, m0, m1, tw, w.rev, lane, pa);
        pin(pa);
        TR(15 + 16 * k);
        if (LDGPOS == 2) load_raw(nxt, x, o0, o1);

        if (!last) turn_wait(wg + (pa[12] >> 31));
        wg_fence();
        wgmma_sp_n192_tb<true, 0>(acc, pa[0], pa[1], pa[2], pa[3], desc_at(kdA + kToV, 0), mk.meta[0]);
        wgmma_sp_n192_tb<false, 1>(acc, pa[4], pa[5], pa[6], pa[7], desc_at(kdA + kToV, 4096), mk.meta[0]);
        wgmma_sp_n192_tb<false, 0>(acc, pa[8], pa[9], pa[10], pa[11], desc_at(kdA + kToV, 8192), mk.meta[1]);
        wgmma_sp_n192_tb<false, 1>(acc, pa[12], pa[13], pa[14], pa[15], desc_at(vdE, 0), mk.meta[1]);
        wg_commit();
        wgmma_sp_n192_tb<false, 0>(acc, pa[16], pa[17], pa[18], pa[19], desc_at(kdB + kToV, 0), mk.meta[0]);
        wgmma_sp_n192_tb<false, 1>(acc, pa[20], pa[21], pa[22], pa[23], desc_at(kdB + kToV, 4096), mk.meta[0]);
        wgmma_sp_n192_tb<false, 0>(acc, pa[24], pa[25], pa[26], pa[27], desc_at(kdB + kToV, 8192), mk.meta[1]);
        wg_commit();
        if (!last) turn_pass(wg);
        TR(16 + 16 * k);
        const float s0 = tree_sum(v0), s1 = tree_sum(v1);
        if (LDGPOS == 3) load_raw(nxt, x, o0, o1);
        wg_wait<1>();
        wg_sync(wg);
        if (!last && elect()) {
            if (wq < 3) w.load_rest(tu + du1, tv + dv1, wg, wq);
            else if (TN(8, 1)) w.prefetch_rows(tu + du1 + du2, tv + dv1 + dv2 + 3);
        }
        __syncwarp();
        TR(17 + 16 * k);
        wg_wait<0>();
        pin(acc);
        TR(18 + 16 * k);
        if (w.corner && i == 1) {
            wg_sync(wg);
            if (wq < 3 && elect()) w.load_first(tu + du1, tv + dv1, wq);
            __syncwarp();
        }

        acc_to_frags(acc, po);
        pin(po);
        if (!last) turn_wait(wg);
        wg_fence();
        proj_gemm<0, 1>(acc, po, wdesc, 0, [](int) {});
        if (!last) turn_pass(wg);
        TR(19 + 16 * k);
        if (LDGPOS == 4) load_raw(nxt, x, o0, o1);
        const uint32_t zero = lds_volatile(s_zero);
        const float inv0 = rcp(quad_sum(s0 + __uint_as_float(zero))), inv1 = rcp(quad_sum(s1 + __uint_as_float(zero)));
        raw_to_frags(nxt, zero, fa);
        pin(fa);
        TR(20 + 16 * k);
        tu += du2; tv += dv2;
        wg_wait<0>();
        pin(acc);
        TR(21 + 16 * k);
        pack_out(acc, inv0, inv1, po);
        pin(po);
    }
    store_out(out, c0, c1, po);
    TR(7);
    TRG(1);
    TRDUMP();
}

typedef CUresult (*EncodeTiledFn)(CUtensorMap*, CUtensorMapDataType, cuuint32_t, void*, const cuuint64_t*, const cuuint64_t*,
                                  const cuuint32_t*, const cuuint32_t*, CUtensorMapInterleave, CUtensorMapSwizzle,
                                  CUtensorMapL2promotion, CUtensorMapFloatOOBfill);

bool make_maps(EncodeTiledFn fn, Maps* maps, void* x, void* wqkv, void* wo) {
    const cuuint64_t pix2 = 2 * kPixBytes, row = (cuuint64_t)kHW * kPixBytes;
    const cuuint32_t estr[5] = {1, 1, 1, 1, 1};
    bool ok = true;
    for (int tr = 0; tr < 2; tr++)
        for (int b = 0; b < 4; b++) {
            const cuuint64_t su = tr ? 2 * row : pix2, sv = tr ? pix2 : 2 * row;
            const cuuint64_t dims[5] = {2 * kC, b < 2 ? 2u : 1u, b < 2 ? 105u : 112u, 2, 112};
            const cuuint64_t strides[4] = {7 * su, su, row, sv};
            const cuuint32_t keys[5] = {64, 2, 7, 1, b ? 2u : 6u}, pixels[5] = {kC, 1, 8, 1, b == 2 ? 8u : 1u};
            ok = ok && fn(&maps->m[4 * tr + b], CU_TENSOR_MAP_DATA_TYPE_BFLOAT16, 5, x, dims, strides, b < 2 ? keys : pixels, estr,
                          CU_TENSOR_MAP_INTERLEAVE_NONE, b < 2 ? CU_TENSOR_MAP_SWIZZLE_128B : CU_TENSOR_MAP_SWIZZLE_NONE,
                          CU_TENSOR_MAP_L2_PROMOTION_L2_128B, CU_TENSOR_MAP_FLOAT_OOB_FILL_NONE) == CUDA_SUCCESS;
        }
    {
        const cuuint64_t dims[3] = {64, kC, 9}, strides[2] = {3 * kPixBytes, 128};
        const cuuint32_t box[3] = {64, 16, 3};
        ok = ok && fn(&maps->wqkv, CU_TENSOR_MAP_DATA_TYPE_BFLOAT16, 3, wqkv, dims, strides, box, estr, CU_TENSOR_MAP_INTERLEAVE_NONE,
                      CU_TENSOR_MAP_SWIZZLE_128B, CU_TENSOR_MAP_L2_PROMOTION_L2_128B, CU_TENSOR_MAP_FLOAT_OOB_FILL_NONE) == CUDA_SUCCESS;
    }
    {
        const cuuint64_t dims[2] = {kC, kC}, strides[1] = {kPixBytes};
        const cuuint32_t box[2] = {32, kC};
        ok = ok && fn(&maps->wo, CU_TENSOR_MAP_DATA_TYPE_BFLOAT16, 2, wo, dims, strides, box, estr, CU_TENSOR_MAP_INTERLEAVE_NONE,
                      CU_TENSOR_MAP_SWIZZLE_64B, CU_TENSOR_MAP_L2_PROMOTION_L2_128B, CU_TENSOR_MAP_FLOAT_OOB_FILL_NONE) == CUDA_SUCCESS;
    }
    return ok;
}

}

extern "C" void kernel_launch(void* const* d_in, const int* in_sizes, int n_in, void* d_out, int out_size) {
    static EncodeTiledFn encode = nullptr;
    static Scratch* scratch = nullptr;
    if (!encode) {
        cudaGetSymbolAddress((void**)&scratch, g_scratch);
        void* fn = nullptr;
        cudaDriverEntryPointQueryResult st;
        cudaGetDriverEntryPoint("cuTensorMapEncodeTiled", &fn, cudaEnableDefault, &st);
        encode = (EncodeTiledFn)fn;
        cudaFuncSetAttribute(nat_fused_kernel, cudaFuncAttributeMaxDynamicSharedMemorySize, kSmemBytes);
    }
    Maps maps;
    if (!encode || !make_maps(encode, &maps, d_in[0], d_in[1], d_in[2])) return;
    nat_fused_kernel<<<kGrid, kThreads, kSmemBytes>>>((const uint8_t*)d_in[0], (const uint8_t*)d_in[1], (uint8_t*)d_out, scratch, maps);
}
```

```cpp
#include <cuda_runtime.h>
#include <cuda_bf16.h>
#include <cuda.h>
#include <stdint.h>
#include <type_traits>
#include <stdlib.h>

#define LDGPOS 0
#define PREFETCH 1

namespace {

constexpr int kC          = 192;
constexpr int kHW         = 224;
constexpr int kPixBytes   = kC * 2;
constexpr int kSlotBytes  = 84 * 128;
constexpr int kMidBytes   = 28 * 128;
constexpr int kOffMid     = 88 * 128;
constexpr int kSlotStride = 120 * 128;
constexpr int kRingChunk  = 208 * 128;
constexpr int kWChunk     = 192 * 128;
constexpr int kWBytes     = 3 * kWChunk;
constexpr uint32_t kSmemBase = 1024;
constexpr uint32_t s_ring = kSmemBase, s_m = s_ring + 3 * kRingChunk, s_wv = s_m + kWBytes, s_bar = s_wv + kWBytes;
constexpr uint32_t bar_b = s_bar, bar_img = s_bar + 24, bar_redo = s_bar + 72, bar_wop = s_bar + 88, bar_a = s_bar + 96, bar_use = s_bar + 104;
constexpr uint32_t s_zero = s_ring + 84 * 128, s_par = s_bar + 120, s_trace = s_bar + 256;
constexpr int kSmemBytes  = s_trace + 2048 - kSmemBase;
constexpr int kThreads    = 384;
constexpr int kGrid       = 132;
constexpr int kPieces     = 144;
constexpr float kScaleLog2e = 0.07216878364870322f * 1.4426950408889634f;

struct Maps {
    CUtensorMap m[6];
    CUtensorMap wo, wv;
};
#define TN(i, dflt) (dflt)

struct Scratch {
    uint8_t img[2][2][kWBytes];
    uint32_t cnt[3];
};
__device__ __align__(1024) Scratch g_scratch;

#define WO4(i) "=f"(d[i]), "=f"(d[i + 1]), "=f"(d[i + 2]), "=f"(d[i + 3])
#define RW4(i) "+f"(d[i]), "+f"(d[i + 1]), "+f"(d[i + 2]), "+f"(d[i + 3])

template <bool FIRST>
__device__ __forceinline__ void wgmma_n192(float (&d)[96], uint32_t a0, uint32_t a1, uint32_t a2, uint32_t a3, uint64_t descb) {
    if constexpr (FIRST) {
        asm volatile(
            "wgmma.mma_async.sync.aligned.m64n192k16.f32.bf16.bf16 "
            "{%0, %1, %2, %3, %4, %5, %6, %7, %8, %9, %10, %11, %12, %13, %14, %15, %16, %17, %18, %19, %20, %21, %22, %23, "
            "%24, %25, %26, %27, %28, %29, %30, %31, %32, %33, %34, %35, %36, %37, %38, %39, %40, %41, %42, %43, %44, %45, %46, %47, "
            "%48, %49, %50, %51, %52, %53, %54, %55, %56, %57, %58, %59, %60, %61, %62, %63, %64, %65, %66, %67, %68, %69, %70, %71, "
            "%72, %73, %74, %75, %76, %77, %78, %79, %80, %81, %82, %83, %84, %85, %86, %87, %88, %89, %90, %91, %92, %93, %94, %95}, "
            "{%96, %97, %98, %99}, %100, 0, 1, 1, 0;"
            : WO4(0), WO4(4), WO4(8), WO4(12), WO4(16), WO4(20), WO4(24), WO4(28), WO4(32), WO4(36), WO4(40), WO4(44),
              WO4(48), WO4(52), WO4(56), WO4(60), WO4(64), WO4(68), WO4(72), WO4(76), WO4(80), WO4(84), WO4(88), WO4(92)
            : "r"(a0), "r"(a1), "r"(a2), "r"(a3), "l"(descb));
    } else {
        asm volatile(
            "wgmma.mma_async.sync.aligned.m64n192k16.f32.bf16.bf16 "
            "{%0, %1, %2, %3, %4, %5, %6, %7, %8, %9, %10, %11, %12, %13, %14, %15, %16, %17, %18, %19, %20, %21, %22, %23, "
            "%24, %25, %26, %27, %28, %29, %30, %31, %32, %33, %34, %35, %36, %37, %38, %39, %40, %41, %42, %43, %44, %45, %46, %47, "
            "%48, %49, %50, %51, %52, %53, %54, %55, %56, %57, %58, %59, %60, %61, %62, %63, %64, %65, %66, %67, %68, %69, %70, %71, "
            "%72, %73, %74, %75, %76, %77, %78, %79, %80, %81, %82, %83, %84, %85, %86, %87, %88, %89, %90, %91, %92, %93, %94, %95}, "
            "{%96, %97, %98, %99}, %100, 1, 1, 1, 0;"
            : RW4(0), RW4(4), RW4(8), RW4(12), RW4(16), RW4(20), RW4(24), RW4(28), RW4(32), RW4(36), RW4(40), RW4(44),
              RW4(48), RW4(52), RW4(56), RW4(60), RW4(64), RW4(68), RW4(72), RW4(76), RW4(80), RW4(84), RW4(88), RW4(92)
            : "r"(a0), "r"(a1), "r"(a2), "r"(a3), "l"(descb));
    }
}

template <bool FIRST>
__device__ __forceinline__ void wgmma_n88(float (&d)[44], uint32_t a0, uint32_t a1, uint32_t a2, uint32_t a3, uint64_t descb) {
    if constexpr (FIRST) {
        asm volatile(
            "wgmma.mma_async.sync.aligned.m64n88k16.f32.bf16.bf16 "
            "{%0, %1, %2, %3, %4, %5, %6, %7, %8, %9, %10, %11, %12, %13, %14, %15, %16, %17, %18, %19, %20, %21, %22, %23, "
            "%24, %25, %26, %27, %28, %29, %30, %31, %32, %33, %34, %35, %36, %37, %38, %39, %40, %41, %42, %43}, "
            "{%44, %45, %46, %47}, %48, 0, 1, 1, 0;"
            : WO4(0), WO4(4), WO4(8), WO4(12), WO4(16), WO4(20), WO4(24), WO4(28), WO4(32), WO4(36), WO4(40)
            : "r"(a0), "r"(a1), "r"(a2), "r"(a3), "l"(descb));
    } else {
        asm volatile(
            "wgmma.mma_async.sync.aligned.m64n88k16.f32.bf16.bf16 "
            "{%0, %1, %2, %3, %4, %5, %6, %7, %8, %9, %10, %11, %12, %13, %14, %15, %16, %17, %18, %19, %20, %21, %22, %23, "
            "%24, %25, %26, %27, %28, %29, %30, %31, %32, %33, %34, %35, %36, %37, %38, %39, %40, %41, %42, %43}, "
            "{%44, %45, %46, %47}, %48, 1, 1, 1, 0;"
            : RW4(0), RW4(4), RW4(8), RW4(12), RW4(16), RW4(20), RW4(24), RW4(28), RW4(32), RW4(36), RW4(40)
            : "r"(a0), "r"(a1), "r"(a2), "r"(a3), "l"(descb));
    }
}

template <bool FIRST>
__device__ __forceinline__ void wgmma_n32(float (&d)[16], uint32_t a0, uint32_t a1, uint32_t a2, uint32_t a3, uint64_t descb) {
    if constexpr (FIRST) {
        asm volatile(
            "wgmma.mma_async.sync.aligned.m64n32k16.f32.bf16.bf16 "
            "{%0, %1, %2, %3, %4, %5, %6, %7, %8, %9, %10, %11, %12, %13, %14, %15}, "
            "{%16, %17, %18, %19}, %20, 0, 1, 1, 0;"
            : WO4(0), WO4(4), WO4(8), WO4(12)
            : "r"(a0), "r"(a1), "r"(a2), "r"(a3), "l"(descb));
    } else {
        asm volatile(
            "wgmma.mma_async.sync.aligned.m64n32k16.f32.bf16.bf16 "
            "{%0, %1, %2, %3, %4, %5, %6, %7, %8, %9, %10, %11, %12, %13, %14, %15}, "
            "{%16, %17, %18, %19}, %20, 1, 1, 1, 0;"
            : RW4(0), RW4(4), RW4(8), RW4(12)
            : "r"(a0), "r"(a1), "r"(a2), "r"(a3), "l"(descb));
    }
}

template <bool FIRST, int SEL>
__device__ __forceinline__ void wgmma_sp_n192_tb(float (&d)[96], uint32_t a0, uint32_t a1, uint32_t a2, uint32_t a3, uint64_t descb, uint32_t meta) {
    if constexpr (FIRST) {
        asm volatile(
            "wgmma.mma_async.sp.sync.aligned.m64n192k32.f32.bf16.bf16 "
            "{%0, %1, %2, %3, %4, %5, %6, %7, %8, %9, %10, %11, %12, %13, %14, %15, %16, %17, %18, %19, %20, %21, %22, %23, "
            "%24, %25, %26, %27, %28, %29, %30, %31, %32, %33, %34, %35, %36, %37, %38, %39, %40, %41, %42, %43, %44, %45, %46, %47, "
            "%48, %49, %50, %51, %52, %53, %54, %55, %56, %57, %58, %59, %60, %61, %62, %63, %64, %65, %66, %67, %68, %69, %70, %71, "
            "%72, %73, %74, %75, %76, %77, %78, %79, %80, %81, %82, %83, %84, %85, %86, %87, %88, %89, %90, %91, %92, %93, %94, %95}, "
            "{%96, %97, %98, %99}, %100, %101, %102, 0, 1, 1, 1;"
            : WO4(0), WO4(4), WO4(8), WO4(12), WO4(16), WO4(20), WO4(24), WO4(28), WO4(32), WO4(36), WO4(40), WO4(44),
              WO4(48), WO4(52), WO4(56), WO4(60), WO4(64), WO4(68), WO4(72), WO4(76), WO4(80), WO4(84), WO4(88), WO4(92)
            : "r"(a0), "r"(a1), "r"(a2), "r"(a3), "l"(descb), "r"(meta), "n"(SEL));
    } else {
        asm volatile(
            "wgmma.mma_async.sp.sync.aligned.m64n192k32.f32.bf16.bf16 "
            "{%0, %1, %2, %3, %4, %5, %6, %7, %8, %9, %10, %11, %12, %13, %14, %15, %16, %17, %18, %19, %20, %21, %22, %23, "
            "%24, %25, %26, %27, %28, %29, %30, %31, %32, %33, %34, %35, %36, %37, %38, %39, %40, %41, %42, %43, %44, %45, %46, %47, "
            "%48, %49, %50, %51, %52, %53, %54, %55, %56, %57, %58, %59, %60, %61, %62, %63, %64, %65, %66, %67, %68, %69, %70, %71, "
            "%72, %73, %74, %75, %76, %77, %78, %79, %80, %81, %82, %83, %84, %85, %86, %87, %88, %89, %90, %91, %92, %93, %94, %95}, "
            "{%96, %97, %98, %99}, %100, %101, %102, 1, 1, 1, 1;"
            : RW4(0), RW4(4), RW4(8), RW4(12), RW4(16), RW4(20), RW4(24), RW4(28), RW4(32), RW4(36), RW4(40), RW4(44),
              RW4(48), RW4(52), RW4(56), RW4(60), RW4(64), RW4(68), RW4(72), RW4(76), RW4(80), RW4(84), RW4(88), RW4(92)
            : "r"(a0), "r"(a1), "r"(a2), "r"(a3), "l"(descb), "r"(meta), "n"(SEL));
    }
}

#define TR(slot)
#define TRW(slot)
#define TRG(slot)
#define TRDUMP()

__device__ __forceinline__ void wg_fence() { asm volatile("wgmma.fence.sync.aligned;" ::: "memory"); }
__device__ __forceinline__ void wg_commit() { asm volatile("wgmma.commit_group.sync.aligned;" ::: "memory"); }
template <int N>
__device__ __forceinline__ void wg_wait() { asm volatile("wgmma.wait_group.sync.aligned %0;" ::"n"(N) : "memory"); }

template <int N>
__device__ __forceinline__ void pin(float (&d)[N]) {
#pragma unroll
    for (int i = 0; i < N; i++) asm volatile("" : "+f"(d[i])::"memory");
}
template <int N>
__device__ __forceinline__ void pin(uint32_t (&d)[N]) {
#pragma unroll
    for (int i = 0; i < N; i++) asm volatile("" : "+r"(d[i])::"memory");
}

__device__ __forceinline__ constexpr uint32_t desc_lo(uint32_t addr, uint32_t lbo) { return (addr >> 4) | ((lbo >> 4) << 16); }
__device__ __forceinline__ uint64_t desc_at(uint32_t lo, uint32_t byte_off) {
    return ((uint64_t)((1u << 30) | (1024u >> 4)) << 32) | (uint64_t)(lo + (byte_off >> 4));
}

__device__ __forceinline__ void mbar_init(uint32_t bar, uint32_t count) {
    asm volatile("mbarrier.init.shared::cta.b64 [%0], %1;" ::"r"(bar), "r"(count) : "memory");
}
__device__ __forceinline__ void mbar_expect_tx(uint32_t bar, uint32_t bytes) {
    asm volatile("mbarrier.arrive.expect_tx.shared::cta.b64 _, [%0], %1;" ::"r"(bar), "r"(bytes) : "memory");
}
__device__ __forceinline__ void mbar_arrive(uint32_t bar) {
    asm volatile("mbarrier.arrive.shared::cta.b64 _, [%0];" ::"r"(bar) : "memory");
}
__device__ __forceinline__ void mbar_wait(uint32_t bar, uint32_t parity) {
    asm volatile(
        "{\n.reg .pred p;\n"
        "W: mbarrier.try_wait.parity.shared::cta.b64 p, [%0], %1;\n"
        "@!p bra W;\n}\n"
        ::"r"(bar), "r"(parity) : "memory");
}
__device__ __forceinline__ uint32_t clock_now() {
    uint32_t c;
    asm volatile("mov.u32 %0, %%clock;" : "=r"(c)::"memory");
    return c;
}
__device__ __forceinline__ void wait_until(uint32_t t0, int t) {
    if (t == 0) return;
    while ((int)(clock_now() - t0) < t) {}
}
__device__ __forceinline__ bool elect() {
    uint32_t ok;
    asm volatile("{\n.reg .pred p;\nelect.sync _|p, 0xffffffff;\nselp.u32 %0, 1, 0, p;\n}\n" : "=r"(ok));
    return ok != 0;
}
__device__ __forceinline__ void turn_wait(int wg) { asm volatile("bar.sync %0, 256;" ::"r"(1 + wg) : "memory"); }
__device__ __forceinline__ void turn_pass(int wg) { asm volatile("bar.arrive %0, 256;" ::"r"(2 - wg) : "memory"); }
__device__ __forceinline__ void wg_sync(int wg) { asm volatile("bar.sync %0, 128;" ::"r"(3 + wg) : "memory"); }

__device__ __forceinline__ void tma_box(uint32_t dst, const CUtensorMap* map, uint32_t bar, int c0, int c2, int c3, int c4) {
    asm volatile(
        "cp.async.bulk.tensor.5d.shared::cluster.global.mbarrier::complete_tx::bytes [%0], [%1, {%3, %4, %5, %6, %7}], [%2];"
        ::"r"(dst), "l"(map), "r"(bar), "r"(c0), "r"(0), "r"(c2), "r"(c3), "r"(c4)
        : "memory");
}
__device__ __forceinline__ void tma_3d(uint32_t dst, const CUtensorMap* map, uint32_t bar, int c1, int c2) {
    asm volatile("cp.async.bulk.tensor.3d.shared::cluster.global.mbarrier::complete_tx::bytes [%0], [%1, {%3, %4, %5}], [%2];"
                 ::"r"(dst), "l"(map), "r"(bar), "r"(0), "r"(c1), "r"(c2)
                 : "memory");
}
__device__ __forceinline__ void tma_prefetch(const CUtensorMap* map, int c0, int c2, int c3, int c4) {
    asm volatile("cp.async.bulk.prefetch.tensor.5d.L2.global [%0, {%1, %2, %3, %4, %5}];"
                 ::"l"(map), "r"(c0), "r"(0), "r"(c2), "r"(c3), "r"(c4)
                 : "memory");
}
__device__ __forceinline__ void prefetch_map(const CUtensorMap* map) {
    asm volatile("prefetch.tensormap [%0];" ::"l"(map) : "memory");
}
__device__ __forceinline__ uint4 ldg(const void* p) {
    uint4 v;
    asm volatile("ld.global.v4.u32 {%0, %1, %2, %3}, [%4];" : "=r"(v.x), "=r"(v.y), "=r"(v.z), "=r"(v.w) : "l"(p) : "memory");
    return v;
}
__device__ __forceinline__ void stg128(void* p, uint32_t a, uint32_t b, uint32_t c, uint32_t d) {
    asm volatile("st.global.v4.u32 [%0], {%1, %2, %3, %4};" ::"l"(p), "r"(a), "r"(b), "r"(c), "r"(d) : "memory");
}
__device__ __forceinline__ uint32_t pack_bf16(float lo, float hi) {
    uint32_t r;
    asm("cvt.rn.bf16x2.f32 %0, %1, %2;" : "=r"(r) : "f"(hi), "f"(lo));
    return r;
}
__device__ __forceinline__ float ex2(float x) {
    float y;
    asm("ex2.approx.ftz.f32 %0, %1;" : "=f"(y) : "f"(x));
    return y;
}
__device__ __forceinline__ float rcp(float x) {
    float y;
    asm("rcp.approx.ftz.f32 %0, %1;" : "=f"(y) : "f"(x));
    return y;
}
__device__ __forceinline__ void mma16816(float (&d)[4], uint32_t a0, uint32_t a1, uint32_t a2, uint32_t a3, uint32_t b0, uint32_t b1) {
    asm volatile("mma.sync.aligned.m16n8k16.row.col.f32.bf16.bf16.f32 {%0, %1, %2, %3}, {%4, %5, %6, %7}, {%8, %9}, {%0, %1, %2, %3};"
                 : "+f"(d[0]), "+f"(d[1]), "+f"(d[2]), "+f"(d[3])
                 : "r"(a0), "r"(a1), "r"(a2), "r"(a3), "r"(b0), "r"(b1));
}
__device__ __forceinline__ uint32_t lds_volatile(uint32_t addr) {
    uint32_t v;
    asm volatile("ld.volatile.shared.u32 %0, [%1];" : "=r"(v) : "r"(addr) : "memory");
    return v;
}

__device__ __forceinline__ int window_start(int i_shifted) { return min(max(i_shifted, 0), 105); }

struct Work {
    int cu, cv;
    uint32_t su, sv;
    int iu, iv;
    int corner, ntiles;
    int rev;
    const CUtensorMap* map;
    int c0, c3;
    __device__ __forceinline__ int origin_u(int u) const { return min(max(u + cu, 0), 98); }
    __device__ __forceinline__ void pixel_offsets(int u, int v, int j, uint32_t& o0, uint32_t& o1) const {
        const uint32_t base = (u + window_start(u + cu) + (cu ? 0 : 7)) * su + j * 16 + (v + (cv ? 0 : 7)) * sv;
        o0 = base + window_start(v + cv) * sv;
        o1 = base + (window_start(v + 1 + cv) + 1) * sv;
    }
    __device__ __forceinline__ void load_keys(int u, int v, bool first, int slot) const {
#pragma unroll 1
        for (int c = 0; c < 3; c++) {
            const uint32_t bar = first ? bar_a : bar_b + 8 * c;
            mbar_expect_tx(bar, first ? kSlotBytes : kSlotBytes + kMidBytes);
            tma_box(s_ring + c * kRingChunk + slot * kSlotStride, map, bar, c0 + 64 * c, origin_u(u), c3, v + cv + (first ? rev : 8 - rev));
            if (!first) tma_box(s_ring + c * kRingChunk + kOffMid + 512, map + 1, bar, c0 + 64 * c, origin_u(u), c3, v + cv + 6);
        }
    }
    __device__ __forceinline__ void prefetch_rows(int u, int v) const { tma_prefetch(map + 2, c0, u, c3, v + cv); }
};

__device__ __forceinline__ Work decode_work(const Maps& maps, int c) {
    Work w;
    const int idx = c >> 2, ypar = (c >> 1) & 1, xpar = c & 1;
    const bool transposed = (idx >> 2) == 7;
    w.corner = idx == 32;
    w.cu = 6 * (transposed ? ypar : xpar) - 6;
    w.cv = 6 * (transposed ? xpar : ypar) - 6;
    w.su = transposed ? kHW * kPixBytes : kPixBytes;
    w.sv = transposed ? kPixBytes : kHW * kPixBytes;
    w.iu = idx < 28 ? 8 * (idx >> 1) : 96 + 4 * (idx & 2);
    w.rev = w.corner ? 0 : 8 * (idx & 1);
    w.iv = w.corner ? 96 : 48 - w.rev;
    w.ntiles = w.corner ? 4 : 6;
    w.map = &maps.m[transposed ? 3 : 0];
    w.c0 = xpar * kC;
    w.c3 = ypar;
    return w;
}

struct RawX { uint4 a[6], b[6]; };
__device__ __forceinline__ void load_raw(RawX& r, const uint8_t* base, uint32_t o0, uint32_t o1) {
    __syncwarp();
#pragma unroll
    for (int c = 0; c < 6; c++) { r.a[c] = ldg(base + o0 + c * 64); r.b[c] = ldg(base + o1 + c * 64); }
    __syncwarp();
}
__device__ __forceinline__ void raw_to_frags(const RawX& r, uint32_t zero, uint32_t (&f)[48]) {
#pragma unroll
    for (int c = 0; c < 6; c++) {
        f[8 * c + 0] = r.a[c].x ^ zero; f[8 * c + 2] = r.a[c].z ^ zero; f[8 * c + 4] = r.a[c].y ^ zero; f[8 * c + 6] = r.a[c].w ^ zero;
        f[8 * c + 1] = r.b[c].x ^ zero; f[8 * c + 3] = r.b[c].z ^ zero; f[8 * c + 5] = r.b[c].y ^ zero; f[8 * c + 7] = r.b[c].w ^ zero;
    }
}
__device__ __forceinline__ void acc_to_frags(const float (&d)[96], uint32_t (&f)[48]) {
#pragma unroll
    for (int i = 0; i < 48; i++) f[i] = pack_bf16(d[2 * i], d[2 * i + 1]);
}

template <int NBARS, int GROUPS, class F>
__device__ __forceinline__ void proj_gemm(float (&d)[96], const uint32_t (&a)[48], uint32_t wdesc, uint32_t wbar, F after) {
#pragma unroll
    for (int c = 0; c < 3; c++) {
        if (c < NBARS) { mbar_wait(wbar + 8 * c, 0); wg_fence(); }
#pragma unroll
        for (int s = 4 * c; s < 4 * c + 4; s++) {
            if (s == 0) wgmma_n192<true>(d, a[4 * s], a[4 * s + 1], a[4 * s + 2], a[4 * s + 3], desc_at(wdesc, c * kWChunk + (s & 3) * 32));
            else wgmma_n192<false>(d, a[4 * s], a[4 * s + 1], a[4 * s + 2], a[4 * s + 3], desc_at(wdesc, c * kWChunk + (s & 3) * 32));
            if (s >= 12 - GROUPS) wg_commit();
            after(s);
        }
    }
}
__device__ __forceinline__ void pack_out(const float (&acc)[96], float i0, float i1, uint32_t (&po)[48]) {
#pragma unroll
    for (int g = 0; g < 6; g++)
#pragma unroll
        for (int q = 0; q < 4; q++) {
            po[8 * g + q] = pack_bf16(acc[16 * g + 4 * q] * i0, acc[16 * g + 4 * q + 1] * i0);
            po[8 * g + 4 + q] = pack_bf16(acc[16 * g + 4 * q + 2] * i1, acc[16 * g + 4 * q + 3] * i1);
        }
}
__device__ __forceinline__ void store_one(bool on, uint8_t* p0, uint8_t* p1, const uint32_t (&po)[48], int n) {
    asm volatile("{\n.reg .pred p;\nsetp.ne.u32 p, %5, 0;\nbar.warp.sync 0xffffffff;\n@p st.global.v4.u32 [%0], {%1, %2, %3, %4};\n}\n"
                 ::"l"(((n & 1) ? p1 : p0) + (n >> 1) * 64), "r"(po[4 * n]), "r"(po[4 * n + 1]), "r"(po[4 * n + 2]), "r"(po[4 * n + 3]), "r"((uint32_t)on) : "memory");
}
__device__ __forceinline__ void store_out(uint8_t* out, uint32_t o0, uint32_t o1, const uint32_t (&po)[48]) {
#pragma unroll
    for (int g = 0; g < 6; g++) {
        stg128(out + o0 + g * 64, po[8 * g], po[8 * g + 1], po[8 * g + 2], po[8 * g + 3]);
        stg128(out + o1 + g * 64, po[8 * g + 4], po[8 * g + 5], po[8 * g + 6], po[8 * g + 7]);
    }
}

struct Masks {
    uint32_t h;
    uint32_t meta[2];
};

__device__ __forceinline__ void make_u_masks(Masks& m, int offu, int j) {
    m.h = (((1u << offu) - 1u) * 0x4081u) >> j;
    uint32_t y = __byte_perm(m.h, 0, 0x4140);
    y = (y | (y << 4)) & 0x0f0f0f0fu;
    y = (y | (y << 2)) & 0x33333333u;
    y = (y | (y << 1)) & 0x55555555u;
    m.meta[0] = __byte_perm(y | 0x8888u, 0, 0x1010);
    m.meta[1] = __byte_perm((y >> (8 - (j & 2))) | 0x8888u, 0, 0x1010);
}

template <int N>
__device__ __forceinline__ float tree_max(const float (&v)[N]) {
    float t[N];
#pragma unroll
    for (int i = 0; i < N; i++) t[i] = v[i];
#pragma unroll
    for (int w = 1; w < N; w *= 2)
#pragma unroll
        for (int i = 0; i + w < N; i += 2 * w) t[i] = fmaxf(t[i], t[i + w]);
    return t[0];
}
template <int N>
__device__ __forceinline__ float tree_sum(const float (&v)[N]) {
    float t[N];
#pragma unroll
    for (int i = 0; i < N; i++) t[i] = v[i];
#pragma unroll
    for (int w = 1; w < N; w *= 2)
#pragma unroll
        for (int i = 0; i + w < N; i += 2 * w) t[i] += t[i + w];
    return t[0];
}

template <int B>
__device__ __forceinline__ void pick(uint32_t h, bool ok0, bool ok1, const float* s, float& v0, float& v1) {
    asm("{\n.reg .pred p, q0, q1;\n.reg .b32 t;\nand.b32 t, %6, %7;\nsetp.ne.u32 p, t, 0;\n"
        "setp.ne.u32 q0, %8, 0;\nsetp.ne.u32 q1, %9, 0;\n"
        "@q0 selp.f32 %0, %3, %2, p;\n@q1 selp.f32 %1, %5, %4, p;\n}\n"
        : "+f"(v0), "+f"(v1)
        : "f"(s[0]), "f"(s[1]), "f"(s[2]), "f"(s[3]), "r"(h), "n"(1 << ((4 * B) % 7)), "r"((uint32_t)ok0), "r"((uint32_t)ok1));
}
template <int B, class F>
__device__ __forceinline__ void for_blocks(F f) {
    if constexpr (B > 0) { for_blocks<B - 1>(f); f(std::integral_constant<int, B - 1>{}); }
}
__device__ __forceinline__ void gather_outer(const float (&s)[44], uint32_t h, int t0, int t1, bool late, float (&v0)[14], float (&v1)[14]) {
    for_blocks<11>([&](auto B) {
        constexpr int b = B.value < 8 ? (B.value >> 1) + 7 * (B.value & 1) : B.value - 4;
        pick<b>(h, (t0 <= 4 * b) != late, (t1 <= 4 * b) != late, &s[4 * b], v0[b], v1[b]);
    });
}
__device__ __forceinline__ void gather_mid(const float (&sE)[16], uint32_t h, int t0, int t1, int j, float (&v0)[14], float (&v1)[14]) {
    for_blocks<4>([&](auto B) {
        constexpr int b = 10 + B.value;
        pick<b>(h, (b > 10 || j >= 2) && (b < 12 || t0 > 4 * b - 49) && (b > 12 || t0 <= 4 * b),
                   (b > 10 || j >= 2) && (b < 12 || t1 > 4 * b - 49) && (b > 12 || t1 <= 4 * b), &sE[4 * B.value], v0[b], v1[b]);
    });
}
__device__ __forceinline__ float quad_max(float m) {
    m = fmaxf(m, __shfl_xor_sync(0xffffffffu, m, 1));
    return fmaxf(m, __shfl_xor_sync(0xffffffffu, m, 2));
}
__device__ __forceinline__ float quad_sum(float s) {
    s += __shfl_xor_sync(0xffffffffu, s, 1);
    return s + __shfl_xor_sync(0xffffffffu, s, 2);
}
__device__ __forceinline__ void exp_scatter(float (&v0)[14], float (&v1)[14], float m0, float m1, int tw, bool rev, int lane, uint32_t (&pa)[28]) {
    const int j = lane & 3;
    const int src1 = (lane & ~3) | ((j & 1) << 1) | (j >> 1);
    const int src2 = src1 ^ 1;
    const uint32_t selr = j < 2 ? 0x5410u : 0x1054u;
    const uint32_t selr8 = j < 2 ? 0x7632u : 0x3276u;
    const bool even = (j & 1) == 0;
#pragma unroll
    for (int b = 0; b < 14; b++) { v0[b] = ex2(v0[b] - m0); v1[b] = ex2(v1[b] - m1); }
#pragma unroll
    for (int b = 0; b < 14; b += 2) {
        const uint32_t x0 = pack_bf16(v0[b], v1[b]), x1 = pack_bf16(v0[b + 1], v1[b + 1]);
        const uint32_t u = __shfl_sync(0xffffffffu, even ? x0 : x1, src1);
        const uint32_t w = __shfl_sync(0xffffffffu, even ? x1 : x0, src2);
        if (b < 12)
            asm("{\n.reg .pred p, q;\nsetp.ne.u32 p, %8, 0;\nsetp.ne.u32 q, %9, 0;\n"
                "@p prmt.b32 %0, %4, %5, %6;\n@p prmt.b32 %1, %4, %5, %7;\n"
                "@q prmt.b32 %2, %4, %5, %6;\n@q prmt.b32 %3, %4, %5, %7;\n}\n"
                : "+r"(pa[b]), "+r"(pa[b + 1]), "+r"(pa[16 + b]), "+r"(pa[17 + b])
                : "r"(u), "r"(w), "r"(selr), "r"(selr8), "r"((uint32_t)((4 * b >= tw) != rev && (b < 10 || j == 0))),
                  "r"((uint32_t)((4 * b >= tw) == rev && (b < 10 || j == 0))));
        if (b >= 10) { pa[b + 2] = __byte_perm(u, w, selr); pa[b + 3] = __byte_perm(u, w, selr8); }
    }
}

__device__ __forceinline__ uint32_t wimg_offset(uint32_t row, uint32_t s, uint32_t j) {
    return (s >> 2) * kWChunk + row * 128 + (((2 * (s & 3) + (j >> 1)) ^ (row & 7)) << 4) + (j & 1) * 8;
}

__device__ __forceinline__ void ldsm4(uint32_t (&r)[4], uint32_t addr) {
    asm volatile("ldmatrix.sync.aligned.m8n8.x4.shared.b16 {%0, %1, %2, %3}, [%4];" : "=r"(r[0]), "=r"(r[1]), "=r"(r[2]), "=r"(r[3]) : "r"(addr) : "memory");
}
__device__ __forceinline__ void ldsm4_t(uint32_t (&r)[4], uint32_t addr) {
    asm volatile("ldmatrix.sync.aligned.m8n8.x4.trans.shared.b16 {%0, %1, %2, %3}, [%4];" : "=r"(r[0]), "=r"(r[1]), "=r"(r[2]), "=r"(r[3]) : "r"(addr) : "memory");
}
__device__ __forceinline__ void m_partial(const uint8_t* wqkv, uint32_t mt, uint32_t sp, uint32_t q, uint32_t lane) {
    const uint32_t r8 = lane >> 2, col = q * 128 + (lane & 3) * 16;
    const uint8_t* pa = wqkv + (16 * mt + r8) * 1152 + col;
    const uint8_t* pb = wqkv + (32 * sp + 8 * (r8 & 2) + (r8 & 5)) * 1152 + col;
    uint4 A[2][2], B[4][2];
#pragma unroll
    for (int c = 0; c < 2; c++) {
#pragma unroll
        for (int h = 0; h < 2; h++) A[h][c] = ldg(pa + 384 + h * 8 * 1152 + c * 64);
#pragma unroll
        for (int n = 0; n < 4; n++) B[n][c] = ldg(pb + ((n & 1) * 8 + (n & 2)) * 1152 + c * 64);
    }
#pragma unroll
    for (int n = 0; n < 4; n++) {
        float d[4] = {0.f, 0.f, 0.f, 0.f};
#pragma unroll
        for (int c = 0; c < 2; c++) {
            mma16816(d, A[0][c].x, A[1][c].x, A[0][c].y, A[1][c].y, B[n][c].x, B[n][c].y);
            mma16816(d, A[0][c].z, A[1][c].z, A[0][c].w, A[1][c].w, B[n][c].z, B[n][c].w);
        }
        asm volatile("st.shared.v4.f32 [%0], {%1, %2, %3, %4};" ::"r"(s_wv + q * 2048 + n * 512 + lane * 16), "f"(d[0]), "f"(d[1]), "f"(d[2]), "f"(d[3]) : "memory");
    }
}
__device__ __forceinline__ void m_reduce(uint32_t e, uint32_t lane, float (&d)[2][4]) {
#pragma unroll
    for (int n = 0; n < 2; n++) {
        float t[3][4];
#pragma unroll
        for (int q = 0; q < 3; q++)
            asm volatile("ld.shared.v4.f32 {%0, %1, %2, %3}, [%4];" : "=f"(t[q][0]), "=f"(t[q][1]), "=f"(t[q][2]), "=f"(t[q][3]) : "r"(s_wv + q * 2048 + e * 1024 + n * 512 + lane * 16) : "memory");
#pragma unroll
        for (int i = 0; i < 4; i++) d[n][i] = (t[0][i] + t[1][i] + t[2][i]) * kScaleLog2e;
    }
}
__device__ __forceinline__ void w_piece(uint32_t q, uint32_t lane, float (&d)[2][4]) {
    const uint32_t rr = lane & 7, mi = lane >> 3, kr = 4 * (rr >> 1) + (mi & 2) + (rr & 1);
    const uint32_t pa = s_wv + q * 6144 + (4 * (mi & 2) + rr) * 32 + (((mi ^ (rr >> 2)) & 1) << 4);
    const uint32_t pb = s_wv + 3 * 6144 + kr * 32 + (((mi ^ (kr >> 2)) & 1) << 4);
#pragma unroll
    for (int i = 0; i < 8; i++) (&d[0][0])[i] = 0.f;
#pragma unroll 2
    for (int k = 0; k < 12; k++) {
        uint32_t aq[4], bq[4];
        ldsm4_t(aq, pa + k * 512);
        ldsm4(bq, pb + k * 512);
        mma16816(d[0], aq[0], aq[1], aq[2], aq[3], bq[0], bq[1]);
        mma16816(d[1], aq[0], aq[1], aq[2], aq[3], bq[2], bq[3]);
    }
}
__device__ __forceinline__ void piece_store(Scratch* g, uint32_t par, uint32_t which, uint32_t s, uint32_t mt, uint32_t lane, const float (&d)[2][4]) {
    const uint32_t r8 = lane >> 2;
    const uint32_t row = which ? 32 * (mt >> 1) + 8 * (r8 >> 1) + 4 * (mt & 1) + (r8 & 1) : 16 * mt + r8;
#pragma unroll
    for (int hf = 0; hf < 2; hf++) {
        const uint32_t off = which * kWBytes + (wimg_offset(row, s, lane & 3) ^ (hf ? which ? 288 : 1024 : 0));
        const uint32_t a = pack_bf16(d[0][2 * hf], d[0][2 * hf + 1]), b = pack_bf16(d[1][2 * hf], d[1][2 * hf + 1]);
        asm volatile("st.relaxed.gpu.global.v2.u32 [%0], {%1, %2};" ::"l"(g->img[par][0] + off), "r"(a ? a : 0x8000u), "r"(b) : "memory");
        asm volatile("st.relaxed.gpu.global.v2.u32 [%0], {%1, %1};" ::"l"(g->img[par ^ 1][0] + off), "r"(0) : "memory");
    }
}

__device__ __forceinline__ uint32_t ld_relaxed(const uint32_t* p) {
    uint32_t v;
    asm volatile("ld.relaxed.gpu.global.u32 %0, [%1];" : "=r"(v) : "l"(p) : "memory");
    return v;
}
__device__ __forceinline__ void count_up(uint32_t* p) {
    asm volatile("red.relaxed.gpu.global.add.u32 [%0], %1;" ::"l"(p), "r"(1) : "memory");
}
__device__ __forceinline__ void await_count(const uint32_t* p, uint32_t target) {
#pragma unroll 1
    for (uint32_t spins = 0; spins < (1u << 20); spins++)
        if (ld_relaxed(p) >= target) break;
}
__device__ __forceinline__ bool image_complete(int wg) {
    uint32_t addr = s_m + wg * (kWBytes - 4096) + threadIdx.x * 32 + (threadIdx.x & 12) * 2, lo = 1;
#pragma unroll 1
    for (int c = 0; c < 3; c++, addr += kWChunk) {
        mbar_wait(bar_img + 24 * wg + 8 * c, 0);
#pragma unroll
        for (int q = 0; q < 6; q++) lo = min(lo, lds_volatile(addr + q * 4096));
    }
    uint32_t ok;
    asm volatile("{\n.reg .pred p;\nsetp.ne.u32 p, %1, 0;\nbarrier.cta.red.and.aligned.pred p, %2, 128, p;\nselp.u32 %0, 1, 0, p;\n}\n"
                 : "=r"(ok) : "r"(lo), "r"(3 + wg) : "memory");
    return ok != 0;
}
__device__ __forceinline__ void bulk_g2s(uint32_t dst, const void* src, uint32_t bytes, uint32_t bar) {
    asm volatile("cp.async.bulk.shared::cluster.global.mbarrier::complete_tx::bytes [%0], [%1], %2, [%3];"
                 ::"r"(dst), "l"(src), "r"(bytes), "r"(bar)
                 : "memory");
}

__global__ void __launch_bounds__(kThreads, 1)
nat_fused_kernel(const uint8_t* __restrict__ x, const uint8_t* __restrict__ wqkv, uint8_t* __restrict__ out, Scratch* g,
                 const __grid_constant__ Maps maps) {
    extern __shared__ __align__(1024) uint8_t smem_raw[];
    const int tid = threadIdx.x, lane = tid & 31;
    const int warp = __shfl_sync(0xffffffffu, tid >> 5, 0);
    const int wg = warp >> 2, wq = warp & 3, r8 = lane >> 2, j = lane & 3;
    const int cta = blockIdx.x;
    const uint32_t t_start = clock_now();
    if (wg == 2) {
        const uint32_t which = cta >= 72, job = cta - 72 * which;
        if (wq < 3 && !which) m_partial(wqkv, job / 6, job % 6, wq, lane);
        asm volatile("setmaxnreg.dec.sync.aligned.u32 40;");
        if (wq < 3) {
            asm volatile("bar.sync 5, 128;" ::: "memory");
            if (cta < 120 && wq < 2 + which) {
                float d[2][4];
                if (wq == 0) TRW(which ? 1 : 18);
                if (which) {
                    mbar_wait(bar_wop, 0);
                    if (wq == 0) TRW(2);
                    w_piece(wq, lane, d);
                } else {
                    m_reduce(wq, lane, d);
                }
                piece_store(g, lds_volatile(s_par) & 1, which, which ? job % 12 : 2 * (job % 6) + wq, which ? 3 * (job / 12) + wq : job / 6, lane, d);
                __syncwarp();
                if (elect()) count_up(&g->cnt[which]);
                if (wq == 0) TRW(which ? 3 : 0);
            }
        } else {
            uint32_t launch = ld_relaxed(&g->cnt[2]);
            const Work w = decode_work(maps, cta);
            const bool leader = elect();
            if (leader) {
#pragma unroll
                for (int i = 0; i < 15; i++) mbar_init(s_bar + 8 * i, i < 12 ? 1 : i < 13 ? 3 : 4);
                asm volatile("fence.mbarrier_init.release.cluster;" ::: "memory");
                if ((uint32_t)__cvta_generic_to_shared(smem_raw) != kSmemBase) __trap();
                prefetch_map(w.map + 1);
                if (which && cta < 120) {
                    mbar_expect_tx(bar_wop, 4 * 6144);
                    tma_3d(s_wv, &maps.wo, bar_wop, 0, 3 * (job / 12));
                    tma_3d(s_wv + 3 * 6144, &maps.wv, bar_wop, 16 * (job % 12), 24);
                }
            }
            int u = w.iu, v = w.iv;
#pragma unroll 1
            for (int step = 0, i = 0;; step++) {
                const bool first = step == 0 || (w.corner && step == 4);
                if (leader) w.load_keys(u, v, first, first ? 0 : ~i & 1);
                if (step == 0) {
                    launch /= kGrid;
                    asm volatile("st.shared.u32 [%0], %1;" ::"r"(s_par), "r"(launch) : "memory");
                    if (leader) count_up(&g->cnt[2]);
                    asm volatile("bar.arrive 5, 128;\nbar.arrive 3, 160;\nbar.arrive 4, 160;" ::: "memory");
                }
                if (step < 2) {
                    if (step) wait_until(t_start, TN(5, 6000));
                    await_count(&g->cnt[step], (launch + 1) * kPieces);
                    TRW(5 + 4 * step);
                    if (leader) {
#pragma unroll 1
                        for (int c = 3 * step; c < 3 * step + 3; c++) {
                            mbar_expect_tx(bar_img + 8 * c, kWChunk);
                            bulk_g2s(s_m + c * kWChunk, g->img[launch & 1][0] + c * kWChunk, kWChunk, bar_img + 8 * c);
                        }
                    }
                    if (!step) { if (TN(1, 1)) mbar_wait(bar_img - 8 + 8 * TN(1, 1), 0); wait_until(t_start, TN(2, 0)); continue; }
                }
                if (w.corner && step == 3) { mbar_wait(bar_use + 8, 1); continue; }
                if (i + 1 == w.ntiles) break;
                mbar_wait(bar_use, i & 1);
                if (w.corner && (i & 1)) { u += 8; v -= 8; } else v += 8 - 2 * w.rev;
                i++;
            }
        }
        TRDUMP();
        return;
    }
    const int order = cta & 4 ? warp ^ 3 : warp;
    if (order > 4) {
#pragma unroll
        for (int r = 0; r < 3; r++)
            asm volatile("st.shared.v4.u32 [%0], {%1, %1, %1, %1};" ::"r"(s_ring + (order - 5) * kRingChunk + (r == 0 ? 84 : r == 1 ? 88 : 204) * 128 + lane * 16), "r"(0) : "memory");
        asm volatile("fence.proxy.async.shared::cta;" ::: "memory");
    }
    wait_until(t_start, TN(0, 600) + order * TN(3, 600));
    asm volatile("setmaxnreg.inc.sync.aligned.u32 232;");
    const Work w = decode_work(maps, cta);
    int tu = w.iu, tv = w.iv + (8 - 2 * w.rev) * wg;
    const int du2 = w.corner ? 8 : 0, dv2 = 16 - 2 * du2 - 4 * w.rev;
    uint32_t o0, o1;
    w.pixel_offsets(tu + r8, tv + 2 * wq, j, o0, o1);
    uint32_t fa[48];
    {
        RawX raw;
        load_raw(raw, x, o0, o1);
        asm volatile("bar.sync %0, 160;" ::"r"(3 + wg) : "memory");
        raw_to_frags(raw, 0, fa);
        pin(fa);
    }
    TR(2);

    constexpr uint32_t mdesc = desc_lo(s_m, 16), wdesc = desc_lo(s_wv, 16);
    constexpr uint32_t kdE = desc_lo(s_ring + kOffMid, 16), vdE = desc_lo(s_ring + kOffMid, kRingChunk);
    const uint32_t kdA = desc_lo(s_ring, 16) + wg * (kSlotStride >> 4), kdB = desc_lo(s_ring + kSlotStride, 16) - wg * (kSlotStride >> 4);
    constexpr uint32_t kToV = desc_lo(0, kRingChunk) - desc_lo(0, 16);

    float acc[96];
    uint32_t po[48];
    uint32_t c0, c1;
    asm volatile("" : "=r"(c0), "=r"(c1));
#pragma unroll
    for (int q = 0; q < 48; q++) asm volatile("" : "=r"(po[q]));
#pragma unroll 1
    for (int i = wg; i < w.ntiles; i += 2) {
        const bool first = i == 0, last = i == w.ntiles - 1;

        TR(8 + 16 * k);
        uint8_t *p0 = out + c0, *p1 = out + c1;
        const bool on = i >= 2;
        store_one(on, p0, p1, po, 0);
#pragma unroll 1
        for (uint32_t redo = 0;; redo++) {
            if (!first && !redo) turn_wait(wg);
            proj_gemm<3, 7>(acc, fa, mdesc, bar_img, [&](int s) { if (s >= 7 && s < 11) store_one(on, p0, p1, po, s - 6); });
            if (!first && !redo) turn_pass(wg);
            TR(9 + 16 * k);
            if (on) break;
            if (image_complete(i) || redo == 4096) break;
            wg_wait<0>();
            wg_sync(wg);
            if (wq == 0 && elect()) {
                mbar_expect_tx(bar_redo + 8 * i, kWBytes);
                bulk_g2s(s_m + i * kWBytes, g->img[lds_volatile(s_par) & 1][i], kWBytes, bar_redo + 8 * i);
            }
            mbar_wait(bar_redo + 8 * i, redo & 1);
        }
        store_one(on, p0, p1, po, 5);
        wg_wait<6>(); store_one(on, p0, p1, po, 6);
        wg_wait<5>(); store_one(on, p0, p1, po, 7);
        wg_wait<4>(); store_one(on, p0, p1, po, 8);
        wg_wait<3>(); store_one(on, p0, p1, po, 9);
        wg_wait<2>(); store_one(on, p0, p1, po, 10);
        wg_wait<1>(); store_one(on, p0, p1, po, 11);
        TR(10 + 16 * k);
        c0 = o0; c1 = o1;
        w.pixel_offsets(tu + du2 + r8, tv + dv2 + 2 * wq, j, o0, o1);
        if (i + 2 >= w.ntiles) o0 = o1 = 0;
        wg_wait<0>();
        pin(acc);
        TR(11 + 16 * k);
        acc_to_frags(acc, fa);
        pin(fa);

        float sA[44], sE[16], sB[44];
        RawX nxt;
        if (!first) turn_wait(wg);
        mbar_wait(bar_a, w.corner ? i >> 1 : 0);
        wg_fence();
#pragma unroll
        for (int s = 0; s < 12; s++)
            if (s == 0) wgmma_n88<true>(sA, fa[4 * s], fa[4 * s + 1], fa[4 * s + 2], fa[4 * s + 3], desc_at(kdA, (s >> 2) * kRingChunk + (s & 3) * 32));
            else wgmma_n88<false>(sA, fa[4 * s], fa[4 * s + 1], fa[4 * s + 2], fa[4 * s + 3], desc_at(kdA, (s >> 2) * kRingChunk + (s & 3) * 32));
        wg_commit();
        if (!first) turn_pass(wg);
        TR(12 + 16 * k);
        if (LDGPOS == 0) load_raw(nxt, x, o0, o1);
        const int vq = tv + w.cv + 2 * wq;
        const int off0 = window_start(vq) - (tv + w.cv), off1 = window_start(vq + 1) - (tv + w.cv);
        const int t0 = 7 * off0 - j, t1 = 7 * off1 - j, tw = 7 * (off0 & ~1) - 2 * j;
        Masks mk;
        make_u_masks(mk, window_start(tu + w.cu + r8) - w.origin_u(tu), j);
        float v0[14], v1[14];
        uint32_t pa[28];
#pragma unroll
        for (int q = 0; q < 28; q++) pa[q] = 0;
        wg_wait<0>();
        pin(sA);
#pragma unroll
        for (int b = 0; b < 14; b++) v0[b] = v1[b] = __int_as_float(0xff800000);
        const int r7 = w.rev ? 7 : 0;
        gather_outer(sA, mk.h, t0 - r7, t1 - r7, w.rev, v0, v1);
        pin(v0); pin(v1);
        if (!first) turn_wait(wg);
#pragma unroll
        for (int c = 0; c < 3; c++) {
            mbar_wait(bar_b + 8 * c, wg);
            TR(64 + 4 * k + c);
            wg_fence();
#pragma unroll
            for (int s = 4 * c; s < 4 * c + 4; s++)
                if (s == 0) wgmma_n88<true>(sB, fa[4 * s], fa[4 * s + 1], fa[4 * s + 2], fa[4 * s + 3], desc_at(kdB, c * kRingChunk + (s & 3) * 32));
                else wgmma_n88<false>(sB, fa[4 * s], fa[4 * s + 1], fa[4 * s + 2], fa[4 * s + 3], desc_at(kdB, c * kRingChunk + (s & 3) * 32));
        }
        wg_commit();
#pragma unroll
        for (int s = 0; s < 12; s++)
            if (s == 0) wgmma_n32<true>(sE, fa[4 * s], fa[4 * s + 1], fa[4 * s + 2], fa[4 * s + 3], desc_at(kdE, (s >> 2) * kRingChunk + (s & 3) * 32));
            else wgmma_n32<false>(sE, fa[4 * s], fa[4 * s + 1], fa[4 * s + 2], fa[4 * s + 3], desc_at(kdE, (s >> 2) * kRingChunk + (s & 3) * 32));
        wg_commit();
        if (!last) turn_pass(wg);
        TR(13 + 16 * k);
        if (LDGPOS == 1) load_raw(nxt, x, o0, o1);
        wg_wait<1>();
        pin(sB);
        gather_outer(sB, mk.h, t0 - 7 + r7, t1 - 7 + r7, !w.rev, v0, v1);
        wg_wait<0>();
        pin(sE);
        TR(14 + 16 * k);
        gather_mid(sE, mk.h, t0, t1, j, v0, v1);
        const float m0 = quad_max(tree_max(v0)), m1 = quad_max(tree_max(v1));

        exp_scatter(v0, v1, m0, m1, tw, w.rev, lane, pa);
        pin(pa);
        TR(15 + 16 * k);
        if (LDGPOS == 2) load_raw(nxt, x, o0, o1);

        if (!last) turn_wait(wg + (pa[12] >> 31));
        wg_fence();
        wgmma_sp_n192_tb<true, 0>(acc, pa[0], pa[1], pa[2], pa[3], desc_at(kdA + kToV, 0), mk.meta[0]);
        wgmma_sp_n192_tb<false, 1>(acc, pa[4], pa[5], pa[6], pa[7], desc_at(kdA + kToV, 4096), mk.meta[0]);
        wgmma_sp_n192_tb<false, 0>(acc, pa[8], pa[9], pa[10], pa[11], desc_at(kdA + kToV, 8192), mk.meta[1]);
        wgmma_sp_n192_tb<false, 1>(acc, pa[12], pa[13], pa[14], pa[15], desc_at(vdE, 0), mk.meta[1]);
        wg_commit();
        wgmma_sp_n192_tb<false, 0>(acc, pa[16], pa[17], pa[18], pa[19], desc_at(kdB + kToV, 0), mk.meta[0]);
        wgmma_sp_n192_tb<false, 1>(acc, pa[20], pa[21], pa[22], pa[23], desc_at(kdB + kToV, 4096), mk.meta[0]);
        wgmma_sp_n192_tb<false, 0>(acc, pa[24], pa[25], pa[26], pa[27], desc_at(kdB + kToV, 8192), mk.meta[1]);
        wg_commit();
        if (!last) turn_pass(wg);
        TR(16 + 16 * k);
        const float s0 = tree_sum(v0), s1 = tree_sum(v1);
        if (LDGPOS == 3) load_raw(nxt, x, o0, o1);
        wg_wait<1>();
        if (lane == 0) mbar_arrive(bar_use);
        TR(17 + 16 * k);
        wg_wait<0>();
        if (lane == 0) mbar_arrive(bar_use + 8);
        pin(acc);
        TR(18 + 16 * k);

        acc_to_frags(acc, po);
        pin(po);
        if (!last) turn_wait(wg);
        wg_fence();
        proj_gemm<0, 1>(acc, po, wdesc, 0, [](int) {});
        if (!last) turn_pass(wg);
        TR(19 + 16 * k);
        if (LDGPOS == 4) load_raw(nxt, x, o0, o1);
        const uint32_t zero = lds_volatile(s_zero);
        const float inv0 = rcp(quad_sum(s0 + __uint_as_float(zero))), inv1 = rcp(quad_sum(s1 + __uint_as_float(zero)));
        raw_to_frags(nxt, zero, fa);
        pin(fa);
        TR(20 + 16 * k);
        tu += du2; tv += dv2;
        wg_wait<0>();
        pin(acc);
        TR(21 + 16 * k);
        pack_out(acc, inv0, inv1, po);
        pin(po);
    }
    store_out(out, c0, c1, po);
    TR(7);
    TRG(1);
    TRDUMP();
}

typedef CUresult (*EncodeTiledFn)(CUtensorMap*, CUtensorMapDataType, cuuint32_t, void*, const cuuint64_t*, const cuuint64_t*,
                                  const cuuint32_t*, const cuuint32_t*, CUtensorMapInterleave, CUtensorMapSwizzle,
                                  CUtensorMapL2promotion, CUtensorMapFloatOOBfill);

bool make_maps(EncodeTiledFn fn, Maps* maps, void* x, void* wqkv, void* wo) {
    const cuuint64_t pix2 = 2 * kPixBytes, row = (cuuint64_t)kHW * kPixBytes;
    const cuuint32_t estr[5] = {1, 1, 1, 1, 1};
    bool ok = true;
    for (int tr = 0; tr < 2; tr++)
        for (int b = 0; b < 3; b++) {
            const cuuint64_t su = tr ? 2 * row : pix2, sv = tr ? pix2 : 2 * row;
            const cuuint64_t dims[5] = {2 * kC, b < 2 ? 2u : 1u, b < 2 ? 105u : 112u, 2, 112};
            const cuuint64_t strides[4] = {7 * su, su, row, sv};
            const cuuint32_t keys[5] = {64, 2, 7, 1, b ? 2u : 6u}, pixels[5] = {kC, 1, 8, 1, 2};
            ok = ok && fn(&maps->m[3 * tr + b], CU_TENSOR_MAP_DATA_TYPE_BFLOAT16, 5, x, dims, strides, b < 2 ? keys : pixels, estr,
                          CU_TENSOR_MAP_INTERLEAVE_NONE, b < 2 ? CU_TENSOR_MAP_SWIZZLE_128B : CU_TENSOR_MAP_SWIZZLE_NONE,
                          CU_TENSOR_MAP_L2_PROMOTION_L2_128B, CU_TENSOR_MAP_FLOAT_OOB_FILL_NONE) == CUDA_SUCCESS;
        }
    for (int b = 0; b < 2; b++) {
        const cuuint64_t dims[3] = {16, kC, b ? 36u : 12u}, strides[2] = {(b ? 3u : 1u) * kPixBytes, 32};
        const cuuint32_t box[3] = {16, b ? 16u : 192u, b ? 12u : 3u};
        ok = ok && fn(b ? &maps->wv : &maps->wo, CU_TENSOR_MAP_DATA_TYPE_BFLOAT16, 3, b ? wqkv : wo, dims, strides, box, estr,
                      CU_TENSOR_MAP_INTERLEAVE_NONE, CU_TENSOR_MAP_SWIZZLE_32B, CU_TENSOR_MAP_L2_PROMOTION_L2_128B,
                      CU_TENSOR_MAP_FLOAT_OOB_FILL_NONE) == CUDA_SUCCESS;
    }
    return ok;
}

}

extern "C" void kernel_launch(void* const* d_in, const int* in_sizes, int n_in, void* d_out, int out_size) {
    static EncodeTiledFn encode = nullptr;
    static Scratch* scratch = nullptr;
    if (!encode) {
        cudaGetSymbolAddress((void**)&scratch, g_scratch);
        void* fn = nullptr;
        cudaDriverEntryPointQueryResult st;
        cudaGetDriverEntryPoint("cuTensorMapEncodeTiled", &fn, cudaEnableDefault, &st);
        encode = (EncodeTiledFn)fn;
        cudaFuncSetAttribute(nat_fused_kernel, cudaFuncAttributeMaxDynamicSharedMemorySize, kSmemBytes);
    }
    Maps maps;
    if (!encode || !make_maps(encode, &maps, d_in[0], d_in[1], d_in[2])) return;
    nat_fused_kernel<<<kGrid, kThreads, kSmemBytes>>>((const uint8_t*)d_in[0], (const uint8_t*)d_in[1], (uint8_t*)d_out, scratch, maps);
}
```

```cpp
#include <cuda_runtime.h>
#include <cuda_bf16.h>
#include <cuda.h>
#include <stdint.h>
#include <type_traits>
#include <stdlib.h>
#include <stddef.h>

#define LDGPOS 0
#define INPLACE 1
#define KEEPFA 1
#define NPRE 5
#define OSPLIT 0
#define NORM 0
#define GORDER 0
#define PREFETCH 1

namespace {

constexpr int kC          = 192;
constexpr int kHW         = 224;
constexpr int kPixBytes   = kC * 2;
constexpr int kSlotBytes  = 84 * 128;
constexpr int kMidBytes   = 28 * 128;
constexpr int kOffMid     = 88 * 128;
constexpr int kSlotStride = 120 * 128;
constexpr int kRingChunk  = 208 * 128;
constexpr int kWChunk     = 192 * 128;
constexpr int kWBytes     = 3 * kWChunk;
constexpr uint32_t kSmemBase = 1024;
constexpr uint32_t s_ring = kSmemBase, s_m = s_ring + 3 * kRingChunk, s_wv = s_m + kWBytes, s_bar = s_wv + kWBytes;
constexpr uint32_t bar_b = s_bar, bar_img = s_bar + 24, bar_redo = s_bar + 72, bar_wop = s_bar + 96, bar_a = s_bar + 104,
                   bar_ok = s_bar + 112, bar_use = s_bar + 144, bar_poll = s_bar + 160;
constexpr uint32_t s_par = s_bar + 168, s_late = s_bar + 172, s_cnt = s_bar + 176, s_tab = s_bar + 256, s_trace = s_tab + 2048;
constexpr int kSmemBytes  = s_trace + 2048 - kSmemBase;
constexpr int kThreads    = 384;
constexpr int kGrid       = 132;
constexpr int kPieces     = 144;
constexpr float kScaleLog2e = 0.07216878364870322f * 1.4426950408889634f;

struct Maps {
    CUtensorMap m[6];
    CUtensorMap wo, wv;
};
#define TN(i, dflt) (dflt)

struct Scratch {
    uint8_t img[2][2][kWBytes];
    uint32_t cnt[4];
};
__device__ __align__(1024) Scratch g_scratch;

struct Table {
    uint32_t route[32][4];
    uint32_t u[8][4][4];
    uint32_t v[16][4][4];
};
struct Tables { Table t[2]; };
constexpr Tables make_tables() {
    Tables r = {};
    for (int rev = 0; rev < 2; rev++)
        for (int j = 0; j < 4; j++) {
            Table& t = r.t[rev];
            for (int q = 0; q < 8; q++) {
                uint32_t* e = t.route[4 * q + j];
                e[0] = 4 * q + 2 * (j & 1) + (j >> 1); e[1] = e[0] ^ 1;
                e[2] = j < 2 ? 0x5410u : 0x1054u; e[3] = e[2] + 0x2222u;
                e = t.u[q][j];
                for (int n = 0; n < 7; n++) e[0] |= ((n + j) % 7 < q ? 1u : 0u) << n;
                e[3] = e[0];
                for (int k = 0; k < 2; k++) {
                    const int step = 2 * k + (j >> 1), p0 = (step < 3 ? 16 * step : 40) + 8 * (j & 1);
                    uint32_t m = 0x8888u;
                    for (int n = 0; n < 8; n++) m |= ((p0 + n) % 7 < q ? 1u : 0u) << (2 * n);
                    e[1 + k] = m * 0x10001u;
                }
            }
            for (int sum = 0; sum < 15; sum++) {
                uint32_t* e = t.v[sum][j];
                for (int row = 0; row < 2; row++)
                    for (int b = 0; b < 14; b++) {
                        const int off = (sum + row) / 2, p = 4 * b + j;
                        const uint32_t bit = 1u << (2 * b + row);
                        if (p < 42 && p >= 7 * off) e[rev] |= bit;
                        if (p < 7 * off - 7) e[1 - rev] |= bit;
                        if (p >= 42 && p >= 7 * off && p < 7 * off + 49) e[2] |= bit;
                    }
                for (int n = 0; n < 6; n++)
                    if (8 * n + 2 * j < 42) e[3] |= 1u << (n + ((8 * n + 2 * j >= 7 * (sum / 2 & ~1)) != rev ? 0 : 8));
            }
        }
    return r;
}
__device__ __align__(128) const Tables g_tables = make_tables();

#define WO4(i) "=f"(d[i]), "=f"(d[i + 1]), "=f"(d[i + 2]), "=f"(d[i + 3])
#define RW4(i) "+f"(d[i]), "+f"(d[i + 1]), "+f"(d[i + 2]), "+f"(d[i + 3])

template <bool FIRST>
__device__ __forceinline__ void wgmma_n192(float (&d)[96], uint32_t a0, uint32_t a1, uint32_t a2, uint32_t a3, uint64_t descb) {
    if constexpr (FIRST) {
        asm volatile(
            "wgmma.mma_async.sync.aligned.m64n192k16.f32.bf16.bf16 "
            "{%0, %1, %2, %3, %4, %5, %6, %7, %8, %9, %10, %11, %12, %13, %14, %15, %16, %17, %18, %19, %20, %21, %22, %23, "
            "%24, %25, %26, %27, %28, %29, %30, %31, %32, %33, %34, %35, %36, %37, %38, %39, %40, %41, %42, %43, %44, %45, %46, %47, "
            "%48, %49, %50, %51, %52, %53, %54, %55, %56, %57, %58, %59, %60, %61, %62, %63, %64, %65, %66, %67, %68, %69, %70, %71, "
            "%72, %73, %74, %75, %76, %77, %78, %79, %80, %81, %82, %83, %84, %85, %86, %87, %88, %89, %90, %91, %92, %93, %94, %95}, "
            "{%96, %97, %98, %99}, %100, 0, 1, 1, 0;"
            : WO4(0), WO4(4), WO4(8), WO4(12), WO4(16), WO4(20), WO4(24), WO4(28), WO4(32), WO4(36), WO4(40), WO4(44),
              WO4(48), WO4(52), WO4(56), WO4(60), WO4(64), WO4(68), WO4(72), WO4(76), WO4(80), WO4(84), WO4(88), WO4(92)
            : "r"(a0), "r"(a1), "r"(a2), "r"(a3), "l"(descb));
    } else {
        asm volatile(
            "wgmma.mma_async.sync.aligned.m64n192k16.f32.bf16.bf16 "
            "{%0, %1, %2, %3, %4, %5, %6, %7, %8, %9, %10, %11, %12, %13, %14, %15, %16, %17, %18, %19, %20, %21, %22, %23, "
            "%24, %25, %26, %27, %28, %29, %30, %31, %32, %33, %34, %35, %36, %37, %38, %39, %40, %41, %42, %43, %44, %45, %46, %47, "
            "%48, %49, %50, %51, %52, %53, %54, %55, %56, %57, %58, %59, %60, %61, %62, %63, %64, %65, %66, %67, %68, %69, %70, %71, "
            "%72, %73, %74, %75, %76, %77, %78, %79, %80, %81, %82, %83, %84, %85, %86, %87, %88, %89, %90, %91, %92, %93, %94, %95}, "
            "{%96, %97, %98, %99}, %100, 1, 1, 1, 0;"
            : RW4(0), RW4(4), RW4(8), RW4(12), RW4(16), RW4(20), RW4(24), RW4(28), RW4(32), RW4(36), RW4(40), RW4(44),
              RW4(48), RW4(52), RW4(56), RW4(60), RW4(64), RW4(68), RW4(72), RW4(76), RW4(80), RW4(84), RW4(88), RW4(92)
            : "r"(a0), "r"(a1), "r"(a2), "r"(a3), "l"(descb));
    }
}

template <bool FIRST>
__device__ __forceinline__ void wgmma_n88(float (&d)[44], uint32_t a0, uint32_t a1, uint32_t a2, uint32_t a3, uint64_t descb) {
    if constexpr (FIRST) {
        asm volatile(
            "wgmma.mma_async.sync.aligned.m64n88k16.f32.bf16.bf16 "
            "{%0, %1, %2, %3, %4, %5, %6, %7, %8, %9, %10, %11, %12, %13, %14, %15, %16, %17, %18, %19, %20, %21, %22, %23, "
            "%24, %25, %26, %27, %28, %29, %30, %31, %32, %33, %34, %35, %36, %37, %38, %39, %40, %41, %42, %43}, "
            "{%44, %45, %46, %47}, %48, 0, 1, 1, 0;"
            : WO4(0), WO4(4), WO4(8), WO4(12), WO4(16), WO4(20), WO4(24), WO4(28), WO4(32), WO4(36), WO4(40)
            : "r"(a0), "r"(a1), "r"(a2), "r"(a3), "l"(descb));
    } else {
        asm volatile(
            "wgmma.mma_async.sync.aligned.m64n88k16.f32.bf16.bf16 "
            "{%0, %1, %2, %3, %4, %5, %6, %7, %8, %9, %10, %11, %12, %13, %14, %15, %16, %17, %18, %19, %20, %21, %22, %23, "
            "%24, %25, %26, %27, %28, %29, %30, %31, %32, %33, %34, %35, %36, %37, %38, %39, %40, %41, %42, %43}, "
            "{%44, %45, %46, %47}, %48, 1, 1, 1, 0;"
            : RW4(0), RW4(4), RW4(8), RW4(12), RW4(16), RW4(20), RW4(24), RW4(28), RW4(32), RW4(36), RW4(40)
            : "r"(a0), "r"(a1), "r"(a2), "r"(a3), "l"(descb));
    }
}

template <bool FIRST>
__device__ __forceinline__ void wgmma_n32(float (&d)[16], uint32_t a0, uint32_t a1, uint32_t a2, uint32_t a3, uint64_t descb) {
    if constexpr (FIRST) {
        asm volatile(
            "wgmma.mma_async.sync.aligned.m64n32k16.f32.bf16.bf16 "
            "{%0, %1, %2, %3, %4, %5, %6, %7, %8, %9, %10, %11, %12, %13, %14, %15}, "
            "{%16, %17, %18, %19}, %20, 0, 1, 1, 0;"
            : WO4(0), WO4(4), WO4(8), WO4(12)
            : "r"(a0), "r"(a1), "r"(a2), "r"(a3), "l"(descb));
    } else {
        asm volatile(
            "wgmma.mma_async.sync.aligned.m64n32k16.f32.bf16.bf16 "
            "{%0, %1, %2, %3, %4, %5, %6, %7, %8, %9, %10, %11, %12, %13, %14, %15}, "
            "{%16, %17, %18, %19}, %20, 1, 1, 1, 0;"
            : RW4(0), RW4(4), RW4(8), RW4(12)
            : "r"(a0), "r"(a1), "r"(a2), "r"(a3), "l"(descb));
    }
}

template <bool FIRST, int SEL>
__device__ __forceinline__ void wgmma_sp_n192_tb(float (&d)[96], uint32_t a0, uint32_t a1, uint32_t a2, uint32_t a3, uint64_t descb, uint32_t meta) {
    if constexpr (FIRST) {
        asm volatile(
            "wgmma.mma_async.sp.sync.aligned.m64n192k32.f32.bf16.bf16 "
            "{%0, %1, %2, %3, %4, %5, %6, %7, %8, %9, %10, %11, %12, %13, %14, %15, %16, %17, %18, %19, %20, %21, %22, %23, "
            "%24, %25, %26, %27, %28, %29, %30, %31, %32, %33, %34, %35, %36, %37, %38, %39, %40, %41, %42, %43, %44, %45, %46, %47, "
            "%48, %49, %50, %51, %52, %53, %54, %55, %56, %57, %58, %59, %60, %61, %62, %63, %64, %65, %66, %67, %68, %69, %70, %71, "
            "%72, %73, %74, %75, %76, %77, %78, %79, %80, %81, %82, %83, %84, %85, %86, %87, %88, %89, %90, %91, %92, %93, %94, %95}, "
            "{%96, %97, %98, %99}, %100, %101, %102, 0, 1, 1, 1;"
            : WO4(0), WO4(4), WO4(8), WO4(12), WO4(16), WO4(20), WO4(24), WO4(28), WO4(32), WO4(36), WO4(40), WO4(44),
              WO4(48), WO4(52), WO4(56), WO4(60), WO4(64), WO4(68), WO4(72), WO4(76), WO4(80), WO4(84), WO4(88), WO4(92)
            : "r"(a0), "r"(a1), "r"(a2), "r"(a3), "l"(descb), "r"(meta), "n"(SEL));
    } else {
        asm volatile(
            "wgmma.mma_async.sp.sync.aligned.m64n192k32.f32.bf16.bf16 "
            "{%0, %1, %2, %3, %4, %5, %6, %7, %8, %9, %10, %11, %12, %13, %14, %15, %16, %17, %18, %19, %20, %21, %22, %23, "
            "%24, %25, %26, %27, %28, %29, %30, %31, %32, %33, %34, %35, %36, %37, %38, %39, %40, %41, %42, %43, %44, %45, %46, %47, "
            "%48, %49, %50, %51, %52, %53, %54, %55, %56, %57, %58, %59, %60, %61, %62, %63, %64, %65, %66, %67, %68, %69, %70, %71, "
            "%72, %73, %74, %75, %76, %77, %78, %79, %80, %81, %82, %83, %84, %85, %86, %87, %88, %89, %90, %91, %92, %93, %94, %95}, "
            "{%96, %97, %98, %99}, %100, %101, %102, 1, 1, 1, 1;"
            : RW4(0), RW4(4), RW4(8), RW4(12), RW4(16), RW4(20), RW4(24), RW4(28), RW4(32), RW4(36), RW4(40), RW4(44),
              RW4(48), RW4(52), RW4(56), RW4(60), RW4(64), RW4(68), RW4(72), RW4(76), RW4(80), RW4(84), RW4(88), RW4(92)
            : "r"(a0), "r"(a1), "r"(a2), "r"(a3), "l"(descb), "r"(meta), "n"(SEL));
    }
}

#define TR(slot)
#define TRF(slot)
#define TRW(slot)
#define TRG(slot)
#define TRDUMP()

__device__ __forceinline__ void wg_fence() { asm volatile("wgmma.fence.sync.aligned;" ::: "memory"); }
__device__ __forceinline__ void wg_commit() { asm volatile("wgmma.commit_group.sync.aligned;" ::: "memory"); }
template <int N>
__device__ __forceinline__ void wg_wait() { asm volatile("wgmma.wait_group.sync.aligned %0;" ::"n"(N) : "memory"); }

template <int N>
__device__ __forceinline__ void pin(float (&d)[N]) {
#pragma unroll
    for (int i = 0; i < N; i++) asm volatile("" : "+f"(d[i])::"memory");
}
template <int N>
__device__ __forceinline__ void pin(uint32_t (&d)[N]) {
#pragma unroll
    for (int i = 0; i < N; i++) asm volatile("" : "+r"(d[i])::"memory");
}

constexpr uint64_t kDescRing = ((uint64_t)((1u << 30) | (1024u >> 4)) << 32) | (1u << 16) | (s_ring >> 4);
constexpr uint32_t kToV = ((kRingChunk >> 4) - 1) << 20;
__device__ __forceinline__ uint64_t desc_at(uint64_t base, uint32_t byte_off) {
    uint64_t d;
    asm volatile("add.s64 %0, %1, %2;" : "=l"(d) : "l"(base), "l"((uint64_t)(byte_off >> 4)));
    return d;
}

__device__ __forceinline__ void mbar_init(uint32_t bar, uint32_t count) {
    asm volatile("mbarrier.init.shared::cta.b64 [%0], %1;" ::"r"(bar), "r"(count) : "memory");
}
__device__ __forceinline__ void mbar_expect_tx(uint32_t bar, uint32_t bytes) {
    asm volatile("mbarrier.arrive.expect_tx.shared::cta.b64 _, [%0], %1;" ::"r"(bar), "r"(bytes) : "memory");
}
__device__ __forceinline__ void mbar_arrive(uint32_t bar) {
    asm volatile("mbarrier.arrive.shared::cta.b64 _, [%0];" ::"r"(bar) : "memory");
}
__device__ __forceinline__ void mbar_wait(uint32_t bar, uint32_t parity) {
    asm volatile(
        "{\n.reg .pred p;\n"
        "W: mbarrier.try_wait.parity.shared::cta.b64 p, [%0], %1;\n"
        "@!p bra W;\n}\n"
        ::"r"(bar), "r"(parity) : "memory");
}
__device__ __forceinline__ uint32_t clock_now() {
    uint32_t c;
    asm volatile("mov.u32 %0, %%clock;" : "=r"(c)::"memory");
    return c;
}
__device__ __forceinline__ void wait_until(uint32_t t0, int t) {
    if (t == 0) return;
    while ((int)(clock_now() - t0) < t) {}
}
__device__ __forceinline__ bool elect() {
    uint32_t ok;
    asm volatile("{\n.reg .pred p;\nelect.sync _|p, 0xffffffff;\nselp.u32 %0, 1, 0, p;\n}\n" : "=r"(ok));
    return ok != 0;
}
__device__ __forceinline__ void turn_wait(int wg) { asm volatile("bar.sync %0, 256;" ::"r"(1 + wg) : "memory"); }
__device__ __forceinline__ void turn_pass(int wg) { asm volatile("bar.arrive %0, 256;" ::"r"(2 - wg) : "memory"); }

__device__ __forceinline__ void tma_box(uint32_t dst, const CUtensorMap* map, uint32_t bar, int c0, int c2, int c3, int c4) {
    asm volatile(
        "cp.async.bulk.tensor.5d.shared::cluster.global.mbarrier::complete_tx::bytes [%0], [%1, {%3, %4, %5, %6, %7}], [%2];"
        ::"r"(dst), "l"(map), "r"(bar), "r"(c0), "r"(0), "r"(c2), "r"(c3), "r"(c4)
        : "memory");
}
__device__ __forceinline__ void tma_3d(uint32_t dst, const CUtensorMap* map, uint32_t bar, int c1, int c2) {
    asm volatile("cp.async.bulk.tensor.3d.shared::cluster.global.mbarrier::complete_tx::bytes [%0], [%1, {%3, %4, %5}], [%2];"
                 ::"r"(dst), "l"(map), "r"(bar), "r"(0), "r"(c1), "r"(c2)
                 : "memory");
}
__device__ __forceinline__ void tma_prefetch(const CUtensorMap* map, int c0, int c2, int c3, int c4) {
    asm volatile("cp.async.bulk.prefetch.tensor.5d.L2.global [%0, {%1, %2, %3, %4, %5}];"
                 ::"l"(map), "r"(c0), "r"(0), "r"(c2), "r"(c3), "r"(c4)
                 : "memory");
}
__device__ __forceinline__ void prefetch_map(const CUtensorMap* map) {
    asm volatile("prefetch.tensormap [%0];" ::"l"(map) : "memory");
}
__device__ __forceinline__ uint4 ldg(const void* p) {
    uint4 v;
    asm volatile("ld.global.v4.u32 {%0, %1, %2, %3}, [%4];" : "=r"(v.x), "=r"(v.y), "=r"(v.z), "=r"(v.w) : "l"(p) : "memory");
    return v;
}
__device__ __forceinline__ uint32_t pack_bf16(float lo, float hi) {
    uint32_t r;
    asm("cvt.rn.bf16x2.f32 %0, %1, %2;" : "=r"(r) : "f"(hi), "f"(lo));
    return r;
}
__device__ __forceinline__ uint32_t mul_bf16x2(uint32_t a, uint32_t b) {
    uint32_t r;
    asm("mul.rn.bf16x2 %0, %1, %2;" : "=r"(r) : "r"(a), "r"(b));
    return r;
}
__device__ __forceinline__ float ex2(float x) {
    float y;
    asm("ex2.approx.ftz.f32 %0, %1;" : "=f"(y) : "f"(x));
    return y;
}
__device__ __forceinline__ float rcp(float x) {
    float y;
    asm("rcp.approx.ftz.f32 %0, %1;" : "=f"(y) : "f"(x));
    return y;
}
__device__ __forceinline__ void mma16816(float (&d)[4], uint32_t a0, uint32_t a1, uint32_t a2, uint32_t a3, uint32_t b0, uint32_t b1) {
    asm volatile("mma.sync.aligned.m16n8k16.row.col.f32.bf16.bf16.f32 {%0, %1, %2, %3}, {%4, %5, %6, %7}, {%8, %9}, {%0, %1, %2, %3};"
                 : "+f"(d[0]), "+f"(d[1]), "+f"(d[2]), "+f"(d[3])
                 : "r"(a0), "r"(a1), "r"(a2), "r"(a3), "r"(b0), "r"(b1));
}
__device__ __forceinline__ uint4 lds128(uint32_t addr) {
    uint4 v;
    asm volatile("ld.volatile.shared.v4.u32 {%0, %1, %2, %3}, [%4];" : "=r"(v.x), "=r"(v.y), "=r"(v.z), "=r"(v.w) : "r"(addr) : "memory");
    return v;
}
__device__ __forceinline__ uint32_t lds_volatile(uint32_t addr) {
    uint32_t v;
    asm volatile("ld.volatile.shared.u32 %0, [%1];" : "=r"(v) : "r"(addr) : "memory");
    return v;
}

__device__ __forceinline__ int window_start(int i_shifted) { return min(max(i_shifted, 0), 105); }

struct Work {
    int cu, cv;
    uint32_t su, sv;
    int iu, iv;
    int corner, ntiles;
    int rev;
    const CUtensorMap* map;
    int c0, c3;
    __device__ __forceinline__ int origin_u(int u) const { return min(max(u + cu, 0), 98); }
    __device__ __forceinline__ void pixel_offsets(int u, int v, int j, uint32_t& o0, uint32_t& o1) const {
        const uint32_t base = (u + window_start(u + cu) + (cu ? 0 : 7)) * su + j * 16 + (v + (cv ? 0 : 7)) * sv;
        o0 = base + window_start(v + cv) * sv;
        o1 = base + (window_start(v + 1 + cv) + 1) * sv;
    }
    __device__ __forceinline__ void load_keys(int u, int v, bool first, int slot) const {
#pragma unroll 1
        for (int c = 0; c < 3; c++) {
            const uint32_t bar = first ? bar_a : bar_b + 8 * c;
            mbar_expect_tx(bar, first ? kSlotBytes : kSlotBytes + kMidBytes);
            tma_box(s_ring + c * kRingChunk + slot * kSlotStride, map, bar, c0 + 64 * c, origin_u(u), c3, v + cv + (first ? rev : 8 - rev));
            if (!first) tma_box(s_ring + c * kRingChunk + kOffMid + 512, map + 1, bar, c0 + 64 * c, origin_u(u), c3, v + cv + 6);
        }
    }
    __device__ __forceinline__ void prefetch_rows(int u, int v) const { tma_prefetch(map + 2, c0, u, c3, v + cv); }
};

__device__ __forceinline__ Work decode_work(const Maps& maps, int c) {
    Work w;
    const int idx = c >> 2, ypar = (c >> 1) & 1, xpar = c & 1;
    const bool transposed = (idx >> 2) == 7;
    w.corner = idx == 32;
    w.cu = 6 * (transposed ? ypar : xpar) - 6;
    w.cv = 6 * (transposed ? xpar : ypar) - 6;
    w.su = transposed ? kHW * kPixBytes : kPixBytes;
    w.sv = transposed ? kPixBytes : kHW * kPixBytes;
    w.iu = idx < 28 ? 8 * (idx >> 1) : 96 + 4 * (idx & 2);
    w.rev = w.corner ? 0 : 8 * (idx & 1);
    w.iv = w.corner ? 96 : 48 - w.rev;
    w.ntiles = w.corner ? 4 : 6;
    w.map = &maps.m[transposed ? 3 : 0];
    w.c0 = xpar * kC;
    w.c3 = ypar;
    return w;
}

struct RawX { uint4 a[6], b[6]; };
__device__ __forceinline__ void load_raw(RawX& r, const uint8_t* base, uint32_t o0, uint32_t o1) {
    __syncwarp();
#pragma unroll
    for (int c = 0; c < 6; c++) { r.a[c] = ldg(base + o0 + c * 64); r.b[c] = ldg(base + o1 + c * 64); }
    __syncwarp();
}
__device__ __forceinline__ void raw_to_frags(const RawX& r, uint32_t zero, uint32_t (&f)[48]) {
#pragma unroll
    for (int c = 0; c < 6; c++) {
        f[8 * c + 0] = r.a[c].x; f[8 * c + 2] = r.a[c].z; f[8 * c + 4] = r.a[c].y ^ zero; f[8 * c + 6] = r.a[c].w ^ zero;
        f[8 * c + 1] = r.b[c].x ^ zero; f[8 * c + 3] = r.b[c].z ^ zero; f[8 * c + 5] = r.b[c].y ^ zero; f[8 * c + 7] = r.b[c].w ^ zero;
    }
}
__device__ __forceinline__ void acc_to_frags(const float (&d)[96], uint32_t (&f)[48]) {
#pragma unroll
    for (int i = 0; i < 48; i++) f[i] = pack_bf16(d[2 * i], d[2 * i + 1]);
}

template <class F>
__device__ __forceinline__ void proj_gemm(float (&d)[96], const uint32_t (&a)[48], uint64_t dsc, uint32_t img, F after) {
#pragma unroll
    for (int s = 0; s < 12; s++) {
        if (s == 0) wgmma_n192<true>(d, a[4 * s], a[4 * s + 1], a[4 * s + 2], a[4 * s + 3], desc_at(dsc, img - s_ring + (s >> 2) * kWChunk + (s & 3) * 32));
        else wgmma_n192<false>(d, a[4 * s], a[4 * s + 1], a[4 * s + 2], a[4 * s + 3], desc_at(dsc, img - s_ring + (s >> 2) * kWChunk + (s & 3) * 32));
        if (s == 11) wg_commit();
        after(s);
    }
}
__device__ __forceinline__ void pack_out(const float (&acc)[96], float i0, float i1, uint32_t (&po)[48]) {
#pragma unroll
    for (int g = 0; g < 6; g++)
#pragma unroll
        for (int q = 0; q < 4; q++) {
            po[8 * g + q] = pack_bf16(acc[16 * g + 4 * q] * i0, acc[16 * g + 4 * q + 1] * i0);
            po[8 * g + 4 + q] = pack_bf16(acc[16 * g + 4 * q + 2] * i1, acc[16 * g + 4 * q + 3] * i1);
        }
}
__device__ __forceinline__ void store_one(bool on, uint8_t* p0, uint8_t* p1, const uint32_t (&po)[48], int n) {
    asm volatile("{\n.reg .pred p;\nsetp.ne.u32 p, %5, 0;\nbar.warp.sync 0xffffffff;\n@p st.global.v4.u32 [%0], {%1, %2, %3, %4};\n}\n"
                 ::"l"(((n & 1) ? p1 : p0) + (n >> 1) * 64), "r"(po[4 * n]), "r"(po[4 * n + 1]), "r"(po[4 * n + 2]), "r"(po[4 * n + 3]), "r"((uint32_t)on) : "memory");
}

template <int N>
__device__ __forceinline__ float tree_max(const float (&v)[N]) {
    float t[N];
#pragma unroll
    for (int i = 0; i < N; i++) t[i] = v[i];
#pragma unroll
    for (int w = 1; w < N; w *= 2)
#pragma unroll
        for (int i = 0; i + w < N; i += 2 * w) t[i] = fmaxf(t[i], t[i + w]);
    return t[0];
}
template <int N>
__device__ __forceinline__ float tree_sum(const float (&v)[N]) {
    float t[N];
#pragma unroll
    for (int i = 0; i < N; i++) t[i] = v[i];
#pragma unroll
    for (int w = 1; w < N; w *= 2)
#pragma unroll
        for (int i = 0; i + w < N; i += 2 * w) t[i] += t[i + w];
    return t[0];
}

template <int B>
__device__ __forceinline__ void pick(uint32_t h, uint32_t ok, const float* s, float& v0, float& v1) {
    asm("{\n.reg .pred p, q0, q1;\n.reg .b32 t;\nand.b32 t, %6, %7;\nsetp.ne.u32 p, t, 0;\n"
        "and.b32 t, %8, %9;\nsetp.ne.u32 q0, t, 0;\nand.b32 t, %8, %10;\nsetp.ne.u32 q1, t, 0;\n"
        "@q0 selp.f32 %0, %3, %2, p;\n@q1 selp.f32 %1, %5, %4, p;\n}\n"
        : "+f"(v0), "+f"(v1)
        : "f"(s[0]), "f"(s[1]), "f"(s[2]), "f"(s[3]), "r"(h), "n"(1 << ((4 * B) % 7)), "r"(ok), "n"(1 << (2 * B)), "n"(2 << (2 * B)));
}
template <int B, class F>
__device__ __forceinline__ void for_blocks(F f) {
    if constexpr (B > 0) { for_blocks<B - 1>(f); f(std::integral_constant<int, B - 1>{}); }
}
__device__ __forceinline__ void gather_outer(const float (&s)[44], uint32_t h, uint32_t ok, float (&v0)[14], float (&v1)[14]) {
    for_blocks<11>([&](auto B) {
        constexpr int b = GORDER ? B.value : B.value < 8 ? (B.value >> 1) + 7 * (B.value & 1) : B.value - 4;
        pick<b>(h, ok, &s[4 * b], v0[b], v1[b]);
    });
}
__device__ __forceinline__ void gather_mid(const float (&sE)[16], uint32_t h, uint32_t ok, float (&v0)[14], float (&v1)[14]) {
    for_blocks<4>([&](auto B) { pick<10 + B.value>(h, ok, &sE[4 * B.value], v0[10 + B.value], v1[10 + B.value]); });
}
__device__ __forceinline__ float quad_max(float m) {
    m = fmaxf(m, __shfl_xor_sync(0xffffffffu, m, 1));
    return fmaxf(m, __shfl_xor_sync(0xffffffffu, m, 2));
}
__device__ __forceinline__ float quad_sum(float s) {
    s += __shfl_xor_sync(0xffffffffu, s, 1);
    return s + __shfl_xor_sync(0xffffffffu, s, 2);
}
template <int B0, int B1>
__device__ __forceinline__ void exp_route(float (&v0)[14], float (&v1)[14], float m0, float m1, const uint4& r, bool even, uint32_t (&y)[14]) {
#pragma unroll
    for (int b = B0; b < B1; b++) { v0[b] = ex2(v0[b] - m0); v1[b] = ex2(v1[b] - m1); }
#pragma unroll
    for (int b = B0; b < B1; b += 2) {
        const uint32_t x0 = pack_bf16(v0[b], v1[b]), x1 = pack_bf16(v0[b + 1], v1[b + 1]);
        const uint32_t u = __shfl_sync(0xffffffffu, even ? x0 : x1, r.x);
        const uint32_t w = __shfl_sync(0xffffffffu, even ? x1 : x0, r.y);
        y[b] = __byte_perm(u, w, r.z); y[b + 1] = __byte_perm(u, w, r.w);
    }
}
template <int BIT0, int N0, int N1>
__device__ __forceinline__ void unfold(const uint32_t (&y)[14], uint32_t fold, uint32_t (&p)[12]) {
    for_blocks<N1 - N0>([&](auto N) {
        constexpr int n = N0 + N.value;
        asm("{\n.reg .pred p;\n.reg .b32 t;\nand.b32 t, %4, %5;\nsetp.ne.u32 p, t, 0;\nselp.b32 %0, %2, 0, p;\nselp.b32 %1, %3, 0, p;\n}\n"
            : "=r"(p[2 * n]), "=r"(p[2 * n + 1]) : "r"(y[2 * n]), "r"(y[2 * n + 1]), "r"(fold), "n"(1 << (BIT0 + n)));
    });
}
__device__ __forceinline__ float late_sum(const float (&v)[14], float one) {
    float t[7];
#pragma unroll
    for (int i = 0; i < 7; i++) t[i] = fmaf(v[2 * i], one, v[2 * i + 1]);
    return tree_sum(t);
}
__device__ __forceinline__ void keep(bool never, uint32_t a, uint32_t b, uint32_t c, uint32_t d) {
    asm volatile("{\n.reg .pred p;\nsetp.ne.u32 p, %4, 0;\n@p st.volatile.shared.v4.u32 [%5], {%0, %1, %2, %3};\n}\n"
                 ::"r"(a), "r"(b), "r"(c), "r"(d), "r"((uint32_t)never), "r"(s_trace) : "memory");
}

__device__ __forceinline__ uint32_t wimg_offset(uint32_t row, uint32_t s, uint32_t j) {
    return (s >> 2) * kWChunk + row * 128 + (((2 * (s & 3) + (j >> 1)) ^ (row & 7)) << 4) + (j & 1) * 8;
}

__device__ __forceinline__ void ldsm4(uint32_t (&r)[4], uint32_t addr) {
    asm volatile("ldmatrix.sync.aligned.m8n8.x4.shared.b16 {%0, %1, %2, %3}, [%4];" : "=r"(r[0]), "=r"(r[1]), "=r"(r[2]), "=r"(r[3]) : "r"(addr) : "memory");
}
__device__ __forceinline__ void ldsm4_t(uint32_t (&r)[4], uint32_t addr) {
    asm volatile("ldmatrix.sync.aligned.m8n8.x4.trans.shared.b16 {%0, %1, %2, %3}, [%4];" : "=r"(r[0]), "=r"(r[1]), "=r"(r[2]), "=r"(r[3]) : "r"(addr) : "memory");
}
__device__ __forceinline__ void m_partial(const uint8_t* wqkv, uint32_t mt, uint32_t sp, uint32_t q, uint32_t lane) {
    const uint32_t r8 = lane >> 2, col = q * 128 + (lane & 3) * 16;
    const uint8_t* pa = wqkv + (16 * mt + r8) * 1152 + col;
    const uint8_t* pb = wqkv + (32 * sp + 8 * (r8 & 2) + (r8 & 5)) * 1152 + col;
    uint4 A[2][2], B[4][2];
#pragma unroll
    for (int c = 0; c < 2; c++) {
#pragma unroll
        for (int h = 0; h < 2; h++) A[h][c] = ldg(pa + 384 + h * 8 * 1152 + c * 64);
#pragma unroll
        for (int n = 0; n < 4; n++) B[n][c] = ldg(pb + ((n & 1) * 8 + (n & 2)) * 1152 + c * 64);
    }
#pragma unroll
    for (int n = 0; n < 4; n++) {
        float d[4] = {0.f, 0.f, 0.f, 0.f};
#pragma unroll
        for (int c = 0; c < 2; c++) {
            mma16816(d, A[0][c].x, A[1][c].x, A[0][c].y, A[1][c].y, B[n][c].x, B[n][c].y);
            mma16816(d, A[0][c].z, A[1][c].z, A[0][c].w, A[1][c].w, B[n][c].z, B[n][c].w);
        }
        asm volatile("st.shared.v4.f32 [%0], {%1, %2, %3, %4};" ::"r"(s_wv + q * 2048 + n * 512 + lane * 16), "f"(d[0]), "f"(d[1]), "f"(d[2]), "f"(d[3]) : "memory");
    }
}
__device__ __forceinline__ void m_reduce(uint32_t e, uint32_t lane, float (&d)[2][4]) {
#pragma unroll
    for (int n = 0; n < 2; n++) {
        float t[3][4];
#pragma unroll
        for (int q = 0; q < 3; q++)
            asm volatile("ld.shared.v4.f32 {%0, %1, %2, %3}, [%4];" : "=f"(t[q][0]), "=f"(t[q][1]), "=f"(t[q][2]), "=f"(t[q][3]) : "r"(s_wv + q * 2048 + e * 1024 + n * 512 + lane * 16) : "memory");
#pragma unroll
        for (int i = 0; i < 4; i++) d[n][i] = (t[0][i] + t[1][i] + t[2][i]) * kScaleLog2e;
    }
}
__device__ __forceinline__ void w_piece(uint32_t q, uint32_t lane, float (&d)[2][4]) {
    const uint32_t rr = lane & 7, mi = lane >> 3, kr = 4 * (rr >> 1) + (mi & 2) + (rr & 1);
    const uint32_t pa = s_wv + q * 6144 + (4 * (mi & 2) + rr) * 32 + (((mi ^ (rr >> 2)) & 1) << 4);
    const uint32_t pb = s_wv + 3 * 6144 + kr * 32 + (((mi ^ (kr >> 2)) & 1) << 4);
#pragma unroll
    for (int i = 0; i < 8; i++) (&d[0][0])[i] = 0.f;
#pragma unroll 2
    for (int k = 0; k < 12; k++) {
        uint32_t aq[4], bq[4];
        ldsm4_t(aq, pa + k * 512);
        ldsm4(bq, pb + k * 512);
        mma16816(d[0], aq[0], aq[1], aq[2], aq[3], bq[0], bq[1]);
        mma16816(d[1], aq[0], aq[1], aq[2], aq[3], bq[2], bq[3]);
    }
}
__device__ __forceinline__ uint32_t piece_offset(uint32_t which, uint32_t s, uint32_t mt, uint32_t lane) {
    const uint32_t r8 = lane >> 2;
    return which * kWBytes + wimg_offset(which ? 32 * (mt >> 1) + 8 * (r8 >> 1) + 4 * (mt & 1) + (r8 & 1) : 16 * mt + r8, s, lane & 3);
}
__device__ __forceinline__ void piece_store(Scratch* g, uint32_t par, uint32_t off0, uint32_t which, const float (&d)[2][4]) {
#pragma unroll
    for (int hf = 0; hf < 2; hf++) {
        const uint32_t off = off0 ^ (hf ? which ? 288 : 1024 : 0);
        const uint32_t a = pack_bf16(d[0][2 * hf], d[0][2 * hf + 1]), b = pack_bf16(d[1][2 * hf], d[1][2 * hf + 1]);
        asm volatile("st.relaxed.gpu.global.v2.u32 [%0], {%1, %2};" ::"l"(g->img[par][0] + off), "r"(a ? a : 0x8000u), "r"(b) : "memory");
        asm volatile("st.relaxed.gpu.global.v2.u32 [%0], {%1, %1};" ::"l"(g->img[par ^ 1][0] + off), "r"(0) : "memory");
    }
}

__device__ __forceinline__ uint32_t ld_relaxed(const uint32_t* p) {
    uint32_t v;
    asm volatile("ld.relaxed.gpu.global.u32 %0, [%1];" : "=r"(v) : "l"(p) : "memory");
    return v;
}
__device__ __forceinline__ void count_up(uint32_t* p) {
    asm volatile("red.relaxed.gpu.global.add.u32 [%0], %1;" ::"l"(p), "r"(1) : "memory");
}
__device__ __forceinline__ void bulk_g2s(uint32_t dst, const void* src, uint32_t bytes, uint32_t bar) {
    asm volatile("cp.async.bulk.shared::cluster.global.mbarrier::complete_tx::bytes [%0], [%1], %2, [%3];"
                 ::"r"(dst), "l"(src), "r"(bytes), "r"(bar)
                 : "memory");
}

__device__ __forceinline__ void await_count(const Scratch* g, uint32_t target, int gap) {
#pragma unroll 1
    for (uint32_t spins = 0; spins < (1u << 16); spins++) {
        asm volatile("mbarrier.expect_tx.relaxed.cta.shared::cta.b64 [%0], %1;" ::"r"(bar_poll), "r"(16) : "memory");
        bulk_g2s(s_cnt, g->cnt, 16, bar_poll);
        wait_until(clock_now(), gap);
        if (lds_volatile(s_cnt) >= target) break;
    }
}

__global__ void __launch_bounds__(kThreads, 1)
nat_fused_kernel(const uint8_t* __restrict__ x, const uint8_t* __restrict__ wqkv, uint8_t* __restrict__ out, Scratch* g,
                 const Tables* tables, uint64_t dsc, const __grid_constant__ Maps maps) {
    extern __shared__ __align__(1024) uint8_t smem_raw[];
    const int tid = threadIdx.x, lane = tid & 31;
    const int warp = __shfl_sync(0xffffffffu, tid >> 5, 0);
    const int wg = warp >> 2, wq = warp & 3, r8 = lane >> 2, j = lane & 3;
    const int cta = blockIdx.x;
    if (x == nullptr) return;
    const uint32_t t_start = clock_now();
    uint32_t launch = 0;
    if (warp == 11) launch = ld_relaxed(&g->cnt[1]);
    const uint32_t which = cta >= 72, job = cta - 72 * which;
    if (warp > 7 && wq < 3 && !which) m_partial(wqkv, job / 6, job % 6, wq, lane);
    const Work w = decode_work(maps, cta);
    if (wg == 2) {
        asm volatile("setmaxnreg.dec.sync.aligned.u32 40;");
        if (wq < 3) {
            const uint32_t off = piece_offset(which, which ? job % 12 : 2 * (job % 6) + wq, which ? 3 * (job / 12) + wq : job / 6, lane);
            asm volatile("bar.sync 5, 128;" ::: "memory");
            const uint32_t par = lds_volatile(s_par) & 1;
            if (cta < 120 && wq < 2 + which) {
                float d[2][4];
                if (wq == 0) TRW(which ? 1 : 18);
                if (which) {
                    mbar_wait(bar_wop, 0);
                    if (wq == 0) TRW(2);
                    w_piece(wq, lane, d);
                } else {
                    m_reduce(wq, lane, d);
                }
                piece_store(g, par, off, which, d);
                __syncwarp();
                if (!which && elect()) count_up(&g->cnt[0]);
                if (wq == 0) TRW(which ? 3 : 0);
            }
            asm volatile("bar.arrive 5, 128;" ::: "memory");
            uint32_t phase = 0;
#pragma unroll 1
            for (uint32_t c = 0; c < 6; c++) {
                const uint32_t part = c * kWChunk + wq * (kWChunk / 3);
                mbar_wait(bar_img + 8 * c, 0);
                if (wq == 0) TRW(10 + c);
#pragma unroll 1
                while (phase < 65536) {
                    uint32_t lo = 1;
#pragma unroll
                    for (int q = 0; q < 8; q++) lo = min(lo, lds_volatile(s_m + part + lane * 32 + (lane & 12) * 2 + q * 1024));
                    if (__all_sync(0xffffffffu, lo)) break;
                    if (elect()) {
                        mbar_expect_tx(bar_redo + 8 * wq, kWChunk / 3);
                        bulk_g2s(s_m + part, g->img[par][0] + part, kWChunk / 3, bar_redo + 8 * wq);
                    }
                    mbar_wait(bar_redo + 8 * wq, phase++ & 1);
                }
                if (elect()) mbar_arrive(bar_ok + 8 * min(c, 3u));
            }
        } else {
            const bool leader = elect();
            if (leader) {
#pragma unroll
                for (int i = 0; i < 21; i++) mbar_init(s_bar + 8 * i, i < 13 ? 1 : i < 17 ? 3 : i < 18 ? 9 : 4);
                asm volatile("fence.mbarrier_init.release.cluster;" ::: "memory");
                if ((uint32_t)__cvta_generic_to_shared(smem_raw) != kSmemBase) __trap();
                prefetch_map(w.map + 1);
                if (which && cta < 120) {
                    mbar_expect_tx(bar_wop, 4 * 6144);
                    tma_3d(s_wv, &maps.wo, bar_wop, 0, 3 * (job / 12));
                    tma_3d(s_wv + 3 * 6144, &maps.wv, bar_wop, 16 * (job % 12), 24);
                }
                asm volatile("mbarrier.expect_tx.relaxed.cta.shared::cta.b64 [%0], %1;" ::"r"(bar_a), "r"((uint32_t)sizeof(Table)) : "memory");
                bulk_g2s(s_tab, &tables->t[w.rev >> 3], sizeof(Table), bar_a);
            }
            int u = w.iu, v = w.iv;
#pragma unroll 1
            for (int step = 0, i = 0;; step++) {
                const bool first = step == 0 || (w.corner && step == 4);
                if (leader) w.load_keys(u, v, first, first ? 0 : ~i & 1);
                if (step == 0) {
                    launch /= kGrid;
                    asm volatile("st.shared.v2.u32 [%0], {%1, %2};\nst.shared.v2.u32 [%0 + 8], {%2, %2};" ::"r"(s_par), "r"(launch), "r"(0) : "memory");
                    if (leader) count_up(&g->cnt[1]);
                    asm volatile("bar.arrive 5, 128;\nbar.arrive 3, 160;\nbar.arrive 4, 160;" ::: "memory");
                }
                if (step < 2) {
                    if (step) asm volatile("bar.sync 5, 128;" ::: "memory");
                    wait_until(t_start, step ? TN(5, 0) : TN(6, 2000));
                    if (leader) {
                        if (!step && !TN(8, 0)) await_count(g, (launch + 1) * kPieces, TN(7, 100));
                        TRW(5 + 4 * step);
#pragma unroll 1
                        for (int c = 3 * step; c < 3 * step + 3; c++) {
                            mbar_expect_tx(bar_img + 8 * c, kWChunk);
                            bulk_g2s(s_m + c * kWChunk, g->img[launch & 1][0] + c * kWChunk, kWChunk, bar_img + 8 * c);
                        }
                    }
                    if (!step) { if (TN(1, 1)) mbar_wait(bar_img - 8 + 8 * TN(1, 1), 0); wait_until(t_start, TN(2, 0)); continue; }
                }
                if (w.corner && step == 3) { mbar_wait(bar_use + 8, 1); continue; }
                if (i + 1 == w.ntiles) break;
                mbar_wait(bar_use, i & 1);
                if (w.corner && (i & 1)) { u += 8; v -= 8; } else v += 8 - 2 * w.rev;
                i++;
            }
        }
        TRDUMP();
        return;
    }
    const int order = w.rev ? warp ^ 3 : warp;
    if (order > 4) {
#pragma unroll
        for (int r = 0; r < 3; r++)
            asm volatile("st.shared.v4.u32 [%0], {%1, %1, %1, %1};" ::"r"(s_ring + (order - 5) * kRingChunk + (r == 0 ? 84 : r == 1 ? 88 : 204) * 128 + lane * 16), "r"(0) : "memory");
        asm volatile("fence.proxy.async.shared::cta;" ::: "memory");
    }
    wait_until(t_start, TN(0, 250) + order * TN(3, 650));
    asm volatile("setmaxnreg.inc.sync.aligned.u32 232;");
    int tu = w.iu, tv = w.iv + (8 - 2 * w.rev) * wg;
    const int du2 = w.corner ? 8 : 0, dv2 = 16 - 2 * du2 - 4 * w.rev;
    uint32_t o0, o1;
    w.pixel_offsets(tu + r8, tv + 2 * wq, j, o0, o1);
    uint32_t fa[48];
    {
        RawX raw;
        load_raw(raw, x, o0, o1);
        asm volatile("bar.sync %0, 160;" ::"r"(3 + wg) : "memory");
        raw_to_frags(raw, 0, fa);
        pin(fa);
    }
    const uint64_t dA = dsc + wg * (kSlotStride >> 4), dB = dsc + (wg ^ 1) * (kSlotStride >> 4);

    float acc[96];
    uint32_t po[48];
    uint32_t c0, c1;
    asm volatile("" : "=r"(c0), "=r"(c1));
#pragma unroll
    for (int q = 0; q < 48; q++) asm volatile("" : "=r"(po[q]));
#pragma unroll 1
    for (int i = wg; i < w.ntiles; i += 2) {
        const bool first = i == 0, last = i == w.ntiles - 1;

        TRF(8 + 16 * k);
        mbar_wait(bar_ok, 0);
        wg_fence();
        if (!first) turn_wait(wg);
        proj_gemm(acc, fa, dsc, s_m, [&](int s) {
            if (s == 11 && !first) turn_pass(wg);
            const int n = s < 7 ? (s + 9) >> 1 : s;
            if ((s == 1 || s == 3 || s >= 7) && n >= NPRE) store_one(i >= 2, out + c0, out + c1, po, n);
            if (s == 3 || s == 7) { mbar_wait(bar_ok + 2 * s + 2, 0); wg_fence(); }
        });
        __syncwarp();
        TRF(9 + 16 * k);
        c0 = o0; c1 = o1;
        w.pixel_offsets(tu + du2 + r8, tv + dv2 + 2 * wq, j, o0, o1);
        if (i + 2 >= w.ntiles) o0 = o1 = 0;
        wg_wait<0>();
        pin(acc);
        TR(11 + 16 * k);
        acc_to_frags(acc, fa);
        pin(fa);

        float sA[44], sE[16], sB[44];
        RawX nxt;
        if (!first) turn_wait(wg);
        mbar_wait(bar_a, w.corner ? i >> 1 : 0);
        wg_fence();
#pragma unroll
        for (int s = 0; s < 12; s++)
            if (s == 0) wgmma_n88<true>(sA, fa[4 * s], fa[4 * s + 1], fa[4 * s + 2], fa[4 * s + 3], desc_at(dA, (s >> 2) * kRingChunk + (s & 3) * 32));
            else wgmma_n88<false>(sA, fa[4 * s], fa[4 * s + 1], fa[4 * s + 2], fa[4 * s + 3], desc_at(dA, (s >> 2) * kRingChunk + (s & 3) * 32));
        wg_commit();
        if (!first) turn_pass(wg);
        TRF(12 + 16 * k);
        const int vq = tv + w.cv + 2 * wq;
        const uint4 tabu = lds128(s_tab + offsetof(Table, u) + (window_start(tu + w.cu + r8) - w.origin_u(tu)) * 64 + j * 16);
        const uint4 tabv = lds128(s_tab + offsetof(Table, v) + (window_start(vq) + window_start(vq + 1) - 2 * (tv + w.cv)) * 64 + j * 16);
        const uint4 route = lds128(s_tab + lane * 16);
        if (LDGPOS == 0) load_raw(nxt, x, o0, o1);
        float v0[14], v1[14];
#pragma unroll
        for (int b = 0; b < 14; b++) v0[b] = v1[b] = __int_as_float(0xff800000);
        wg_wait<0>();
        pin(sA);
        gather_outer(sA, tabu.x, tabv.x, v0, v1);
        pin(v0); pin(v1);
        if (!first) turn_wait(wg);
#pragma unroll
        for (int c = 0; c < 3; c++) {
            mbar_wait(bar_b + 8 * c, wg);
            TRF(64 + 4 * k + c);
            wg_fence();
#pragma unroll
            for (int s = 4 * c; s < 4 * c + 4; s++)
                if (s == 0) wgmma_n88<true>(sB, fa[4 * s], fa[4 * s + 1], fa[4 * s + 2], fa[4 * s + 3], desc_at(dB, c * kRingChunk + (s & 3) * 32));
                else wgmma_n88<false>(sB, fa[4 * s], fa[4 * s + 1], fa[4 * s + 2], fa[4 * s + 3], desc_at(dB, c * kRingChunk + (s & 3) * 32));
        }
        wg_commit();
#pragma unroll
        for (int s = 0; s < 12; s++)
            if (s == 0) wgmma_n32<true>(sE, fa[4 * s], fa[4 * s + 1], fa[4 * s + 2], fa[4 * s + 3], desc_at(dsc, kOffMid + (s >> 2) * kRingChunk + (s & 3) * 32));
            else wgmma_n32<false>(sE, fa[4 * s], fa[4 * s + 1], fa[4 * s + 2], fa[4 * s + 3], desc_at(dsc, kOffMid + (s >> 2) * kRingChunk + (s & 3) * 32));
        wg_commit();
        if (OSPLIT || !last) turn_pass(wg);
        TRF(13 + 16 * k);
        wg_wait<1>();
        pin(sB);
        gather_outer(sB, tabu.w, tabv.y, v0, v1);
        wg_wait<0>();
        pin(sE);
        TRF(14 + 16 * k);
        gather_mid(sE, tabu.w, tabv.z, v0, v1);
        const float m0 = quad_max(tree_max(v0)), m1 = quad_max(tree_max(v1));

        uint32_t y[14], pa[12], pb[12];
        exp_route<0, 14>(v0, v1, m0, m1, route, (j & 1) == 0, y);
        unfold<0, 0, 6>(y, tabv.w, pa);
        if (OSPLIT || !last) turn_wait(wg + (y[0] >> 31));
        TRF(15 + 16 * k + (y[13] >> 31));
        wg_fence();
        wgmma_sp_n192_tb<true, 0>(acc, pa[0], pa[1], pa[2], pa[3], desc_at(dA, kToV), tabu.y);
        wgmma_sp_n192_tb<false, 1>(acc, pa[4], pa[5], pa[6], pa[7], desc_at(dA, kToV + 4096), tabu.y);
        wgmma_sp_n192_tb<false, 0>(acc, pa[8], pa[9], pa[10], pa[11], desc_at(dA, kToV + 8192), tabu.z);
        wgmma_sp_n192_tb<false, 1>(acc, y[10], y[11], y[12], y[13], desc_at(dsc, kToV + kOffMid), tabu.z);
        wg_commit();
        unfold<8, 0, 6>(y, tabv.w, pb);
        wg_fence();
        wgmma_sp_n192_tb<false, 0>(acc, pb[0], pb[1], pb[2], pb[3], desc_at(dB, kToV), tabu.y);
        wgmma_sp_n192_tb<false, 1>(acc, pb[4], pb[5], pb[6], pb[7], desc_at(dB, kToV + 4096), tabu.y);
        wgmma_sp_n192_tb<false, 0>(acc, pb[8], pb[9], pb[10], pb[11], desc_at(dB, kToV + 8192), tabu.z);
        wg_commit();
        if (!last) turn_pass(wg);
        TRF(16 + 16 * k);
        const float one = __uint_as_float(lds_volatile(s_late) | 0x3f800000u);
        const float s0 = late_sum(v0, one), s1 = late_sum(v1, one);
        if (LDGPOS == 3) load_raw(nxt, x, o0, o1);
        wg_wait<1>();
        if (lane == 0) mbar_arrive(bar_use);
        TRF(17 + 16 * k);
        mbar_wait(bar_ok + 24, 0);
        wg_wait<0>();
        if (lane == 0) mbar_arrive(bar_use + 8);
        pin(acc);
        TR(18 + 16 * k);

        acc_to_frags(acc, po);
        pin(po);
        if (!last) turn_wait(wg);
        if (OSPLIT && last) turn_pass(wg);
        wg_fence();
        proj_gemm(acc, po, dsc, s_wv, [&](int s) {
            if (s + 1 == OSPLIT && i + 2 == w.ntiles) { turn_pass(wg); turn_wait(wg); }
        });
        if (!last) turn_pass(wg);
        TRF(19 + 16 * k);
        const uint32_t zero = lds_volatile(s_late);
        const float inv0 = rcp(quad_sum(s0 + __uint_as_float(zero))), inv1 = rcp(quad_sum(s1 + __uint_as_float(zero)));
        raw_to_frags(nxt, zero, fa);
        pin(fa);
#pragma unroll
        for (int q = 0; q < 48; q += 4) keep(wqkv == nullptr, fa[q], fa[q + 1], fa[q + 2], fa[q + 3]);
        keep(wqkv == nullptr, __float_as_uint(inv0), __float_as_uint(inv1), zero, lane);
        TRF(20 + 16 * k);
        tu += du2; tv += dv2;
        wg_wait<0>();
        pin(acc);
        TR(21 + 16 * k);
        pack_out(acc, inv0, inv1, po);
        if (OSPLIT && i + 2 == w.ntiles) turn_wait(wg);
#pragma unroll
        for (int n = 0; n < NPRE; n++) store_one(true, out + c0, out + c1, po, n);
        pin(po);
    }
#pragma unroll
    for (int n = NPRE; n < 12; n++) store_one(true, out + c0, out + c1, po, n);
    TR(7);
    TRG(1);
    TRDUMP();
}

typedef CUresult (*EncodeTiledFn)(CUtensorMap*, CUtensorMapDataType, cuuint32_t, void*, const cuuint64_t*, const cuuint64_t*,
                                  const cuuint32_t*, const cuuint32_t*, CUtensorMapInterleave, CUtensorMapSwizzle,
                                  CUtensorMapL2promotion, CUtensorMapFloatOOBfill);

bool make_maps(EncodeTiledFn fn, Maps* maps, void* x, void* wqkv, void* wo) {
    const cuuint64_t pix2 = 2 * kPixBytes, row = (cuuint64_t)kHW * kPixBytes;
    const cuuint32_t estr[5] = {1, 1, 1, 1, 1};
    bool ok = true;
    for (int tr = 0; tr < 2; tr++)
        for (int b = 0; b < 3; b++) {
            const cuuint64_t su = tr ? 2 * row : pix2, sv = tr ? pix2 : 2 * row;
            const cuuint64_t dims[5] = {2 * kC, b < 2 ? 2u : 1u, b < 2 ? 105u : 112u, 2, 112};
            const cuuint64_t strides[4] = {7 * su, su, row, sv};
            const cuuint32_t keys[5] = {64, 2, 7, 1, b ? 2u : 6u}, pixels[5] = {kC, 1, 8, 1, 2};
            ok = ok && fn(&maps->m[3 * tr + b], CU_TENSOR_MAP_DATA_TYPE_BFLOAT16, 5, x, dims, strides, b < 2 ? keys : pixels, estr,
                          CU_TENSOR_MAP_INTERLEAVE_NONE, b < 2 ? CU_TENSOR_MAP_SWIZZLE_128B : CU_TENSOR_MAP_SWIZZLE_NONE,
                          CU_TENSOR_MAP_L2_PROMOTION_L2_128B, CU_TENSOR_MAP_FLOAT_OOB_FILL_NONE) == CUDA_SUCCESS;
        }
    for (int b = 0; b < 2; b++) {
        const cuuint64_t dims[3] = {16, kC, b ? 36u : 12u}, strides[2] = {(b ? 3u : 1u) * kPixBytes, 32};
        const cuuint32_t box[3] = {16, b ? 16u : 192u, b ? 12u : 3u};
        ok = ok && fn(b ? &maps->wv : &maps->wo, CU_TENSOR_MAP_DATA_TYPE_BFLOAT16, 3, b ? wqkv : wo, dims, strides, box, estr,
                      CU_TENSOR_MAP_INTERLEAVE_NONE, CU_TENSOR_MAP_SWIZZLE_32B, CU_TENSOR_MAP_L2_PROMOTION_L2_128B,
                      CU_TENSOR_MAP_FLOAT_OOB_FILL_NONE) == CUDA_SUCCESS;
    }
    return ok;
}

}

extern "C" void kernel_launch(void* const* d_in, const int* in_sizes, int n_in, void* d_out, int out_size) {
    static EncodeTiledFn encode = nullptr;
    static Scratch* scratch = nullptr;
    static Tables* tables = nullptr;
    if (!encode) {
        cudaGetSymbolAddress((void**)&scratch, g_scratch);
        cudaGetSymbolAddress((void**)&tables, g_tables);
        void* fn = nullptr;
        cudaDriverEntryPointQueryResult st;
        cudaGetDriverEntryPoint("cuTensorMapEncodeTiled", &fn, cudaEnableDefault, &st);
        encode = (EncodeTiledFn)fn;
        cudaFuncSetAttribute(nat_fused_kernel, cudaFuncAttributeMaxDynamicSharedMemorySize, kSmemBytes);
    }
    Maps maps;
    if (!encode || !make_maps(encode, &maps, d_in[0], d_in[1], d_in[2])) return;
    nat_fused_kernel<<<kGrid, kThreads, kSmemBytes>>>((const uint8_t*)d_in[0], (const uint8_t*)d_in[1], (uint8_t*)d_out, scratch, tables, kDescRing, maps);
}
```

```cpp
#include <cuda_runtime.h>
#include <cuda_bf16.h>
#include <cuda.h>
#include <stdint.h>
#include <type_traits>
#include <stdlib.h>
#include <stddef.h>

#define LDGPOS 0
#define INPLACE 1
#define KEEPFA 1
#define ASLOTS 0x3800
#define BSLOTS 0x6
#define QSLOTS 0x78a
#define NPRE 0
#define LATESUM 0
#define PREGS 40
#define WUNROLL 2
#define SPLITBLK 0
#define FENCELAST 0
#define GATE 7
#define OSPLIT 0
#define NORM 0
#define GORDER 0
#define ABL 0

namespace {

constexpr int kC          = 192;
constexpr int kHW         = 224;
constexpr int kPixBytes   = kC * 2;
constexpr int kSlotBytes  = 84 * 128;
constexpr int kMidBytes   = 28 * 128;
constexpr int kOffMid     = 88 * 128;
constexpr int kSlotStride = 120 * 128;
constexpr int kRingChunk  = 208 * 128;
constexpr int kWChunk     = 192 * 128;
constexpr int kWBytes     = 3 * kWChunk;
constexpr uint32_t kSmemBase = 1024;
constexpr uint32_t s_ring = kSmemBase, s_m = s_ring + 3 * kRingChunk, s_wv = s_m + kWBytes, s_bar = s_wv + kWBytes;
constexpr uint32_t bar_b = s_bar, bar_img = s_bar + 24, bar_redo = s_bar + 72, bar_wop = s_bar + 96, bar_a = s_bar + 104,
                   bar_ok = s_bar + 112, bar_use = s_bar + 144, bar_poll = s_bar + 160;
constexpr uint32_t s_par = s_bar + 168, s_late = s_bar + 172, s_cnt = s_bar + 176, s_tab = s_bar + 256, s_trace = s_tab + 2048;
constexpr int kSmemBytes  = s_trace + 2048 - kSmemBase;
constexpr int kThreads    = 384, kWUnroll = WUNROLL;
constexpr int kGrid       = 132;
constexpr int kPieces     = 144;
constexpr float kScaleLog2e = 0.07216878364870322f * 1.4426950408889634f;

struct Maps {
    CUtensorMap m[4];
    CUtensorMap wo, wv;
};
#define TN(i, dflt) (dflt)

struct Scratch {
    uint8_t img[2][2][kWBytes];
    uint32_t cnt[4];
};
__device__ __align__(1024) Scratch g_scratch;

struct Table {
    uint32_t route[32][4];
    uint32_t u[8][4][4];
    uint32_t v[16][4][4];
};
struct Tables { Table t[2]; };
constexpr Tables make_tables() {
    Tables r = {};
    for (int rev = 0; rev < 2; rev++)
        for (int j = 0; j < 4; j++) {
            Table& t = r.t[rev];
            for (int q = 0; q < 8; q++) {
                uint32_t* e = t.route[4 * q + j];
                e[0] = 4 * q + 2 * (j & 1) + (j >> 1); e[1] = e[0] ^ 1;
                e[2] = j < 2 ? 0x5410u : 0x1054u; e[3] = e[2] + 0x2222u;
                e = t.u[q][j];
                for (int n = 0; n < 7; n++) e[0] |= ((n + j) % 7 < q ? 1u : 0u) << n;
                e[3] = e[0];
                for (int k = 0; k < 2; k++) {
                    const int step = 2 * k + (j >> 1), p0 = (step < 3 ? 16 * step : 40) + 8 * (j & 1);
                    uint32_t m = 0x8888u;
                    for (int n = 0; n < 8; n++) m |= ((p0 + n) % 7 < q ? 1u : 0u) << (2 * n);
                    e[1 + k] = m * 0x10001u;
                }
            }
            for (int sum = 0; sum < 15; sum++) {
                uint32_t* e = t.v[sum][j];
                for (int row = 0; row < 2; row++)
                    for (int b = 0; b < 14; b++) {
                        const int off = (sum + row) / 2, p = 4 * b + j;
                        const uint32_t bit = 1u << (2 * b + row);
                        if (p < 42 && p >= 7 * off) e[rev] |= bit;
                        if (p < 7 * off - 7) e[1 - rev] |= bit;
                        if (p >= 42 && p >= 7 * off && p < 7 * off + 49) e[2] |= bit;
                    }
                for (int n = 0; n < 6; n++)
                    if (8 * n + 2 * j < 42) e[3] |= 1u << (n + ((8 * n + 2 * j >= 7 * (sum / 2 & ~1)) != rev ? 0 : 8));
            }
        }
    return r;
}
__device__ __align__(128) const Tables g_tables = make_tables();

#define WO4(i) "=f"(d[i]), "=f"(d[i + 1]), "=f"(d[i + 2]), "=f"(d[i + 3])
#define RW4(i) "+f"(d[i]), "+f"(d[i + 1]), "+f"(d[i + 2]), "+f"(d[i + 3])

template <bool FIRST>
__device__ __forceinline__ void wgmma_n192(float (&d)[96], uint32_t a0, uint32_t a1, uint32_t a2, uint32_t a3, uint64_t descb) {
    if constexpr (FIRST) {
        asm volatile(
            "wgmma.mma_async.sync.aligned.m64n192k16.f32.bf16.bf16 "
            "{%0, %1, %2, %3, %4, %5, %6, %7, %8, %9, %10, %11, %12, %13, %14, %15, %16, %17, %18, %19, %20, %21, %22, %23, "
            "%24, %25, %26, %27, %28, %29, %30, %31, %32, %33, %34, %35, %36, %37, %38, %39, %40, %41, %42, %43, %44, %45, %46, %47, "
            "%48, %49, %50, %51, %52, %53, %54, %55, %56, %57, %58, %59, %60, %61, %62, %63, %64, %65, %66, %67, %68, %69, %70, %71, "
            "%72, %73, %74, %75, %76, %77, %78, %79, %80, %81, %82, %83, %84, %85, %86, %87, %88, %89, %90, %91, %92, %93, %94, %95}, "
            "{%96, %97, %98, %99}, %100, 0, 1, 1, 0;"
            : WO4(0), WO4(4), WO4(8), WO4(12), WO4(16), WO4(20), WO4(24), WO4(28), WO4(32), WO4(36), WO4(40), WO4(44),
              WO4(48), WO4(52), WO4(56), WO4(60), WO4(64), WO4(68), WO4(72), WO4(76), WO4(80), WO4(84), WO4(88), WO4(92)
            : "r"(a0), "r"(a1), "r"(a2), "r"(a3), "l"(descb));
    } else {
        asm volatile(
            "wgmma.mma_async.sync.aligned.m64n192k16.f32.bf16.bf16 "
            "{%0, %1, %2, %3, %4, %5, %6, %7, %8, %9, %10, %11, %12, %13, %14, %15, %16, %17, %18, %19, %20, %21, %22, %23, "
            "%24, %25, %26, %27, %28, %29, %30, %31, %32, %33, %34, %35, %36, %37, %38, %39, %40, %41, %42, %43, %44, %45, %46, %47, "
            "%48, %49, %50, %51, %52, %53, %54, %55, %56, %57, %58, %59, %60, %61, %62, %63, %64, %65, %66, %67, %68, %69, %70, %71, "
            "%72, %73, %74, %75, %76, %77, %78, %79, %80, %81, %82, %83, %84, %85, %86, %87, %88, %89, %90, %91, %92, %93, %94, %95}, "
            "{%96, %97, %98, %99}, %100, 1, 1, 1, 0;"
            : RW4(0), RW4(4), RW4(8), RW4(12), RW4(16), RW4(20), RW4(24), RW4(28), RW4(32), RW4(36), RW4(40), RW4(44),
              RW4(48), RW4(52), RW4(56), RW4(60), RW4(64), RW4(68), RW4(72), RW4(76), RW4(80), RW4(84), RW4(88), RW4(92)
            : "r"(a0), "r"(a1), "r"(a2), "r"(a3), "l"(descb));
    }
}

template <bool FIRST>
__device__ __forceinline__ void wgmma_n88(float (&d)[44], uint32_t a0, uint32_t a1, uint32_t a2, uint32_t a3, uint64_t descb) {
    if constexpr (FIRST) {
        asm volatile(
            "wgmma.mma_async.sync.aligned.m64n88k16.f32.bf16.bf16 "
            "{%0, %1, %2, %3, %4, %5, %6, %7, %8, %9, %10, %11, %12, %13, %14, %15, %16, %17, %18, %19, %20, %21, %22, %23, "
            "%24, %25, %26, %27, %28, %29, %30, %31, %32, %33, %34, %35, %36, %37, %38, %39, %40, %41, %42, %43}, "
            "{%44, %45, %46, %47}, %48, 0, 1, 1, 0;"
            : WO4(0), WO4(4), WO4(8), WO4(12), WO4(16), WO4(20), WO4(24), WO4(28), WO4(32), WO4(36), WO4(40)
            : "r"(a0), "r"(a1), "r"(a2), "r"(a3), "l"(descb));
    } else {
        asm volatile(
            "wgmma.mma_async.sync.aligned.m64n88k16.f32.bf16.bf16 "
            "{%0, %1, %2, %3, %4, %5, %6, %7, %8, %9, %10, %11, %12, %13, %14, %15, %16, %17, %18, %19, %20, %21, %22, %23, "
            "%24, %25, %26, %27, %28, %29, %30, %31, %32, %33, %34, %35, %36, %37, %38, %39, %40, %41, %42, %43}, "
            "{%44, %45, %46, %47}, %48, 1, 1, 1, 0;"
            : RW4(0), RW4(4), RW4(8), RW4(12), RW4(16), RW4(20), RW4(24), RW4(28), RW4(32), RW4(36), RW4(40)
            : "r"(a0), "r"(a1), "r"(a2), "r"(a3), "l"(descb));
    }
}

template <bool FIRST>
__device__ __forceinline__ void wgmma_n32(float (&d)[16], uint32_t a0, uint32_t a1, uint32_t a2, uint32_t a3, uint64_t descb) {
    if constexpr (FIRST) {
        asm volatile(
            "wgmma.mma_async.sync.aligned.m64n32k16.f32.bf16.bf16 "
            "{%0, %1, %2, %3, %4, %5, %6, %7, %8, %9, %10, %11, %12, %13, %14, %15}, "
            "{%16, %17, %18, %19}, %20, 0, 1, 1, 0;"
            : WO4(0), WO4(4), WO4(8), WO4(12)
            : "r"(a0), "r"(a1), "r"(a2), "r"(a3), "l"(descb));
    } else {
        asm volatile(
            "wgmma.mma_async.sync.aligned.m64n32k16.f32.bf16.bf16 "
            "{%0, %1, %2, %3, %4, %5, %6, %7, %8, %9, %10, %11, %12, %13, %14, %15}, "
            "{%16, %17, %18, %19}, %20, 1, 1, 1, 0;"
            : RW4(0), RW4(4), RW4(8), RW4(12)
            : "r"(a0), "r"(a1), "r"(a2), "r"(a3), "l"(descb));
    }
}

template <bool FIRST, int SEL>
__device__ __forceinline__ void wgmma_sp_n192_tb(float (&d)[96], uint32_t a0, uint32_t a1, uint32_t a2, uint32_t a3, uint64_t descb, uint32_t meta) {
    if constexpr (FIRST) {
        asm volatile(
            "wgmma.mma_async.sp.sync.aligned.m64n192k32.f32.bf16.bf16 "
            "{%0, %1, %2, %3, %4, %5, %6, %7, %8, %9, %10, %11, %12, %13, %14, %15, %16, %17, %18, %19, %20, %21, %22, %23, "
            "%24, %25, %26, %27, %28, %29, %30, %31, %32, %33, %34, %35, %36, %37, %38, %39, %40, %41, %42, %43, %44, %45, %46, %47, "
            "%48, %49, %50, %51, %52, %53, %54, %55, %56, %57, %58, %59, %60, %61, %62, %63, %64, %65, %66, %67, %68, %69, %70, %71, "
            "%72, %73, %74, %75, %76, %77, %78, %79, %80, %81, %82, %83, %84, %85, %86, %87, %88, %89, %90, %91, %92, %93, %94, %95}, "
            "{%96, %97, %98, %99}, %100, %101, %102, 0, 1, 1, 1;"
            : WO4(0), WO4(4), WO4(8), WO4(12), WO4(16), WO4(20), WO4(24), WO4(28), WO4(32), WO4(36), WO4(40), WO4(44),
              WO4(48), WO4(52), WO4(56), WO4(60), WO4(64), WO4(68), WO4(72), WO4(76), WO4(80), WO4(84), WO4(88), WO4(92)
            : "r"(a0), "r"(a1), "r"(a2), "r"(a3), "l"(descb), "r"(meta), "n"(SEL));
    } else {
        asm volatile(
            "wgmma.mma_async.sp.sync.aligned.m64n192k32.f32.bf16.bf16 "
            "{%0, %1, %2, %3, %4, %5, %6, %7, %8, %9, %10, %11, %12, %13, %14, %15, %16, %17, %18, %19, %20, %21, %22, %23, "
            "%24, %25, %26, %27, %28, %29, %30, %31, %32, %33, %34, %35, %36, %37, %38, %39, %40, %41, %42, %43, %44, %45, %46, %47, "
            "%48, %49, %50, %51, %52, %53, %54, %55, %56, %57, %58, %59, %60, %61, %62, %63, %64, %65, %66, %67, %68, %69, %70, %71, "
            "%72, %73, %74, %75, %76, %77, %78, %79, %80, %81, %82, %83, %84, %85, %86, %87, %88, %89, %90, %91, %92, %93, %94, %95}, "
            "{%96, %97, %98, %99}, %100, %101, %102, 1, 1, 1, 1;"
            : RW4(0), RW4(4), RW4(8), RW4(12), RW4(16), RW4(20), RW4(24), RW4(28), RW4(32), RW4(36), RW4(40), RW4(44),
              RW4(48), RW4(52), RW4(56), RW4(60), RW4(64), RW4(68), RW4(72), RW4(76), RW4(80), RW4(84), RW4(88), RW4(92)
            : "r"(a0), "r"(a1), "r"(a2), "r"(a3), "l"(descb), "r"(meta), "n"(SEL));
    }
}

#define TR(slot)
#define TRT(slot)
#define TRF(slot)
#define TRW(slot)
#define TRG(slot)
#define TRDUMP()

__device__ __forceinline__ void wg_fence() { asm volatile("wgmma.fence.sync.aligned;" ::: "memory"); }
__device__ __forceinline__ void wg_commit() { asm volatile("wgmma.commit_group.sync.aligned;" ::: "memory"); }
template <int N>
__device__ __forceinline__ void wg_wait() { asm volatile("wgmma.wait_group.sync.aligned %0;" ::"n"(N) : "memory"); }

template <int N>
__device__ __forceinline__ void pin(float (&d)[N]) {
#pragma unroll
    for (int i = 0; i < N; i++) asm volatile("" : "+f"(d[i])::"memory");
}
template <int N>
__device__ __forceinline__ void pin(uint32_t (&d)[N]) {
#pragma unroll
    for (int i = 0; i < N; i++) asm volatile("" : "+r"(d[i])::"memory");
}

constexpr uint64_t kDescRing = ((uint64_t)((1u << 30) | (1024u >> 4)) << 32) | (1u << 16) | (s_ring >> 4);
constexpr uint32_t kToV = ((kRingChunk >> 4) - 1) << 20;
__device__ __forceinline__ uint64_t desc_at(uint64_t base, uint32_t byte_off) {
    uint64_t d;
    asm volatile("add.s64 %0, %1, %2;" : "=l"(d) : "l"(base), "l"((uint64_t)(byte_off >> 4)));
    return d;
}

__device__ __forceinline__ void mbar_init(uint32_t bar, uint32_t count) {
    asm volatile("mbarrier.init.shared::cta.b64 [%0], %1;" ::"r"(bar), "r"(count) : "memory");
}
__device__ __forceinline__ void mbar_expect_tx(uint32_t bar, uint32_t bytes) {
    asm volatile("mbarrier.arrive.expect_tx.shared::cta.b64 _, [%0], %1;" ::"r"(bar), "r"(bytes) : "memory");
}
__device__ __forceinline__ void mbar_arrive(uint32_t bar) {
    asm volatile("mbarrier.arrive.shared::cta.b64 _, [%0];" ::"r"(bar) : "memory");
}
__device__ __forceinline__ void mbar_wait(uint32_t bar, uint32_t parity) {
    asm volatile(
        "{\n.reg .pred p;\n"
        "W: mbarrier.try_wait.parity.shared::cta.b64 p, [%0], %1;\n"
        "@!p bra W;\n}\n"
        ::"r"(bar), "r"(parity) : "memory");
}
__device__ __forceinline__ uint32_t clock_now() {
    uint32_t c;
    asm volatile("mov.u32 %0, %%clock;" : "=r"(c)::"memory");
    return c;
}
__device__ __forceinline__ void wait_until(uint32_t t0, int t) {
    if (t == 0) return;
    while ((int)(clock_now() - t0) < t) {}
}
__device__ __forceinline__ bool elect() {
    uint32_t ok;
    asm volatile("{\n.reg .pred p;\nelect.sync _|p, 0xffffffff;\nselp.u32 %0, 1, 0, p;\n}\n" : "=r"(ok));
    return ok != 0;
}
__device__ __forceinline__ void turn_wait(int wg) { asm volatile("bar.sync %0, 256;" ::"r"(1 + wg) : "memory"); }
__device__ __forceinline__ void turn_pass(int wg) { asm volatile("bar.arrive %0, 256;" ::"r"(2 - wg) : "memory"); }

__device__ __forceinline__ void tma_box(uint32_t dst, const CUtensorMap* map, uint32_t bar, int c0, int c2, int c3, int c4) {
    asm volatile(
        "cp.async.bulk.tensor.5d.shared::cluster.global.mbarrier::complete_tx::bytes [%0], [%1, {%3, %4, %5, %6, %7}], [%2];"
        ::"r"(dst), "l"(map), "r"(bar), "r"(c0), "r"(0), "r"(c2), "r"(c3), "r"(c4)
        : "memory");
}
__device__ __forceinline__ void tma_3d(uint32_t dst, const CUtensorMap* map, uint32_t bar, int c1, int c2) {
    asm volatile("cp.async.bulk.tensor.3d.shared::cluster.global.mbarrier::complete_tx::bytes [%0], [%1, {%3, %4, %5}], [%2];"
                 ::"r"(dst), "l"(map), "r"(bar), "r"(0), "r"(c1), "r"(c2)
                 : "memory");
}
__device__ __forceinline__ void prefetch_map(const CUtensorMap* map) {
    asm volatile("prefetch.tensormap [%0];" ::"l"(map) : "memory");
}
__device__ __forceinline__ uint4 ldg(const void* p) {
    uint4 v;
    asm volatile("ld.global.v4.u32 {%0, %1, %2, %3}, [%4];" : "=r"(v.x), "=r"(v.y), "=r"(v.z), "=r"(v.w) : "l"(p) : "memory");
    return v;
}
__device__ __forceinline__ uint32_t pack_bf16(float lo, float hi) {
    uint32_t r;
    asm("cvt.rn.bf16x2.f32 %0, %1, %2;" : "=r"(r) : "f"(hi), "f"(lo));
    return r;
}
__device__ __forceinline__ uint32_t mul_bf16x2(uint32_t a, uint32_t b) {
    uint32_t r;
    asm("mul.rn.bf16x2 %0, %1, %2;" : "=r"(r) : "r"(a), "r"(b));
    return r;
}
__device__ __forceinline__ float ex2(float x) {
    float y;
    asm("ex2.approx.ftz.f32 %0, %1;" : "=f"(y) : "f"(x));
    return y;
}
__device__ __forceinline__ float rcp(float x) {
    float y;
    asm("rcp.approx.ftz.f32 %0, %1;" : "=f"(y) : "f"(x));
    return y;
}
__device__ __forceinline__ void mma16816(float (&d)[4], uint32_t a0, uint32_t a1, uint32_t a2, uint32_t a3, uint32_t b0, uint32_t b1) {
    asm volatile("mma.sync.aligned.m16n8k16.row.col.f32.bf16.bf16.f32 {%0, %1, %2, %3}, {%4, %5, %6, %7}, {%8, %9}, {%0, %1, %2, %3};"
                 : "+f"(d[0]), "+f"(d[1]), "+f"(d[2]), "+f"(d[3])
                 : "r"(a0), "r"(a1), "r"(a2), "r"(a3), "r"(b0), "r"(b1));
}
__device__ __forceinline__ uint4 lds128(uint32_t addr) {
    uint4 v;
    asm volatile("ld.volatile.shared.v4.u32 {%0, %1, %2, %3}, [%4];" : "=r"(v.x), "=r"(v.y), "=r"(v.z), "=r"(v.w) : "r"(addr) : "memory");
    return v;
}
__device__ __forceinline__ uint32_t lds_volatile(uint32_t addr) {
    uint32_t v;
    asm volatile("ld.volatile.shared.u32 %0, [%1];" : "=r"(v) : "r"(addr) : "memory");
    return v;
}

__device__ __forceinline__ int window_start(int i_shifted) { return min(max(i_shifted, 0), 105); }

struct Work {
    int cu, cv;
    uint32_t su, sv;
    int iu, iv;
    int corner, ntiles;
    int rev;
    const CUtensorMap* map;
    int c0, c3;
    __device__ __forceinline__ int origin_u(int u) const { return min(max(u + cu, 0), 98); }
    __device__ __forceinline__ void pixel_offsets(int u, int v, int j, uint32_t& o0, uint32_t& o1) const {
        const uint32_t base = (u + window_start(u + cu) + (cu ? 0 : 7)) * su + j * 16 + (v + (cv ? 0 : 7)) * sv;
        o0 = base + window_start(v + cv) * sv;
        o1 = base + (window_start(v + 1 + cv) + 1) * sv;
    }
    __device__ __forceinline__ void load_keys(int u, int v, bool first, int slot) const {
#pragma unroll 1
        for (int c = 0; c < 3; c++) {
            const uint32_t bar = first ? bar_a : bar_b + 8 * c;
            mbar_expect_tx(bar, first ? kSlotBytes : kSlotBytes + kMidBytes);
            tma_box(s_ring + c * kRingChunk + slot * kSlotStride, map, bar, c0 + 64 * c, origin_u(u), c3, v + cv + (first ? rev : 8 - rev));
            if (!first) tma_box(s_ring + c * kRingChunk + kOffMid + 512, map + 1, bar, c0 + 64 * c, origin_u(u), c3, v + cv + 6);
        }
    }
};

__device__ __forceinline__ Work decode_work(const Maps& maps, int c) {
    Work w;
    const int idx = c >> 2, ypar = (c >> 1) & 1, xpar = c & 1;
    const bool transposed = (idx >> 2) == 7;
    w.corner = idx == 32;
    w.cu = 6 * (transposed ? ypar : xpar) - 6;
    w.cv = 6 * (transposed ? xpar : ypar) - 6;
    w.su = transposed ? kHW * kPixBytes : kPixBytes;
    w.sv = transposed ? kPixBytes : kHW * kPixBytes;
    w.iu = idx < 28 ? 8 * (idx >> 1) : 96 + 4 * (idx & 2);
    w.rev = w.corner ? 0 : 8 * (idx & 1);
    w.iv = w.corner ? 96 : 48 - w.rev;
    w.ntiles = w.corner ? 4 : 6;
    w.map = &maps.m[transposed ? 2 : 0];
    w.c0 = xpar * kC;
    w.c3 = ypar;
    return w;
}

struct RawX { uint4 a[6], b[6]; };
__device__ __forceinline__ void load_raw(RawX& r, const uint8_t* base, uint32_t o0, uint32_t o1) {
    __syncwarp();
#pragma unroll
    for (int c = 0; c < 6; c++) { r.a[c] = ldg(base + o0 + c * 64); r.b[c] = ldg(base + o1 + c * 64); }
    __syncwarp();
}
__device__ __forceinline__ void raw_to_frags(const RawX& r, uint32_t zero, uint32_t (&f)[48]) {
#pragma unroll
    for (int c = 0; c < 6; c++) {
        f[8 * c + 0] = r.a[c].x; f[8 * c + 2] = r.a[c].z; f[8 * c + 4] = r.a[c].y ^ zero; f[8 * c + 6] = r.a[c].w ^ zero;
        f[8 * c + 1] = r.b[c].x ^ zero; f[8 * c + 3] = r.b[c].z ^ zero; f[8 * c + 5] = r.b[c].y ^ zero; f[8 * c + 7] = r.b[c].w ^ zero;
    }
}
__device__ __forceinline__ void acc_to_frags(const float (&d)[96], uint32_t (&f)[48]) {
#pragma unroll
    for (int i = 0; i < 48; i++) f[i] = pack_bf16(d[2 * i], d[2 * i + 1]);
}

template <class F>
__device__ __forceinline__ void proj_gemm(float (&d)[96], const uint32_t (&a)[48], uint64_t dsc, uint32_t img, F after) {
#pragma unroll
    for (int s = 0; s < 12; s++) {
        if (s == 0) wgmma_n192<true>(d, a[4 * s], a[4 * s + 1], a[4 * s + 2], a[4 * s + 3], desc_at(dsc, img - s_ring + (s >> 2) * kWChunk + (s & 3) * 32));
        else wgmma_n192<false>(d, a[4 * s], a[4 * s + 1], a[4 * s + 2], a[4 * s + 3], desc_at(dsc, img - s_ring + (s >> 2) * kWChunk + (s & 3) * 32));
        if (s == 11) wg_commit();
        after(s);
    }
}
__device__ __forceinline__ void pack_out(const float (&acc)[96], uint32_t (&po)[48]) {
#pragma unroll
    for (int g = 0; g < 6; g++)
#pragma unroll
        for (int q = 0; q < 4; q++) {
            po[8 * g + q] = pack_bf16(acc[16 * g + 4 * q], acc[16 * g + 4 * q + 1]);
            po[8 * g + 4 + q] = pack_bf16(acc[16 * g + 4 * q + 2], acc[16 * g + 4 * q + 3]);
        }
}
template <bool PINNED = true>
__device__ __forceinline__ void store_one(bool on, uint8_t* p0, uint8_t* p1, const uint32_t (&po)[48], int n) {
    if (PINNED) __syncwarp();
    asm volatile("{\n.reg .pred p;\nsetp.ne.u32 p, %5, 0;\n@p st.global.v4.u32 [%0], {%1, %2, %3, %4};\n}\n"
                 ::"l"(((n & 1) ? p1 : p0) + (n >> 1) * 64), "r"(po[4 * n]), "r"(po[4 * n + 1]), "r"(po[4 * n + 2]), "r"(po[4 * n + 3]), "r"((uint32_t)on) : "memory");
}

template <int N>
__device__ __forceinline__ float tree_max(const float (&v)[N]) {
    float t[N];
#pragma unroll
    for (int i = 0; i < N; i++) t[i] = v[i];
#pragma unroll
    for (int w = 1; w < N; w *= 2)
#pragma unroll
        for (int i = 0; i + w < N; i += 2 * w) t[i] = fmaxf(t[i], t[i + w]);
    return t[0];
}
template <int N>
__device__ __forceinline__ float tree_sum(const float (&v)[N]) {
    float t[N];
#pragma unroll
    for (int i = 0; i < N; i++) t[i] = v[i];
#pragma unroll
    for (int w = 1; w < N; w *= 2)
#pragma unroll
        for (int i = 0; i + w < N; i += 2 * w) t[i] += t[i + w];
    return t[0];
}

template <int B>
__device__ __forceinline__ void pick(uint32_t h, uint32_t ok, const float* s, float& v0, float& v1) {
    asm("{\n.reg .pred p, q0, q1;\n.reg .b32 t;\nand.b32 t, %6, %7;\nsetp.ne.u32 p, t, 0;\n"
        "and.b32 t, %8, %9;\nsetp.ne.u32 q0, t, 0;\nand.b32 t, %8, %10;\nsetp.ne.u32 q1, t, 0;\n"
        "@q0 selp.f32 %0, %3, %2, p;\n@q1 selp.f32 %1, %5, %4, p;\n}\n"
        : "+f"(v0), "+f"(v1)
        : "f"(s[0]), "f"(s[1]), "f"(s[2]), "f"(s[3]), "r"(h), "n"(1 << ((4 * B) % 7)), "r"(ok), "n"(1 << (2 * B)), "n"(2 << (2 * B)));
}
template <int B, class F>
__device__ __forceinline__ void for_blocks(F f) {
    if constexpr (B > 0) { for_blocks<B - 1>(f); f(std::integral_constant<int, B - 1>{}); }
}
__device__ __forceinline__ void gather_outer(const float (&s)[44], uint32_t h, uint32_t ok, float (&v0)[14], float (&v1)[14]) {
    for_blocks<11>([&](auto B) {
        constexpr int b = GORDER ? B.value : B.value < 8 ? (B.value >> 1) + 7 * (B.value & 1) : B.value - 4;
        pick<b>(h, ok, &s[4 * b], v0[b], v1[b]);
    });
}
__device__ __forceinline__ void gather_mid(const float (&sE)[16], uint32_t h, uint32_t ok, float (&v0)[14], float (&v1)[14]) {
    for_blocks<4>([&](auto B) { pick<10 + B.value>(h, ok, &sE[4 * B.value], v0[10 + B.value], v1[10 + B.value]); });
}
__device__ __forceinline__ float quad_max(float m) {
    m = fmaxf(m, __shfl_xor_sync(0xffffffffu, m, 1));
    return fmaxf(m, __shfl_xor_sync(0xffffffffu, m, 2));
}
__device__ __forceinline__ float quad_sum(float s) {
    s += __shfl_xor_sync(0xffffffffu, s, 1);
    return s + __shfl_xor_sync(0xffffffffu, s, 2);
}
template <int B0, int B1>
__device__ __forceinline__ void exp_route(float (&v0)[14], float (&v1)[14], float m0, float m1, const uint4& r, bool even, uint32_t (&y)[14]) {
#pragma unroll
    for (int b = B0; b < B1; b++) { v0[b] = ex2(v0[b] - m0); v1[b] = ex2(v1[b] - m1); }
#pragma unroll
    for (int b = B0; b < B1; b += 2) {
        const uint32_t x0 = pack_bf16(v0[b], v1[b]), x1 = pack_bf16(v0[b + 1], v1[b + 1]);
        const uint32_t u = __shfl_sync(0xffffffffu, even ? x0 : x1, r.x);
        const uint32_t w = __shfl_sync(0xffffffffu, even ? x1 : x0, r.y);
        y[b] = __byte_perm(u, w, r.z); y[b + 1] = __byte_perm(u, w, r.w);
    }
}
template <int BIT0, int N0, int N1>
__device__ __forceinline__ void unfold(const uint32_t (&y)[14], uint32_t fold, uint32_t (&p)[12]) {
    for_blocks<N1 - N0>([&](auto N) {
        constexpr int n = N0 + N.value;
        asm("{\n.reg .pred p;\n.reg .b32 t;\nand.b32 t, %4, %5;\nsetp.ne.u32 p, t, 0;\nselp.b32 %0, %2, 0, p;\nselp.b32 %1, %3, 0, p;\n}\n"
            : "=r"(p[2 * n]), "=r"(p[2 * n + 1]) : "r"(y[2 * n]), "r"(y[2 * n + 1]), "r"(fold), "n"(1 << (BIT0 + n)));
    });
}
__device__ __forceinline__ float late_sum(const float (&v)[14], float one) {
    float t[7];
#pragma unroll
    for (int i = 0; i < 7; i++) t[i] = fmaf(v[2 * i], one, v[2 * i + 1]);
    return tree_sum(t);
}
__device__ __forceinline__ void keep(bool never, uint32_t a, uint32_t b, uint32_t c, uint32_t d) {
    asm volatile("{\n.reg .pred p;\nsetp.ne.u32 p, %4, 0;\n@p st.volatile.shared.v4.u32 [%5], {%0, %1, %2, %3};\n}\n"
                 ::"r"(a), "r"(b), "r"(c), "r"(d), "r"((uint32_t)never), "r"(s_trace) : "memory");
}

__device__ __forceinline__ uint32_t wimg_offset(uint32_t row, uint32_t s, uint32_t j) {
    return (s >> 2) * kWChunk + row * 128 + (((2 * (s & 3) + (j >> 1)) ^ (row & 7)) << 4) + (j & 1) * 8;
}

__device__ __forceinline__ void ldsm4(uint32_t (&r)[4], uint32_t addr) {
    asm volatile("ldmatrix.sync.aligned.m8n8.x4.shared.b16 {%0, %1, %2, %3}, [%4];" : "=r"(r[0]), "=r"(r[1]), "=r"(r[2]), "=r"(r[3]) : "r"(addr) : "memory");
}
__device__ __forceinline__ void ldsm4_t(uint32_t (&r)[4], uint32_t addr) {
    asm volatile("ldmatrix.sync.aligned.m8n8.x4.trans.shared.b16 {%0, %1, %2, %3}, [%4];" : "=r"(r[0]), "=r"(r[1]), "=r"(r[2]), "=r"(r[3]) : "r"(addr) : "memory");
}
__device__ __forceinline__ void m_partial(const uint8_t* wqkv, uint32_t mt, uint32_t sp, uint32_t q, uint32_t lane) {
    const uint32_t r8 = lane >> 2, col = q * 128 + (lane & 3) * 16;
    const uint8_t* pa = wqkv + (16 * mt + r8) * 1152 + col;
    const uint8_t* pb = wqkv + (32 * sp + 8 * (r8 & 2) + (r8 & 5)) * 1152 + col;
    uint4 A[2][2], B[4][2];
#pragma unroll
    for (int c = 0; c < 2; c++) {
#pragma unroll
        for (int h = 0; h < 2; h++) A[h][c] = ldg(pa + 384 + h * 8 * 1152 + c * 64);
#pragma unroll
        for (int n = 0; n < 4; n++) B[n][c] = ldg(pb + ((n & 1) * 8 + (n & 2)) * 1152 + c * 64);
    }
#pragma unroll
    for (int n = 0; n < 4; n++) {
        float d[4] = {0.f, 0.f, 0.f, 0.f};
#pragma unroll
        for (int c = 0; c < 2; c++) {
            mma16816(d, A[0][c].x, A[1][c].x, A[0][c].y, A[1][c].y, B[n][c].x, B[n][c].y);
            mma16816(d, A[0][c].z, A[1][c].z, A[0][c].w, A[1][c].w, B[n][c].z, B[n][c].w);
        }
        asm volatile("st.shared.v4.f32 [%0], {%1, %2, %3, %4};" ::"r"(s_wv + q * 2048 + n * 512 + lane * 16), "f"(d[0]), "f"(d[1]), "f"(d[2]), "f"(d[3]) : "memory");
    }
}
__device__ __forceinline__ void m_reduce(uint32_t e, uint32_t lane, float (&d)[2][4]) {
#pragma unroll
    for (int n = 0; n < 2; n++) {
        float t[3][4];
#pragma unroll
        for (int q = 0; q < 3; q++)
            asm volatile("ld.shared.v4.f32 {%0, %1, %2, %3}, [%4];" : "=f"(t[q][0]), "=f"(t[q][1]), "=f"(t[q][2]), "=f"(t[q][3]) : "r"(s_wv + q * 2048 + e * 1024 + n * 512 + lane * 16) : "memory");
#pragma unroll
        for (int i = 0; i < 4; i++) d[n][i] = (t[0][i] + t[1][i] + t[2][i]) * kScaleLog2e;
    }
}
__device__ __forceinline__ void w_piece(uint32_t q, uint32_t lane, float (&d)[2][4]) {
    const uint32_t rr = lane & 7, mi = lane >> 3, kr = 4 * (rr >> 1) + (mi & 2) + (rr & 1);
    const uint32_t pa = s_wv + q * 6144 + (4 * (mi & 2) + rr) * 32 + (((mi ^ (rr >> 2)) & 1) << 4);
    const uint32_t pb = s_wv + 3 * 6144 + kr * 32 + (((mi ^ (kr >> 2)) & 1) << 4);
#pragma unroll
    for (int i = 0; i < 8; i++) (&d[0][0])[i] = 0.f;
#pragma unroll kWUnroll
    for (int k = 0; k < 12; k++) {
        uint32_t aq[4], bq[4];
        ldsm4_t(aq, pa + k * 512);
        ldsm4(bq, pb + k * 512);
        mma16816(d[0], aq[0], aq[1], aq[2], aq[3], bq[0], bq[1]);
        mma16816(d[1], aq[0], aq[1], aq[2], aq[3], bq[2], bq[3]);
    }
}
__device__ __forceinline__ uint32_t piece_offset(uint32_t which, uint32_t s, uint32_t mt, uint32_t lane) {
    const uint32_t r8 = lane >> 2;
    return which * kWBytes + wimg_offset(which ? 32 * (mt >> 1) + 8 * (r8 >> 1) + 4 * (mt & 1) + (r8 & 1) : 16 * mt + r8, s, lane & 3);
}
__device__ __forceinline__ void piece_store(Scratch* g, uint32_t par, uint32_t off0, uint32_t which, const float (&d)[2][4]) {
#pragma unroll
    for (int hf = 0; hf < 2; hf++) {
        const uint32_t off = off0 ^ (hf ? which ? 288 : 1024 : 0);
        const uint32_t a = pack_bf16(d[0][2 * hf], d[0][2 * hf + 1]), b = pack_bf16(d[1][2 * hf], d[1][2 * hf + 1]);
        asm volatile("st.relaxed.gpu.global.v2.u32 [%0], {%1, %2};" ::"l"(g->img[par][0] + off), "r"(a ? a : 0x8000u), "r"(b) : "memory");
        asm volatile("st.relaxed.gpu.global.v2.u32 [%0], {%1, %1};" ::"l"(g->img[par ^ 1][0] + off), "r"(0) : "memory");
    }
}

__device__ __forceinline__ uint32_t ld_relaxed(const uint32_t* p) {
    uint32_t v;
    asm volatile("ld.relaxed.gpu.global.u32 %0, [%1];" : "=r"(v) : "l"(p) : "memory");
    return v;
}
__device__ __forceinline__ void count_up(uint32_t* p) {
    asm volatile("red.relaxed.gpu.global.add.u32 [%0], %1;" ::"l"(p), "r"(1) : "memory");
}
__device__ __forceinline__ void bulk_g2s(uint32_t dst, const void* src, uint32_t bytes, uint32_t bar) {
    asm volatile("cp.async.bulk.shared::cluster.global.mbarrier::complete_tx::bytes [%0], [%1], %2, [%3];"
                 ::"r"(dst), "l"(src), "r"(bytes), "r"(bar)
                 : "memory");
}

__device__ __forceinline__ void await_count(const Scratch* g, uint32_t target, int gap) {
#pragma unroll 1
    for (uint32_t spins = 0; spins < (1u << 16); spins++) {
        asm volatile("mbarrier.expect_tx.relaxed.cta.shared::cta.b64 [%0], %1;" ::"r"(bar_poll), "r"(16) : "memory");
        bulk_g2s(s_cnt, g->cnt, 16, bar_poll);
        wait_until(clock_now(), gap);
        if (lds_volatile(s_cnt) >= target) break;
    }
}

__global__ void __launch_bounds__(kThreads, 1)
nat_fused_kernel(const uint8_t* __restrict__ x, const uint8_t* __restrict__ wqkv, uint8_t* __restrict__ out, Scratch* g,
                 const Tables* tables, uint64_t dsc, const __grid_constant__ Maps maps) {
    extern __shared__ __align__(1024) uint8_t smem_raw[];
    const int tid = threadIdx.x, lane = tid & 31;
    const int warp = __shfl_sync(0xffffffffu, tid >> 5, 0);
    const int wg = warp >> 2, wq = warp & 3, r8 = lane >> 2, j = lane & 3;
    const int cta = blockIdx.x;
    if (x == nullptr) return;
    const uint32_t t_start = clock_now();
    uint32_t launch = 0;
    if (warp == 11) launch = ld_relaxed(&g->cnt[1]);
    const uint32_t which = cta >= 72, job = cta - 72 * which;
    if (warp > 7 && wq < 3 && !which) m_partial(wqkv, job / 6, job % 6, wq, lane);
    const Work w = decode_work(maps, cta);
    if (wg == 2) {
        asm volatile("setmaxnreg.dec.sync.aligned.u32 %0;" ::"n"(PREGS));
        if (wq < 3) {
            const uint32_t off = piece_offset(which, which ? job % 12 : 2 * (job % 6) + wq, which ? 3 * (job / 12) + wq : job / 6, lane);
            asm volatile("bar.sync 5, 128;" ::: "memory");
            const uint32_t par = lds_volatile(s_par) & 1;
            if (cta < 120 && wq < 2 + which) {
                float d[2][4];
                if (wq == 0) TRW(which ? 1 : 18);
                if (which) {
                    mbar_wait(bar_wop, 0);
                    if (wq == 0) TRW(2);
                    w_piece(wq, lane, d);
                } else {
                    m_reduce(wq, lane, d);
                }
                piece_store(g, par, off, which, d);
                __syncwarp();
                if (!which && elect()) count_up(&g->cnt[0]);
                if (wq == 0) TRW(which ? 3 : 0);
            }
            asm volatile("bar.arrive 6, 128;" ::: "memory");
            uint32_t phase = 0;
#pragma unroll 1
            for (uint32_t c = 0; c < 6; c++) {
                const uint32_t part = c * kWChunk + wq * (kWChunk / 3);
                mbar_wait(bar_img + 8 * c, 0);
                if (wq == 0) TRW(10 + c);
#pragma unroll 1
                while (phase < 65536) {
                    uint32_t lo = 1;
#pragma unroll
                    for (int q = 0; q < 8; q++) lo = min(lo, lds_volatile(s_m + part + lane * 32 + (lane & 12) * 2 + q * 1024));
                    if (__all_sync(0xffffffffu, lo) || ((ABL & 1) && wqkv)) break;
                    if (elect()) {
                        mbar_expect_tx(bar_redo + 8 * wq, kWChunk / 3);
                        bulk_g2s(s_m + part, g->img[par][0] + part, kWChunk / 3, bar_redo + 8 * wq);
                    }
                    mbar_wait(bar_redo + 8 * wq, phase++ & 1);
                }
                if (elect()) mbar_arrive(bar_ok + 8 * min(c, 3u));
            }
        } else {
            const bool leader = elect();
            if (leader) {
#pragma unroll
                for (int i = 0; i < 21; i++) mbar_init(s_bar + 8 * i, i < 13 ? 1 : i < 17 ? 3 : i < 18 ? 9 : 4);
                asm volatile("fence.mbarrier_init.release.cluster;" ::: "memory");
                if ((uint32_t)__cvta_generic_to_shared(smem_raw) != kSmemBase) __trap();
                prefetch_map(w.map + 1);
                if (which && cta < 120) {
                    mbar_expect_tx(bar_wop, 4 * 6144);
                    tma_3d(s_wv, &maps.wo, bar_wop, 0, 3 * (job / 12));
                    tma_3d(s_wv + 3 * 6144, &maps.wv, bar_wop, 16 * (job % 12), 24);
                }
                asm volatile("mbarrier.expect_tx.relaxed.cta.shared::cta.b64 [%0], %1;" ::"r"(bar_a), "r"((uint32_t)sizeof(Table)) : "memory");
                bulk_g2s(s_tab, &tables->t[w.rev >> 3], sizeof(Table), bar_a);
            }
            int u = w.iu, v = w.iv;
#pragma unroll 1
            for (int step = 0, i = 0;; step++) {
                const bool first = step == 0 || (w.corner && step == 4);
                if (leader) w.load_keys(u, v, first, first ? 0 : ~i & 1);
                if (step == 0) {
                    launch /= kGrid;
                    asm volatile("st.shared.v2.u32 [%0], {%1, %2};\nst.shared.v2.u32 [%0 + 8], {%2, %2};" ::"r"(s_par), "r"(launch), "r"(0) : "memory");
                    if (leader) count_up(&g->cnt[1]);
                    asm volatile("bar.arrive 5, 128;\nbar.arrive 3, 160;\nbar.arrive 4, 160;" ::: "memory");
                }
                if (step < 2) {
                    if (step) asm volatile("bar.sync 6, 128;" ::: "memory");
                    wait_until(t_start, step ? TN(5, 6000) : (ABL & 1) ? 0 : TN(6, 2000));
                    if (leader) {
                        if (!step && !TN(8, 0) && !(ABL & 1)) await_count(g, (launch + 1) * kPieces, TN(7, 100));
                        TRW(5 + 4 * step);
#pragma unroll 1
                        for (int c = 3 * step; c < 3 * step + 3; c++) {
                            mbar_expect_tx(bar_img + 8 * c, kWChunk);
                            bulk_g2s(s_m + c * kWChunk, (ABL & 1) ? wqkv + c * kWChunk : g->img[launch & 1][0] + c * kWChunk, kWChunk, bar_img + 8 * c);
                        }
                    }
                    if (!step) { if (TN(1, 1)) mbar_wait(bar_img - 8 + 8 * TN(1, 1), 0); wait_until(t_start, TN(2, 0)); continue; }
                }
                if (w.corner && step == 3) { mbar_wait(bar_use + 8, 1); continue; }
                if (i + 1 == w.ntiles) break;
                mbar_wait(bar_use, i & 1);
                if (w.corner && (i & 1)) { u += 8; v -= 8; } else v += 8 - 2 * w.rev;
                i++;
            }
        }
        TRDUMP();
        return;
    }
    const int order = w.rev ? warp ^ 3 : warp;
    if (order > 4) {
#pragma unroll
        for (int r = 0; r < 3; r++)
            asm volatile("st.shared.v4.u32 [%0], {%1, %1, %1, %1};" ::"r"(s_ring + (order - 5) * kRingChunk + (r == 0 ? 84 : r == 1 ? 88 : 204) * 128 + lane * 16), "r"(0) : "memory");
        asm volatile("fence.proxy.async.shared::cta;" ::: "memory");
    }
    wait_until(t_start, TN(0, 500) + order * TN(3, 650));
    asm volatile("setmaxnreg.inc.sync.aligned.u32 %0;" ::"n"(252 - PREGS / 2));
    int tu = w.iu, tv = w.iv + (8 - 2 * w.rev) * wg;
    const int du2 = w.corner ? 8 : 0, dv2 = 16 - 2 * du2 - 4 * w.rev;
    uint32_t o0, o1;
    w.pixel_offsets(tu + r8, tv + 2 * wq, j, o0, o1);
    uint32_t fa[48];
    {
        RawX raw;
        load_raw(raw, x, o0, o1);
        asm volatile("bar.sync %0, 160;" ::"r"(3 + wg) : "memory");
        raw_to_frags(raw, 0, fa);
        pin(fa);
    }
    mbar_wait(bar_ok, 0);
    const uint64_t dA = dsc + wg * (kSlotStride >> 4), dB = dsc + (wg ^ 1) * (kSlotStride >> 4);

    float acc[96];
    uint32_t po[48];
    uint32_t c0, c1;
    asm volatile("" : "=r"(c0), "=r"(c1));
#pragma unroll
    for (int q = 0; q < 48; q++) asm volatile("" : "=r"(po[q]));
#pragma unroll 1
    for (int i = wg; i < w.ntiles; i += 2) {
        const bool first = i == 0, last = i == w.ntiles - 1;

        TRF(8 + 16 * k);
        wg_fence();
        if (!first) turn_wait(wg);
        proj_gemm(acc, fa, dsc, s_m, [&](int s) {
            if (s == 11 && !first) turn_pass(wg);
            const int n = NPRE + __builtin_popcount(QSLOTS & ((1 << s) - 1));
            if (((QSLOTS >> s) & 1) && n < 12) store_one(i >= 2 && !((ABL & 8) && wqkv), out + c0, out + c1, po, n);
            if (s == 3 || s == 7) { mbar_wait(bar_ok + 2 * s + 2, 0); wg_fence(); }
        });
        __syncwarp();
        TRF(9 + 16 * k);
        uint8_t *p0 = out + c0, *p1 = out + c1;
        c0 = o0; c1 = o1;
        w.pixel_offsets(tu + du2 + r8, tv + dv2 + 2 * wq, j, o0, o1);
        if (i + 2 >= w.ntiles || (ABL & 4)) o0 = o1 = 0;
        wg_wait<0>();
        pin(acc);
        TR(11 + 16 * k); TRT(80 + k);
#pragma unroll
        for (int n = NPRE + __builtin_popcount(QSLOTS); n < 12 - __builtin_popcount(ASLOTS) - __builtin_popcount(BSLOTS); n++) store_one(i >= 2, p0, p1, po, n);
        acc_to_frags(acc, fa);
        pin(fa);

        float sA[44], sE[16], sB[44];
        RawX nxt;
        if (!first) turn_wait(wg);
        mbar_wait(bar_a, w.corner ? i >> 1 : 0);
        wg_fence();
#pragma unroll
        for (int s = 0; s < 12; s++) {
            if (s == 0) wgmma_n88<true>(sA, fa[4 * s], fa[4 * s + 1], fa[4 * s + 2], fa[4 * s + 3], desc_at(dA, (s >> 2) * kRingChunk + (s & 3) * 32));
            else wgmma_n88<false>(sA, fa[4 * s], fa[4 * s + 1], fa[4 * s + 2], fa[4 * s + 3], desc_at(dA, (s >> 2) * kRingChunk + (s & 3) * 32));
            if (s == 11) { wg_commit(); if (!first) turn_pass(wg); }
            if ((ASLOTS >> s) & 1) store_one(i >= 2, p0, p1, po, 12 - __builtin_popcount(BSLOTS) - __builtin_popcount(ASLOTS >> s));
        }
#pragma unroll
        for (int s = 12; s < 16; s++)
            if ((ASLOTS >> s) & 1) store_one(i >= 2, p0, p1, po, 12 - __builtin_popcount(BSLOTS) - __builtin_popcount(ASLOTS >> s));
        TRF(12 + 16 * k);
        const int vq = tv + w.cv + 2 * wq;
        const uint4 tabu = lds128(s_tab + offsetof(Table, u) + (window_start(tu + w.cu + r8) - w.origin_u(tu)) * 64 + j * 16);
        const uint4 tabv = lds128(s_tab + offsetof(Table, v) + (window_start(vq) + window_start(vq + 1) - 2 * (tv + w.cv)) * 64 + j * 16);
        const uint4 route = lds128(s_tab + lane * 16);
        if (LDGPOS == 0) load_raw(nxt, x, o0, o1);
        float v0[14], v1[14];
#pragma unroll
        for (int b = 0; b < 14; b++) v0[b] = v1[b] = __int_as_float(0xff800000);
        wg_wait<0>();
        pin(sA);
        gather_outer(sA, tabu.x, tabv.x, v0, v1);
        pin(v0); pin(v1);
        if (!first) turn_wait(wg);
#pragma unroll
        for (int c = 0; c < 3; c++) {
            mbar_wait(bar_b + 8 * c, wg);
            TRF(64 + 4 * k + c);
            wg_fence();
#pragma unroll
            for (int s = 4 * c; s < 4 * c + 4; s++) {
                if (s == 0) wgmma_n88<true>(sB, fa[4 * s], fa[4 * s + 1], fa[4 * s + 2], fa[4 * s + 3], desc_at(dB, c * kRingChunk + (s & 3) * 32));
                else wgmma_n88<false>(sB, fa[4 * s], fa[4 * s + 1], fa[4 * s + 2], fa[4 * s + 3], desc_at(dB, c * kRingChunk + (s & 3) * 32));
                if ((BSLOTS >> s) & 1) store_one(i >= 2, p0, p1, po, 12 - __builtin_popcount(BSLOTS >> s));
            }
        }
        wg_commit();
#pragma unroll
        for (int s = 0; s < 12; s++)
            if (s == 0) wgmma_n32<true>(sE, fa[4 * s], fa[4 * s + 1], fa[4 * s + 2], fa[4 * s + 3], desc_at(dsc, kOffMid + (s >> 2) * kRingChunk + (s & 3) * 32));
            else wgmma_n32<false>(sE, fa[4 * s], fa[4 * s + 1], fa[4 * s + 2], fa[4 * s + 3], desc_at(dsc, kOffMid + (s >> 2) * kRingChunk + (s & 3) * 32));
        wg_commit();
        if (OSPLIT || !last) turn_pass(wg);
        TRF(13 + 16 * k);
        wg_wait<1>();
        pin(sB);
        gather_outer(sB, tabu.w, tabv.y, v0, v1);
        wg_wait<0>();
        pin(sE);
        TRF(14 + 16 * k);
        gather_mid(sE, tabu.w, tabv.z, v0, v1);
        const float m0 = quad_max(tree_max(v0)), m1 = quad_max(tree_max(v1));

        uint32_t y[14], pa[12], pb[12];
        exp_route<0, 14>(v0, v1, m0, m1, route, (j & 1) == 0, y);
        float s0 = tree_sum(v0), s1 = tree_sum(v1);
        asm volatile("" : "+f"(s0), "+f"(s1));
        unfold<0, 0, 6>(y, tabv.w, pa);
        if (OSPLIT || !last) turn_wait(wg + (y[0] >> 31));
        TRF(15 + 16 * k + (y[13] >> 31));
        wg_fence();
        wgmma_sp_n192_tb<true, 0>(acc, pa[0], pa[1], pa[2], pa[3], desc_at(dA, kToV), tabu.y);
        wgmma_sp_n192_tb<false, 1>(acc, pa[4], pa[5], pa[6], pa[7], desc_at(dA, kToV + 4096), tabu.y);
        wgmma_sp_n192_tb<false, 0>(acc, pa[8], pa[9], pa[10], pa[11], desc_at(dA, kToV + 8192), tabu.z);
        wgmma_sp_n192_tb<false, 1>(acc, y[10], y[11], y[12], y[13], desc_at(dsc, kToV + kOffMid), tabu.z);
        wg_commit();
        unfold<8, 0, 6>(y, tabv.w, pb);
        wg_fence();
        wgmma_sp_n192_tb<false, 0>(acc, pb[0], pb[1], pb[2], pb[3], desc_at(dB, kToV), tabu.y);
        wgmma_sp_n192_tb<false, 1>(acc, pb[4], pb[5], pb[6], pb[7], desc_at(dB, kToV + 4096), tabu.y);
        wgmma_sp_n192_tb<false, 0>(acc, pb[8], pb[9], pb[10], pb[11], desc_at(dB, kToV + 8192), tabu.z);
        wg_commit();
        if (!last) turn_pass(wg);
        TRF(16 + 16 * k);
        if (LDGPOS == 3) load_raw(nxt, x, o0, o1);
        wg_wait<1>();
        if (lane == 0) mbar_arrive(bar_use);
        TRF(17 + 16 * k);
        mbar_wait(bar_ok + 24, 0);
        wg_wait<0>();
        if (lane == 0) mbar_arrive(bar_use + 8);
        pin(acc);
        TR(18 + 16 * k);

        acc_to_frags(acc, po);
        pin(po);
        if (!last) turn_wait(wg);
        wg_fence();
        proj_gemm(acc, po, dsc, s_wv, [&](int s) {
            if (s + 1 == OSPLIT && i + 2 == w.ntiles) { turn_pass(wg); turn_wait(wg); }
            if (OSPLIT && GATE < 11 && s == GATE && last) turn_pass(wg);
        });
        if (!last || (OSPLIT && GATE == 11)) turn_pass(wg);
        TRF(19 + 16 * k);
        const uint32_t zero = lds_volatile(s_late);
        const float inv0 = rcp(quad_sum(s0 + __uint_as_float(zero))), inv1 = rcp(quad_sum(s1 + __uint_as_float(zero)));
        raw_to_frags(nxt, zero, fa);
        pin(fa);
#pragma unroll
        for (int q = 0; q < 48; q += 4) keep(wqkv == nullptr, fa[q], fa[q + 1], fa[q + 2], fa[q + 3]);
        keep(wqkv == nullptr, __float_as_uint(inv0), __float_as_uint(inv1), zero, lane);
        TRF(20 + 16 * k);
        tu += du2; tv += dv2;
        wg_wait<0>();
        pin(acc);
        TR(21 + 16 * k);
#pragma unroll
        for (int q = 0; q < 96; q++) acc[q] *= q & 2 ? inv1 : inv0;
        pack_out(acc, po);
        if (OSPLIT && i + 2 == w.ntiles) turn_wait(wg);
#pragma unroll
        for (int n = 0; n < 12; n++) store_one<FENCELAST>(n < NPRE || i + 2 >= w.ntiles, out + c0, out + c1, po, n);
        pin(po);
    }
    TR(7);
    TRG(1);
    TRDUMP();
}

typedef CUresult (*EncodeTiledFn)(CUtensorMap*, CUtensorMapDataType, cuuint32_t, void*, const cuuint64_t*, const cuuint64_t*,
                                  const cuuint32_t*, const cuuint32_t*, CUtensorMapInterleave, CUtensorMapSwizzle,
                                  CUtensorMapL2promotion, CUtensorMapFloatOOBfill);

bool make_maps(EncodeTiledFn fn, Maps* maps, void* x, void* wqkv, void* wo) {
    const cuuint64_t pix2 = 2 * kPixBytes, row = (cuuint64_t)kHW * kPixBytes;
    const cuuint32_t estr[5] = {1, 1, 1, 1, 1};
    bool ok = true;
    for (int tr = 0; tr < 2; tr++)
        for (int b = 0; b < 2; b++) {
            const cuuint64_t su = tr ? 2 * row : pix2, sv = tr ? pix2 : 2 * row;
            const cuuint64_t dims[5] = {2 * kC, 2, 105, 2, 112};
            const cuuint64_t strides[4] = {7 * su, su, row, sv};
            const cuuint32_t box[5] = {64, 2, 7, 1, b ? 2u : 6u};
            ok = ok && fn(&maps->m[2 * tr + b], CU_TENSOR_MAP_DATA_TYPE_BFLOAT16, 5, x, dims, strides, box, estr,
                          CU_TENSOR_MAP_INTERLEAVE_NONE, CU_TENSOR_MAP_SWIZZLE_128B, CU_TENSOR_MAP_L2_PROMOTION_L2_128B,
                          CU_TENSOR_MAP_FLOAT_OOB_FILL_NONE) == CUDA_SUCCESS;
        }
    for (int b = 0; b < 2; b++) {
        const cuuint64_t dims[3] = {16, kC, b ? 36u : 12u}, strides[2] = {(b ? 3u : 1u) * kPixBytes, 32};
        const cuuint32_t box[3] = {16, b ? 16u : 192u, b ? 12u : 3u};
        ok = ok && fn(b ? &maps->wv : &maps->wo, CU_TENSOR_MAP_DATA_TYPE_BFLOAT16, 3, b ? wqkv : wo, dims, strides, box, estr,
                      CU_TENSOR_MAP_INTERLEAVE_NONE, CU_TENSOR_MAP_SWIZZLE_32B, CU_TENSOR_MAP_L2_PROMOTION_L2_128B,
                      CU_TENSOR_MAP_FLOAT_OOB_FILL_NONE) == CUDA_SUCCESS;
    }
    return ok;
}

}

extern "C" void kernel_launch(void* const* d_in, const int* in_sizes, int n_in, void* d_out, int out_size) {
    static EncodeTiledFn encode = nullptr;
    static Scratch* scratch = nullptr;
    static Tables* tables = nullptr;
    if (!encode) {
        cudaGetSymbolAddress((void**)&scratch, g_scratch);
        cudaGetSymbolAddress((void**)&tables, g_tables);
        void* fn = nullptr;
        cudaDriverEntryPointQueryResult st;
        cudaGetDriverEntryPoint("cuTensorMapEncodeTiled", &fn, cudaEnableDefault, &st);
        encode = (EncodeTiledFn)fn;
        cudaFuncSetAttribute(nat_fused_kernel, cudaFuncAttributeMaxDynamicSharedMemorySize, kSmemBytes);
    }
    Maps maps;
    if (!encode || !make_maps(encode, &maps, d_in[0], d_in[1], d_in[2])) return;
    nat_fused_kernel<<<kGrid, kThreads, kSmemBytes>>>((const uint8_t*)d_in[0], (const uint8_t*)d_in[1], (uint8_t*)d_out, scratch, tables, kDescRing, maps);
}
```

```cpp
#include <cuda_runtime.h>
#include <cuda_bf16.h>
#include <cuda.h>
#include <stdint.h>
#include <type_traits>
#include <stdlib.h>
#include <stddef.h>

#define LDGPOS 0
#define INPLACE 1
#define KEEPFA 1
#define ASLOTS 0x3800
#define BSLOTS 0x6
#define QSLOTS 0x78a
#define WUNROLL 2

namespace {

constexpr int kC          = 192;
constexpr int kHW         = 224;
constexpr int kPixBytes   = kC * 2;
constexpr int kSlotBytes  = 84 * 128;
constexpr int kMidBytes   = 28 * 128;
constexpr int kOffMid     = 88 * 128;
constexpr int kSlotStride = 120 * 128;
constexpr int kRingChunk  = 208 * 128;
constexpr int kWChunk     = 192 * 128;
constexpr int kWBytes     = 3 * kWChunk;
constexpr uint32_t kSmemBase = 1024;
constexpr uint32_t s_ring = kSmemBase, s_m = s_ring + 3 * kRingChunk, s_wv = s_m + kWBytes, s_bar = s_wv + kWBytes;
constexpr uint32_t bar_b = s_bar, bar_img = s_bar + 24, bar_redo = s_bar + 56, bar_wop = s_bar + 80, bar_a = s_bar + 88,
                   bar_ok = s_bar + 96, bar_use = s_bar + 128;
constexpr uint32_t s_cnt = s_bar + 144, s_par = s_bar + 160, s_late = s_bar + 164, s_tab = s_bar + 256, s_trace = s_tab + 2048;
constexpr int kSmemBytes  = s_trace + 2048 - kSmemBase;
constexpr int kThreads    = 384, kWUnroll = WUNROLL;
constexpr int kGrid       = 132;
constexpr int kPieces     = 144;
constexpr float kScaleLog2e = 0.07216878364870322f * 1.4426950408889634f;

struct Maps {
    CUtensorMap m[4];
    CUtensorMap wo, wv;
};
#define TN(i, dflt) (dflt)

struct Scratch {
    uint8_t img[2][2][kWBytes];
    uint32_t cnt[4];
};
__device__ __align__(1024) Scratch g_scratch;

struct Table {
    uint32_t route[32][4];
    uint32_t u[8][4][4];
    uint32_t v[16][4][4];
};
struct Tables { Table t[2]; };
constexpr Tables make_tables() {
    Tables r = {};
    for (int rev = 0; rev < 2; rev++)
        for (int j = 0; j < 4; j++) {
            Table& t = r.t[rev];
            for (int q = 0; q < 8; q++) {
                uint32_t* e = t.route[4 * q + j];
                e[0] = 4 * q + 2 * (j & 1) + (j >> 1); e[1] = e[0] ^ 1;
                e[2] = j < 2 ? 0x5410u : 0x1054u; e[3] = e[2] + 0x2222u;
                e = t.u[q][j];
                for (int n = 0; n < 7; n++) e[0] |= ((n + j) % 7 < q ? 1u : 0u) << n;
                e[3] = e[0];
                for (int k = 0; k < 2; k++) {
                    const int step = 2 * k + (j >> 1), p0 = (step < 3 ? 16 * step : 40) + 8 * (j & 1);
                    uint32_t m = 0x8888u;
                    for (int n = 0; n < 8; n++) m |= ((p0 + n) % 7 < q ? 1u : 0u) << (2 * n);
                    e[1 + k] = m * 0x10001u;
                }
            }
            for (int sum = 0; sum < 15; sum++) {
                uint32_t* e = t.v[sum][j];
                for (int row = 0; row < 2; row++)
                    for (int b = 0; b < 14; b++) {
                        const int off = (sum + row) / 2, p = 4 * b + j;
                        const uint32_t bit = 1u << (2 * b + row);
                        if (p < 42 && p >= 7 * off) e[rev] |= bit;
                        if (p < 7 * off - 7) e[1 - rev] |= bit;
                        if (p >= 42 && p >= 7 * off && p < 7 * off + 49) e[2] |= bit;
                    }
                for (int n = 0; n < 6; n++)
                    if (8 * n + 2 * j < 42) e[3] |= 1u << (n + ((8 * n + 2 * j >= 7 * (sum / 2 & ~1)) != rev ? 0 : 8));
            }
        }
    return r;
}
__device__ __align__(128) const Tables g_tables = make_tables();

#define WO4(i) "=f"(d[i]), "=f"(d[i + 1]), "=f"(d[i + 2]), "=f"(d[i + 3])
#define RW4(i) "+f"(d[i]), "+f"(d[i + 1]), "+f"(d[i + 2]), "+f"(d[i + 3])

template <bool FIRST>
__device__ __forceinline__ void wgmma_n192(float (&d)[96], uint32_t a0, uint32_t a1, uint32_t a2, uint32_t a3, uint64_t descb) {
    if constexpr (FIRST) {
        asm volatile(
            "wgmma.mma_async.sync.aligned.m64n192k16.f32.bf16.bf16 "
            "{%0, %1, %2, %3, %4, %5, %6, %7, %8, %9, %10, %11, %12, %13, %14, %15, %16, %17, %18, %19, %20, %21, %22, %23, "
            "%24, %25, %26, %27, %28, %29, %30, %31, %32, %33, %34, %35, %36, %37, %38, %39, %40, %41, %42, %43, %44, %45, %46, %47, "
            "%48, %49, %50, %51, %52, %53, %54, %55, %56, %57, %58, %59, %60, %61, %62, %63, %64, %65, %66, %67, %68, %69, %70, %71, "
            "%72, %73, %74, %75, %76, %77, %78, %79, %80, %81, %82, %83, %84, %85, %86, %87, %88, %89, %90, %91, %92, %93, %94, %95}, "
            "{%96, %97, %98, %99}, %100, 0, 1, 1, 0;"
            : WO4(0), WO4(4), WO4(8), WO4(12), WO4(16), WO4(20), WO4(24), WO4(28), WO4(32), WO4(36), WO4(40), WO4(44),
              WO4(48), WO4(52), WO4(56), WO4(60), WO4(64), WO4(68), WO4(72), WO4(76), WO4(80), WO4(84), WO4(88), WO4(92)
            : "r"(a0), "r"(a1), "r"(a2), "r"(a3), "l"(descb));
    } else {
        asm volatile(
            "wgmma.mma_async.sync.aligned.m64n192k16.f32.bf16.bf16 "
            "{%0, %1, %2, %3, %4, %5, %6, %7, %8, %9, %10, %11, %12, %13, %14, %15, %16, %17, %18, %19, %20, %21, %22, %23, "
            "%24, %25, %26, %27, %28, %29, %30, %31, %32, %33, %34, %35, %36, %37, %38, %39, %40, %41, %42, %43, %44, %45, %46, %47, "
            "%48, %49, %50, %51, %52, %53, %54, %55, %56, %57, %58, %59, %60, %61, %62, %63, %64, %65, %66, %67, %68, %69, %70, %71, "
            "%72, %73, %74, %75, %76, %77, %78, %79, %80, %81, %82, %83, %84, %85, %86, %87, %88, %89, %90, %91, %92, %93, %94, %95}, "
            "{%96, %97, %98, %99}, %100, 1, 1, 1, 0;"
            : RW4(0), RW4(4), RW4(8), RW4(12), RW4(16), RW4(20), RW4(24), RW4(28), RW4(32), RW4(36), RW4(40), RW4(44),
              RW4(48), RW4(52), RW4(56), RW4(60), RW4(64), RW4(68), RW4(72), RW4(76), RW4(80), RW4(84), RW4(88), RW4(92)
            : "r"(a0), "r"(a1), "r"(a2), "r"(a3), "l"(descb));
    }
}

template <bool FIRST>
__device__ __forceinline__ void wgmma_n88(float (&d)[44], uint32_t a0, uint32_t a1, uint32_t a2, uint32_t a3, uint64_t descb) {
    if constexpr (FIRST) {
        asm volatile(
            "wgmma.mma_async.sync.aligned.m64n88k16.f32.bf16.bf16 "
            "{%0, %1, %2, %3, %4, %5, %6, %7, %8, %9, %10, %11, %12, %13, %14, %15, %16, %17, %18, %19, %20, %21, %22, %23, "
            "%24, %25, %26, %27, %28, %29, %30, %31, %32, %33, %34, %35, %36, %37, %38, %39, %40, %41, %42, %43}, "
            "{%44, %45, %46, %47}, %48, 0, 1, 1, 0;"
            : WO4(0), WO4(4), WO4(8), WO4(12), WO4(16), WO4(20), WO4(24), WO4(28), WO4(32), WO4(36), WO4(40)
            : "r"(a0), "r"(a1), "r"(a2), "r"(a3), "l"(descb));
    } else {
        asm volatile(
            "wgmma.mma_async.sync.aligned.m64n88k16.f32.bf16.bf16 "
            "{%0, %1, %2, %3, %4, %5, %6, %7, %8, %9, %10, %11, %12, %13, %14, %15, %16, %17, %18, %19, %20, %21, %22, %23, "
            "%24, %25, %26, %27, %28, %29, %30, %31, %32, %33, %34, %35, %36, %37, %38, %39, %40, %41, %42, %43}, "
            "{%44, %45, %46, %47}, %48, 1, 1, 1, 0;"
            : RW4(0), RW4(4), RW4(8), RW4(12), RW4(16), RW4(20), RW4(24), RW4(28), RW4(32), RW4(36), RW4(40)
            : "r"(a0), "r"(a1), "r"(a2), "r"(a3), "l"(descb));
    }
}

template <bool FIRST>
__device__ __forceinline__ void wgmma_n32(float (&d)[16], uint32_t a0, uint32_t a1, uint32_t a2, uint32_t a3, uint64_t descb) {
    if constexpr (FIRST) {
        asm volatile(
            "wgmma.mma_async.sync.aligned.m64n32k16.f32.bf16.bf16 "
            "{%0, %1, %2, %3, %4, %5, %6, %7, %8, %9, %10, %11, %12, %13, %14, %15}, "
            "{%16, %17, %18, %19}, %20, 0, 1, 1, 0;"
            : WO4(0), WO4(4), WO4(8), WO4(12)
            : "r"(a0), "r"(a1), "r"(a2), "r"(a3), "l"(descb));
    } else {
        asm volatile(
            "wgmma.mma_async.sync.aligned.m64n32k16.f32.bf16.bf16 "
            "{%0, %1, %2, %3, %4, %5, %6, %7, %8, %9, %10, %11, %12, %13, %14, %15}, "
            "{%16, %17, %18, %19}, %20, 1, 1, 1, 0;"
            : RW4(0), RW4(4), RW4(8), RW4(12)
            : "r"(a0), "r"(a1), "r"(a2), "r"(a3), "l"(descb));
    }
}

template <bool FIRST, int SEL>
__device__ __forceinline__ void wgmma_sp_n192_tb(float (&d)[96], uint32_t a0, uint32_t a1, uint32_t a2, uint32_t a3, uint64_t descb, uint32_t meta) {
    if constexpr (FIRST) {
        asm volatile(
            "wgmma.mma_async.sp.sync.aligned.m64n192k32.f32.bf16.bf16 "
            "{%0, %1, %2, %3, %4, %5, %6, %7, %8, %9, %10, %11, %12, %13, %14, %15, %16, %17, %18, %19, %20, %21, %22, %23, "
            "%24, %25, %26, %27, %28, %29, %30, %31, %32, %33, %34, %35, %36, %37, %38, %39, %40, %41, %42, %43, %44, %45, %46, %47, "
            "%48, %49, %50, %51, %52, %53, %54, %55, %56, %57, %58, %59, %60, %61, %62, %63, %64, %65, %66, %67, %68, %69, %70, %71, "
            "%72, %73, %74, %75, %76, %77, %78, %79, %80, %81, %82, %83, %84, %85, %86, %87, %88, %89, %90, %91, %92, %93, %94, %95}, "
            "{%96, %97, %98, %99}, %100, %101, %102, 0, 1, 1, 1;"
            : WO4(0), WO4(4), WO4(8), WO4(12), WO4(16), WO4(20), WO4(24), WO4(28), WO4(32), WO4(36), WO4(40), WO4(44),
              WO4(48), WO4(52), WO4(56), WO4(60), WO4(64), WO4(68), WO4(72), WO4(76), WO4(80), WO4(84), WO4(88), WO4(92)
            : "r"(a0), "r"(a1), "r"(a2), "r"(a3), "l"(descb), "r"(meta), "n"(SEL));
    } else {
        asm volatile(
            "wgmma.mma_async.sp.sync.aligned.m64n192k32.f32.bf16.bf16 "
            "{%0, %1, %2, %3, %4, %5, %6, %7, %8, %9, %10, %11, %12, %13, %14, %15, %16, %17, %18, %19, %20, %21, %22, %23, "
            "%24, %25, %26, %27, %28, %29, %30, %31, %32, %33, %34, %35, %36, %37, %38, %39, %40, %41, %42, %43, %44, %45, %46, %47, "
            "%48, %49, %50, %51, %52, %53, %54, %55, %56, %57, %58, %59, %60, %61, %62, %63, %64, %65, %66, %67, %68, %69, %70, %71, "
            "%72, %73, %74, %75, %76, %77, %78, %79, %80, %81, %82, %83, %84, %85, %86, %87, %88, %89, %90, %91, %92, %93, %94, %95}, "
            "{%96, %97, %98, %99}, %100, %101, %102, 1, 1, 1, 1;"
            : RW4(0), RW4(4), RW4(8), RW4(12), RW4(16), RW4(20), RW4(24), RW4(28), RW4(32), RW4(36), RW4(40), RW4(44),
              RW4(48), RW4(52), RW4(56), RW4(60), RW4(64), RW4(68), RW4(72), RW4(76), RW4(80), RW4(84), RW4(88), RW4(92)
            : "r"(a0), "r"(a1), "r"(a2), "r"(a3), "l"(descb), "r"(meta), "n"(SEL));
    }
}

#define TR(slot)
#define TRT(slot)
#define TRF(slot)
#define TRW(slot)
#define TRG(slot)
#define TRDUMP()

__device__ __forceinline__ void wg_fence() { asm volatile("wgmma.fence.sync.aligned;" ::: "memory"); }
__device__ __forceinline__ void wg_commit() { asm volatile("wgmma.commit_group.sync.aligned;" ::: "memory"); }
template <int N>
__device__ __forceinline__ void wg_wait() { asm volatile("wgmma.wait_group.sync.aligned %0;" ::"n"(N) : "memory"); }

template <int N>
__device__ __forceinline__ void pin(float (&d)[N]) {
#pragma unroll
    for (int i = 0; i < N; i++) asm volatile("" : "+f"(d[i])::"memory");
}
template <int N>
__device__ __forceinline__ void pin(uint32_t (&d)[N]) {
#pragma unroll
    for (int i = 0; i < N; i++) asm volatile("" : "+r"(d[i])::"memory");
}

constexpr uint64_t kDescRing = ((uint64_t)((1u << 30) | (1024u >> 4)) << 32) | (1u << 16) | (s_ring >> 4);
constexpr uint32_t kToV = ((kRingChunk >> 4) - 1) << 20;
__device__ __forceinline__ uint64_t desc_at(uint64_t base, uint32_t byte_off) {
    uint64_t d;
    asm volatile("add.s64 %0, %1, %2;" : "=l"(d) : "l"(base), "l"((uint64_t)(byte_off >> 4)));
    return d;
}

__device__ __forceinline__ void mbar_init(uint32_t bar, uint32_t count) {
    asm volatile("mbarrier.init.shared::cta.b64 [%0], %1;" ::"r"(bar), "r"(count) : "memory");
}
__device__ __forceinline__ void mbar_expect_tx(uint32_t bar, uint32_t bytes) {
    asm volatile("mbarrier.arrive.expect_tx.shared::cta.b64 _, [%0], %1;" ::"r"(bar), "r"(bytes) : "memory");
}
__device__ __forceinline__ void expect_tx_only(uint32_t bar, uint32_t bytes) {
    asm volatile("mbarrier.expect_tx.relaxed.cta.shared::cta.b64 [%0], %1;" ::"r"(bar), "r"(bytes) : "memory");
}
__device__ __forceinline__ void mbar_arrive(uint32_t bar) {
    asm volatile("mbarrier.arrive.shared::cta.b64 _, [%0];" ::"r"(bar) : "memory");
}
__device__ __forceinline__ void mbar_wait(uint32_t bar, uint32_t parity) {
    asm volatile(
        "{\n.reg .pred p;\n"
        "W: mbarrier.try_wait.parity.shared::cta.b64 p, [%0], %1;\n"
        "@!p bra W;\n}\n"
        ::"r"(bar), "r"(parity) : "memory");
}
__device__ __forceinline__ uint32_t clock_now() {
    uint32_t c;
    asm volatile("mov.u32 %0, %%clock;" : "=r"(c)::"memory");
    return c;
}
__device__ __forceinline__ void wait_until(uint32_t t0, int t) {
    if (t == 0) return;
    while ((int)(clock_now() - t0) < t) {}
}
__device__ __forceinline__ bool elect() {
    uint32_t ok;
    asm volatile("{\n.reg .pred p;\nelect.sync _|p, 0xffffffff;\nselp.u32 %0, 1, 0, p;\n}\n" : "=r"(ok));
    return ok != 0;
}
__device__ __forceinline__ void turn_wait(int wg) { asm volatile("bar.sync %0, 256;" ::"r"(1 + wg) : "memory"); }
__device__ __forceinline__ void turn_pass(int wg) { asm volatile("bar.arrive %0, 256;" ::"r"(2 - wg) : "memory"); }

__device__ __forceinline__ void tma_box(uint32_t dst, const CUtensorMap* map, uint32_t bar, int c0, int c2, int c3, int c4) {
    asm volatile(
        "cp.async.bulk.tensor.5d.shared::cluster.global.mbarrier::complete_tx::bytes [%0], [%1, {%3, %4, %5, %6, %7}], [%2];"
        ::"r"(dst), "l"(map), "r"(bar), "r"(c0), "r"(0), "r"(c2), "r"(c3), "r"(c4)
        : "memory");
}
__device__ __forceinline__ void tma_3d(uint32_t dst, const CUtensorMap* map, uint32_t bar, int c1, int c2) {
    asm volatile("cp.async.bulk.tensor.3d.shared::cluster.global.mbarrier::complete_tx::bytes [%0], [%1, {%3, %4, %5}], [%2];"
                 ::"r"(dst), "l"(map), "r"(bar), "r"(0), "r"(c1), "r"(c2)
                 : "memory");
}
__device__ __forceinline__ void prefetch_map(const CUtensorMap* map) {
    asm volatile("prefetch.tensormap [%0];" ::"l"(map) : "memory");
}
__device__ __forceinline__ uint4 ldg(const void* p) {
    uint4 v;
    asm volatile("ld.global.v4.u32 {%0, %1, %2, %3}, [%4];" : "=r"(v.x), "=r"(v.y), "=r"(v.z), "=r"(v.w) : "l"(p) : "memory");
    return v;
}
__device__ __forceinline__ uint32_t pack_bf16(float lo, float hi) {
    uint32_t r;
    asm("cvt.rn.bf16x2.f32 %0, %1, %2;" : "=r"(r) : "f"(hi), "f"(lo));
    return r;
}
__device__ __forceinline__ float ex2(float x) {
    float y;
    asm("ex2.approx.ftz.f32 %0, %1;" : "=f"(y) : "f"(x));
    return y;
}
__device__ __forceinline__ float rcp(float x) {
    float y;
    asm("rcp.approx.ftz.f32 %0, %1;" : "=f"(y) : "f"(x));
    return y;
}
__device__ __forceinline__ void mma16816(float (&d)[4], uint32_t a0, uint32_t a1, uint32_t a2, uint32_t a3, uint32_t b0, uint32_t b1) {
    asm volatile("mma.sync.aligned.m16n8k16.row.col.f32.bf16.bf16.f32 {%0, %1, %2, %3}, {%4, %5, %6, %7}, {%8, %9}, {%0, %1, %2, %3};"
                 : "+f"(d[0]), "+f"(d[1]), "+f"(d[2]), "+f"(d[3])
                 : "r"(a0), "r"(a1), "r"(a2), "r"(a3), "r"(b0), "r"(b1));
}
__device__ __forceinline__ uint4 lds128(uint32_t addr) {
    uint4 v;
    asm volatile("ld.volatile.shared.v4.u32 {%0, %1, %2, %3}, [%4];" : "=r"(v.x), "=r"(v.y), "=r"(v.z), "=r"(v.w) : "r"(addr) : "memory");
    return v;
}
__device__ __forceinline__ uint32_t lds_volatile(uint32_t addr) {
    uint32_t v;
    asm volatile("ld.volatile.shared.u32 %0, [%1];" : "=r"(v) : "r"(addr) : "memory");
    return v;
}

__device__ __forceinline__ int window_start(int n) { return min(max(n, 0), 105); }
__device__ __forceinline__ int origin_u(int u) { return min(max(u, 0), 98); }

struct Work {
    int u, v;
    int step;
    uint32_t su, sv;
    uint32_t base;
    bool corner;
    int ntiles;
    __device__ __forceinline__ void pixel_offsets(int qu, int qv, int j, uint32_t& o0, uint32_t& o1) const {
        const uint32_t b = (qu + window_start(qu)) * su + j * 16 + base;
        o0 = b + (qv + window_start(qv)) * sv;
        o1 = b + (qv + 1 + window_start(qv + 1)) * sv;
    }
};

__device__ __forceinline__ Work decode_work(int c) {
    Work w;
    const bool transposed = (c >> 4) == 7;
    const int px = 6 * (c & 1), py = 3 * (c & 2);
    w.corner = c >= 128;
    w.step = 8 - 4 * (c & 4);
    w.u = (c < 112 ? c & ~7 : 96 + (c & 8)) + (transposed ? py : px) - 6;
    w.v = (w.corner ? 96 : 48 - 2 * (c & 4)) + (transposed ? px : py) - 6;
    w.su = transposed ? kHW * kPixBytes : kPixBytes;
    w.sv = transposed ? kPixBytes : kHW * kPixBytes;
    w.base = px * (kPixBytes / 6) + py * (kHW * kPixBytes / 6) + 6 * (kHW + 1) * kPixBytes;
    w.ntiles = w.corner ? 4 : 6;
    return w;
}

struct RawX { uint4 a[6], b[6]; };
__device__ __forceinline__ void load_raw(RawX& r, const uint8_t* base, uint32_t o0, uint32_t o1) {
    __syncwarp();
#pragma unroll
    for (int c = 0; c < 6; c++) { r.a[c] = ldg(base + o0 + c * 64); r.b[c] = ldg(base + o1 + c * 64); }
    __syncwarp();
}
__device__ __forceinline__ void raw_to_frags(const RawX& r, uint32_t zero, uint32_t (&f)[48]) {
#pragma unroll
    for (int c = 0; c < 6; c++) {
        f[8 * c + 0] = r.a[c].x; f[8 * c + 2] = r.a[c].z; f[8 * c + 4] = r.a[c].y ^ zero; f[8 * c + 6] = r.a[c].w ^ zero;
        f[8 * c + 1] = r.b[c].x ^ zero; f[8 * c + 3] = r.b[c].z ^ zero; f[8 * c + 5] = r.b[c].y ^ zero; f[8 * c + 7] = r.b[c].w ^ zero;
    }
}
__device__ __forceinline__ void acc_to_frags(const float (&d)[96], uint32_t (&f)[48]) {
#pragma unroll
    for (int i = 0; i < 48; i++) f[i] = pack_bf16(d[2 * i], d[2 * i + 1]);
}

template <class F>
__device__ __forceinline__ void proj_gemm(float (&d)[96], const uint32_t (&a)[48], uint64_t dsc, uint32_t img, F after) {
#pragma unroll
    for (int s = 0; s < 12; s++) {
        if (s == 0) wgmma_n192<true>(d, a[4 * s], a[4 * s + 1], a[4 * s + 2], a[4 * s + 3], desc_at(dsc, img - s_ring + (s >> 2) * kWChunk + (s & 3) * 32));
        else wgmma_n192<false>(d, a[4 * s], a[4 * s + 1], a[4 * s + 2], a[4 * s + 3], desc_at(dsc, img - s_ring + (s >> 2) * kWChunk + (s & 3) * 32));
        if (s == 11) wg_commit();
        after(s);
    }
}
__device__ __forceinline__ void pack_out(const float (&acc)[96], uint32_t (&po)[48]) {
#pragma unroll
    for (int g = 0; g < 6; g++)
#pragma unroll
        for (int q = 0; q < 4; q++) {
            po[8 * g + q] = pack_bf16(acc[16 * g + 4 * q], acc[16 * g + 4 * q + 1]);
            po[8 * g + 4 + q] = pack_bf16(acc[16 * g + 4 * q + 2], acc[16 * g + 4 * q + 3]);
        }
}
template <bool PINNED = true>
__device__ __forceinline__ void store_one(bool on, uint8_t* p0, uint8_t* p1, const uint32_t (&po)[48], int n) {
    if (PINNED) __syncwarp();
    asm volatile("{\n.reg .pred p;\nsetp.ne.u32 p, %5, 0;\n@p st.global.v4.u32 [%0], {%1, %2, %3, %4};\n}\n"
                 ::"l"(((n & 1) ? p1 : p0) + (n >> 1) * 64), "r"(po[4 * n]), "r"(po[4 * n + 1]), "r"(po[4 * n + 2]), "r"(po[4 * n + 3]), "r"((uint32_t)on) : "memory");
}

template <int N>
__device__ __forceinline__ float tree_max(const float (&v)[N]) {
    float t[N];
#pragma unroll
    for (int i = 0; i < N; i++) t[i] = v[i];
#pragma unroll
    for (int w = 1; w < N; w *= 2)
#pragma unroll
        for (int i = 0; i + w < N; i += 2 * w) t[i] = fmaxf(t[i], t[i + w]);
    return t[0];
}
template <int N>
__device__ __forceinline__ float tree_sum(const float (&v)[N]) {
    float t[N];
#pragma unroll
    for (int i = 0; i < N; i++) t[i] = v[i];
#pragma unroll
    for (int w = 1; w < N; w *= 2)
#pragma unroll
        for (int i = 0; i + w < N; i += 2 * w) t[i] += t[i + w];
    return t[0];
}

template <int B>
__device__ __forceinline__ void pick(uint32_t h, uint32_t ok, const float* s, float& v0, float& v1) {
    asm("{\n.reg .pred p, q0, q1;\n.reg .b32 t;\nand.b32 t, %6, %7;\nsetp.ne.u32 p, t, 0;\n"
        "and.b32 t, %8, %9;\nsetp.ne.u32 q0, t, 0;\nand.b32 t, %8, %10;\nsetp.ne.u32 q1, t, 0;\n"
        "@q0 selp.f32 %0, %3, %2, p;\n@q1 selp.f32 %1, %5, %4, p;\n}\n"
        : "+f"(v0), "+f"(v1)
        : "f"(s[0]), "f"(s[1]), "f"(s[2]), "f"(s[3]), "r"(h), "n"(1 << ((4 * B) % 7)), "r"(ok), "n"(1 << (2 * B)), "n"(2 << (2 * B)));
}
template <int B, class F>
__device__ __forceinline__ void for_blocks(F f) {
    if constexpr (B > 0) { for_blocks<B - 1>(f); f(std::integral_constant<int, B - 1>{}); }
}
__device__ __forceinline__ void gather_outer(const float (&s)[44], uint32_t h, uint32_t ok, float (&v0)[14], float (&v1)[14]) {
    for_blocks<11>([&](auto B) {
        constexpr int b = B.value < 8 ? (B.value >> 1) + 7 * (B.value & 1) : B.value - 4;
        pick<b>(h, ok, &s[4 * b], v0[b], v1[b]);
    });
}
__device__ __forceinline__ void gather_mid(const float (&sE)[16], uint32_t h, uint32_t ok, float (&v0)[14], float (&v1)[14]) {
    for_blocks<4>([&](auto B) { pick<10 + B.value>(h, ok, &sE[4 * B.value], v0[10 + B.value], v1[10 + B.value]); });
}
__device__ __forceinline__ float quad_max(float m) {
    m = fmaxf(m, __shfl_xor_sync(0xffffffffu, m, 1));
    return fmaxf(m, __shfl_xor_sync(0xffffffffu, m, 2));
}
__device__ __forceinline__ float quad_sum(float s) {
    s += __shfl_xor_sync(0xffffffffu, s, 1);
    return s + __shfl_xor_sync(0xffffffffu, s, 2);
}
template <int B0, int B1>
__device__ __forceinline__ void exp_route(float (&v0)[14], float (&v1)[14], float m0, float m1, const uint4& r, bool even, uint32_t (&y)[14]) {
#pragma unroll
    for (int b = B0; b < B1; b++) { v0[b] = ex2(v0[b] - m0); v1[b] = ex2(v1[b] - m1); }
#pragma unroll
    for (int b = B0; b < B1; b += 2) {
        const uint32_t x0 = pack_bf16(v0[b], v1[b]), x1 = pack_bf16(v0[b + 1], v1[b + 1]);
        const uint32_t u = __shfl_sync(0xffffffffu, even ? x0 : x1, r.x);
        const uint32_t w = __shfl_sync(0xffffffffu, even ? x1 : x0, r.y);
        y[b] = __byte_perm(u, w, r.z); y[b + 1] = __byte_perm(u, w, r.w);
    }
}
template <int BIT0, int N0, int N1>
__device__ __forceinline__ void unfold(const uint32_t (&y)[14], uint32_t fold, uint32_t (&p)[12]) {
    for_blocks<N1 - N0>([&](auto N) {
        constexpr int n = N0 + N.value;
        asm("{\n.reg .pred p;\n.reg .b32 t;\nand.b32 t, %4, %5;\nsetp.ne.u32 p, t, 0;\nselp.b32 %0, %2, 0, p;\nselp.b32 %1, %3, 0, p;\n}\n"
            : "=r"(p[2 * n]), "=r"(p[2 * n + 1]) : "r"(y[2 * n]), "r"(y[2 * n + 1]), "r"(fold), "n"(1 << (BIT0 + n)));
    });
}
__device__ __forceinline__ void keep(bool never, uint32_t a, uint32_t b, uint32_t c, uint32_t d) {
    asm volatile("{\n.reg .pred p;\nsetp.ne.u32 p, %4, 0;\n@p st.volatile.shared.v4.u32 [%5], {%0, %1, %2, %3};\n}\n"
                 ::"r"(a), "r"(b), "r"(c), "r"(d), "r"((uint32_t)never), "r"(s_trace) : "memory");
}

__device__ __forceinline__ uint32_t wimg_offset(uint32_t row, uint32_t s, uint32_t j) {
    return (s >> 2) * kWChunk + row * 128 + (((2 * (s & 3) + (j >> 1)) ^ (row & 7)) << 4) + (j & 1) * 8;
}

__device__ __forceinline__ void ldsm4(uint32_t (&r)[4], uint32_t addr) {
    asm volatile("ldmatrix.sync.aligned.m8n8.x4.shared.b16 {%0, %1, %2, %3}, [%4];" : "=r"(r[0]), "=r"(r[1]), "=r"(r[2]), "=r"(r[3]) : "r"(addr) : "memory");
}
__device__ __forceinline__ void ldsm4_t(uint32_t (&r)[4], uint32_t addr) {
    asm volatile("ldmatrix.sync.aligned.m8n8.x4.trans.shared.b16 {%0, %1, %2, %3}, [%4];" : "=r"(r[0]), "=r"(r[1]), "=r"(r[2]), "=r"(r[3]) : "r"(addr) : "memory");
}
__device__ __forceinline__ void m_partial(const uint8_t* wqkv, uint32_t mt, uint32_t s, uint32_t q, uint32_t lane, uint32_t zero) {
    const uint32_t r8 = lane >> 2, col = q * 128 + (lane & 3) * 16;
    const uint8_t* pa = wqkv + (16 * mt + r8) * 1152 + col;
    const uint8_t* pb = wqkv + (16 * s + 8 * (r8 & 2) + (r8 & 5)) * 1152 + col;
    uint4 A[2][2], B[4][2];
#pragma unroll
    for (int c = 0; c < 2; c++) {
#pragma unroll
        for (int h = 0; h < 2; h++) A[h][c] = ldg(pa + 384 + h * 8 * 1152 + c * 64);
#pragma unroll
        for (int n = 0; n < 4; n++) B[n][c] = ldg(pb + ((n & 1) * 8 + (n & 2)) * 1152 + c * 64);
    }
#pragma unroll
    for (int i = 0; i < 4; i++) { uint4& a = A[i >> 1][i & 1]; a.x ^= zero; a.y ^= zero; a.z ^= zero; a.w ^= zero; }
#pragma unroll
    for (int n = 0; n < 4; n++) {
        float d[4] = {0.f, 0.f, 0.f, 0.f};
#pragma unroll
        for (int c = 0; c < 2; c++) {
            mma16816(d, A[0][c].x, A[1][c].x, A[0][c].y, A[1][c].y, B[n][c].x, B[n][c].y);
            mma16816(d, A[0][c].z, A[1][c].z, A[0][c].w, A[1][c].w, B[n][c].z, B[n][c].w);
        }
        asm volatile("st.shared.v4.f32 [%0], {%1, %2, %3, %4};" ::"r"(s_wv + q * 2048 + n * 512 + lane * 16), "f"(d[0]), "f"(d[1]), "f"(d[2]), "f"(d[3]) : "memory");
    }
}
__device__ __forceinline__ void m_reduce(uint32_t e, uint32_t lane, float (&d)[2][4]) {
#pragma unroll
    for (int n = 0; n < 2; n++) {
        float t[3][4];
#pragma unroll
        for (int q = 0; q < 3; q++)
            asm volatile("ld.shared.v4.f32 {%0, %1, %2, %3}, [%4];" : "=f"(t[q][0]), "=f"(t[q][1]), "=f"(t[q][2]), "=f"(t[q][3]) : "r"(s_wv + q * 2048 + e * 1024 + n * 512 + lane * 16) : "memory");
#pragma unroll
        for (int i = 0; i < 4; i++) d[n][i] = (t[0][i] + t[1][i] + t[2][i]) * kScaleLog2e;
    }
}
__device__ __forceinline__ void w_piece(uint32_t q, uint32_t lane, float (&d)[2][4]) {
    const uint32_t rr = lane & 7, mi = lane >> 3, kr = 4 * (rr >> 1) + (mi & 2) + (rr & 1);
    const uint32_t pa = s_wv + q * 6144 + (4 * (mi & 2) + rr) * 32 + (((mi ^ (rr >> 2)) & 1) << 4);
    const uint32_t pb = s_wv + 3 * 6144 + kr * 32 + (((mi ^ (kr >> 2)) & 1) << 4);
#pragma unroll
    for (int i = 0; i < 8; i++) (&d[0][0])[i] = 0.f;
#pragma unroll kWUnroll
    for (int k = 0; k < 12; k++) {
        uint32_t aq[4], bq[4];
        ldsm4_t(aq, pa + k * 512);
        ldsm4(bq, pb + k * 512);
        mma16816(d[0], aq[0], aq[1], aq[2], aq[3], bq[0], bq[1]);
        mma16816(d[1], aq[0], aq[1], aq[2], aq[3], bq[2], bq[3]);
    }
}
__device__ __forceinline__ uint32_t piece_offset(uint32_t which, uint32_t s, uint32_t mt, uint32_t lane) {
    const uint32_t r8 = lane >> 2;
    return which * kWBytes + wimg_offset(which ? 32 * (mt >> 1) + 8 * (r8 >> 1) + 4 * (mt & 1) + (r8 & 1) : 16 * mt + r8, s, lane & 3);
}
__device__ __forceinline__ void piece_store(Scratch* g, uint32_t par, uint32_t off0, uint32_t which, const float (&d)[2][4]) {
#pragma unroll
    for (int hf = 0; hf < 2; hf++) {
        const uint32_t off = off0 ^ (hf ? which ? 288 : 1024 : 0);
        const uint32_t a = pack_bf16(d[0][2 * hf], d[0][2 * hf + 1]), b = pack_bf16(d[1][2 * hf], d[1][2 * hf + 1]);
        asm volatile("st.relaxed.gpu.global.v2.u32 [%0], {%1, %2};" ::"l"(g->img[0][0] + (par + off)), "r"(a ? a : 0x8000u), "r"(b) : "memory");
        asm volatile("st.relaxed.gpu.global.v2.u32 [%0], {%1, %1};" ::"l"(g->img[1][0] + (int)(off - par)), "r"(0) : "memory");
    }
}

__device__ __forceinline__ uint32_t ld_relaxed(const uint32_t* p) {
    uint32_t v;
    asm volatile("ld.relaxed.gpu.global.u32 %0, [%1];" : "=r"(v) : "l"(p) : "memory");
    return v;
}
__device__ __forceinline__ void count_up(uint32_t* p) {
    asm volatile("red.relaxed.gpu.global.add.u32 [%0], %1;" ::"l"(p), "r"(1) : "memory");
}
__device__ __forceinline__ void bulk_g2s(uint32_t dst, const void* src, uint32_t bytes, uint32_t bar) {
    asm volatile("cp.async.bulk.shared::cluster.global.mbarrier::complete_tx::bytes [%0], [%1], %2, [%3];"
                 ::"r"(dst), "l"(src), "r"(bytes), "r"(bar)
                 : "memory");
}

__global__ void __launch_bounds__(kThreads, 1)
nat_fused_kernel(const uint8_t* __restrict__ x, const uint8_t* __restrict__ wqkv, uint8_t* __restrict__ out, Scratch* g,
                 const Tables* tables, uint64_t dsc, const __grid_constant__ Maps maps) {
    const int tid = threadIdx.x, lane = tid & 31;
    const int warp = __shfl_sync(0xffffffffu, tid >> 5, 0);
    const int wg = warp >> 2, wq = warp & 3, r8 = lane >> 2, j = lane & 3;
    const int cta = blockIdx.x;
    const Work w = decode_work(cta);
    const uint32_t which = cta >= 72, job = which ? cta - 72 : 2 * cta, jhi = job / 12, jlo = job % 12;
    if (wg == 1 && wq < 3) {
#pragma unroll
        for (int r = 0; r < 3; r++)
            asm volatile("st.shared.v4.u32 [%0], {%1, %1, %1, %1};" ::"r"(s_ring + wq * kRingChunk + (r == 0 ? 84 : r == 1 ? 88 : 204) * 128 + lane * 16), "r"(0) : "memory");
        asm volatile("fence.proxy.async.shared::cta;" ::: "memory");
    }
    if (x == nullptr) return;
    const uint32_t t_start = clock_now();
    if (wg == 2) {
        if (wq < 3 && !which) m_partial(wqkv, jhi, jlo, wq, lane, (uint32_t)dsc & 1);
        asm volatile("setmaxnreg.dec.sync.aligned.u32 40;");
        if (wq < 3) {
            const uint32_t off = piece_offset(which, which ? jlo : jlo + wq, which ? 3 * jhi + wq : jhi, lane);
            asm volatile("bar.sync %0, 128;" ::"r"(5 + (off >> 31)) : "memory");
            const uint32_t par = lds_volatile(s_par);
            if (cta < 120 && wq < 2 + which) {
                float d[2][4];
                if (wq == 0) TRW(which ? 1 : 18);
                if (which) {
                    mbar_wait(bar_wop, 0);
                    if (wq == 0) TRW(2);
                    w_piece(wq, lane, d);
                } else {
                    m_reduce(wq, lane, d);
                }
                piece_store(g, par, off, which, d);
                __syncwarp();
                if (!which && lane == 0) count_up(&g->cnt[0]);
                if (wq == 0) TRW(which ? 3 : 0);
            }
            asm volatile("bar.arrive 6, 128;" ::: "memory");
            uint32_t phase = 0;
#pragma unroll 1
            for (uint32_t c = 0; c < 6; c++) {
                const uint32_t part = c * kWChunk + wq * (kWChunk / 3), img = 8 * min(c, 3u);
                mbar_wait(bar_img + img, 0);
                if (wq == 0) TRW(10 + c);
#pragma unroll 1
                while (true) {
                    uint32_t lo = ~0u;
#pragma unroll
                    for (int q = 0; q < 8; q++) lo = min(lo, lds_volatile(s_m + part + lane * 32 + (lane & 12) * 2 + q * 1024));
                    if (__all_sync(0xffffffffu, lo) || phase > 65535) break;
                    if (elect()) {
                        mbar_expect_tx(bar_redo + 8 * wq, kWChunk / 3);
                        bulk_g2s(s_m + part, g->img[0][0] + par + part, kWChunk / 3, bar_redo + 8 * wq);
                    }
                    mbar_wait(bar_redo + 8 * wq, phase++ & 1);
                }
                if (c != 3 && c != 4 && lane == 0) mbar_arrive(bar_ok + img);
            }
        } else {
            uint32_t launch = ld_relaxed(&g->cnt[1]);
            const CUtensorMap* map = &maps.m[w.sv == kPixBytes ? 2 : 0];
            if (elect()) {
#pragma unroll
                for (int i = 0; i < 18; i++) mbar_init(s_bar + 8 * i, i < 11 ? 1 : i < 16 ? 3 : 4);
                asm volatile("fence.mbarrier_init.release.cluster;" ::: "memory");
                prefetch_map(map + 1);
                expect_tx_only(bar_a, sizeof(Table));
                bulk_g2s(s_tab, &tables->t[w.step < 0], sizeof(Table), bar_a);
            }
            if (which && cta < 120 && elect()) {
                mbar_expect_tx(bar_wop, 4 * 6144);
                tma_3d(s_wv, &maps.wo, bar_wop, 0, 3 * jhi);
                tma_3d(s_wv + 3 * 6144, &maps.wv, bar_wop, 16 * jlo, 24);
            }
            int u = w.u, v = w.v;
            uint32_t wait_bar = bar_use, wait_par = 1, slot = 0;
#pragma unroll 1
            for (int step = 0; step < 7 - w.corner; step++) {
                const bool first = step == 0 || (w.corner && step == 4);
                const int row = v + 4 + (first ? -w.step : w.step) / 2, ou = origin_u(u);
                uint32_t dst = s_ring + (first ? 0 : slot), mid = s_ring + kOffMid + 512, bar = first ? bar_a : bar_b;
                mbar_wait(wait_bar, wait_par);
#pragma unroll 1
                for (int ch = (cta & 1) * kC; mid < s_m; ch += 64, dst += kRingChunk, mid += kRingChunk) {
                    if (elect()) {
                        mbar_expect_tx(bar, first ? kSlotBytes : kSlotBytes + kMidBytes);
                        tma_box(dst, map, bar, ch, ou, (cta >> 1) & 1, row);
                    }
                    if (!first) {
                        if (elect()) tma_box(mid, map + 1, bar, ch, ou, (cta >> 1) & 1, v + 6);
                        bar += 8;
                    }
                }
                if (step == 0) {
                    launch /= kGrid;
                    asm volatile("st.shared.u32 [%0], %2;\nst.shared.v2.u32 [%0 + 16], {%1, %2};" ::"r"(s_cnt), "r"((launch & 1) * 2 * kWBytes), "r"(0) : "memory");
                    if (lane == 0) count_up(&g->cnt[1]);
                    asm volatile("bar.arrive 5, 128;\nbar.arrive 3, 160;\nbar.arrive 4, 160;" ::: "memory");
#pragma unroll 1
                    for (int t = TN(6, 2000); t < (1 << 24); t += TN(7, 200)) {
                        wait_until(t_start, t);
                        if (__shfl_sync(0xffffffffu, lds_volatile(s_cnt), 0) >= (launch + 1) * kPieces) break;
                        if (elect()) {
                            expect_tx_only(bar_use + 8, 16);
                            bulk_g2s(s_cnt, g->cnt, 16, bar_use + 8);
                        }
                    }
                }
                if (step == 1) {
                    asm volatile("bar.sync 6, 128;" ::: "memory");
                    wait_until(t_start, TN(5, 6000));
                }
                if (step < 2) {
                    TRW(5 + 4 * step);
                    const uint32_t bytes = step ? kWBytes : kWChunk;
#pragma unroll 1
                    for (int c = 3 * step; c < 3 + step; c++)
                        if (elect()) {
                            mbar_expect_tx(bar_img + 8 * c, bytes);
                            bulk_g2s(s_m + c * kWChunk, g->img[launch & 1][0] + c * kWChunk, bytes, bar_img + 8 * c);
                        }
                }
                const bool again = w.corner && step == 3;
                wait_bar = step == 0 ? bar_img : again ? bar_use + 8 : bar_use;
                if (!again) {
                    wait_par = slot ? 0 : step != 0;
                    slot ^= kSlotStride;
                    if (w.corner && step == 2) { u += 8; v -= 8; } else if (step) v += w.step;
                }
            }
        }
        TRDUMP();
        return;
    }
    const int order = w.step < 0 ? warp ^ 3 : warp;
    wait_until(t_start, TN(0, 500) + order * TN(3, 650));
    asm volatile("setmaxnreg.inc.sync.aligned.u32 232;");
    int tu = w.u, tv = w.v + w.step * wg;
    const int du2 = w.corner ? 8 : 0, dv2 = w.corner ? 0 : 2 * w.step;
    uint32_t o0, o1;
    w.pixel_offsets(tu + r8, tv + 2 * wq, j, o0, o1);
    uint32_t fa[48];
    {
        RawX raw;
        load_raw(raw, x, o0, o1);
        asm volatile("bar.sync %0, 160;" ::"r"(3 + wg) : "memory");
        raw_to_frags(raw, 0, fa);
        pin(fa);
    }
    mbar_wait(bar_ok, 0);
    const uint64_t dA = dsc + wg * (kSlotStride >> 4), dB = dsc + (wg ^ 1) * (kSlotStride >> 4);

    float acc[96];
    uint32_t po[48];
    uint32_t c0, c1;
    asm volatile("" : "=r"(c0), "=r"(c1));
#pragma unroll
    for (int q = 0; q < 48; q++) asm volatile("" : "=r"(po[q]));
#pragma unroll 1
    for (int i = wg; i < w.ntiles; i += 2) {
        const bool first = i == 0, last = i == w.ntiles - 1;

        TRF(8 + 16 * k);
        wg_fence();
        if (!first) turn_wait(wg);
        proj_gemm(acc, fa, dsc, s_m, [&](int s) {
            if (s == 11 && !first) turn_pass(wg);
            const int n = __builtin_popcount(QSLOTS & ((1 << s) - 1));
            if (((QSLOTS >> s) & 1) && n < 12) store_one(i >= 2, out + c0, out + c1, po, n);
            if (s == 3 || s == 7) { mbar_wait(bar_ok + 2 * s + 2, 0); wg_fence(); }
        });
        __syncwarp();
        TRF(9 + 16 * k);
        uint8_t *p0 = out + c0, *p1 = out + c1;
        c0 = o0; c1 = o1;
        w.pixel_offsets(tu + du2 + r8, tv + dv2 + 2 * wq, j, o0, o1);
        if (i + 2 >= w.ntiles) o0 = o1 = 0;
        wg_wait<0>();
        pin(acc);
        TR(11 + 16 * k); TRT(80 + k);
#pragma unroll
        for (int n = __builtin_popcount(QSLOTS); n < 12 - __builtin_popcount(ASLOTS) - __builtin_popcount(BSLOTS); n++) store_one(i >= 2, p0, p1, po, n);
        acc_to_frags(acc, fa);
        pin(fa);

        float sA[44], sE[16], sB[44];
        RawX nxt;
        if (!first) turn_wait(wg);
        mbar_wait(bar_a, w.corner ? i >> 1 : 0);
        wg_fence();
#pragma unroll
        for (int s = 0; s < 12; s++) {
            if (s == 0) wgmma_n88<true>(sA, fa[4 * s], fa[4 * s + 1], fa[4 * s + 2], fa[4 * s + 3], desc_at(dA, (s >> 2) * kRingChunk + (s & 3) * 32));
            else wgmma_n88<false>(sA, fa[4 * s], fa[4 * s + 1], fa[4 * s + 2], fa[4 * s + 3], desc_at(dA, (s >> 2) * kRingChunk + (s & 3) * 32));
            if (s == 11) { wg_commit(); if (!first) turn_pass(wg); }
            if ((ASLOTS >> s) & 1) store_one(i >= 2, p0, p1, po, 12 - __builtin_popcount(BSLOTS) - __builtin_popcount(ASLOTS >> s));
        }
#pragma unroll
        for (int s = 12; s < 16; s++)
            if ((ASLOTS >> s) & 1) store_one(i >= 2, p0, p1, po, 12 - __builtin_popcount(BSLOTS) - __builtin_popcount(ASLOTS >> s));
        TRF(12 + 16 * k);
        const int vq = tv + 2 * wq;
        const uint4 tabu = lds128(s_tab + offsetof(Table, u) + (window_start(tu + r8) - origin_u(tu)) * 64 + j * 16);
        const uint4 tabv = lds128(s_tab + offsetof(Table, v) + (window_start(vq) + window_start(vq + 1) - 2 * tv) * 64 + j * 16);
        const uint4 route = lds128(s_tab + lane * 16);
        if (LDGPOS == 0) load_raw(nxt, x, o0, o1);
        float v0[14], v1[14];
#pragma unroll
        for (int b = 0; b < 14; b++) v0[b] = v1[b] = __int_as_float(0xff800000);
        wg_wait<0>();
        pin(sA);
        gather_outer(sA, tabu.x, tabv.x, v0, v1);
        pin(v0); pin(v1);
        if (!first) turn_wait(wg);
#pragma unroll
        for (int c = 0; c < 3; c++) {
            mbar_wait(bar_b + 8 * c, wg);
            TRF(64 + 4 * k + c);
            wg_fence();
#pragma unroll
            for (int s = 4 * c; s < 4 * c + 4; s++) {
                if (s == 0) wgmma_n88<true>(sB, fa[4 * s], fa[4 * s + 1], fa[4 * s + 2], fa[4 * s + 3], desc_at(dB, c * kRingChunk + (s & 3) * 32));
                else wgmma_n88<false>(sB, fa[4 * s], fa[4 * s + 1], fa[4 * s + 2], fa[4 * s + 3], desc_at(dB, c * kRingChunk + (s & 3) * 32));
                if ((BSLOTS >> s) & 1) store_one(i >= 2, p0, p1, po, 12 - __builtin_popcount(BSLOTS >> s));
            }
        }
        wg_commit();
#pragma unroll
        for (int s = 0; s < 12; s++)
            if (s == 0) wgmma_n32<true>(sE, fa[4 * s], fa[4 * s + 1], fa[4 * s + 2], fa[4 * s + 3], desc_at(dsc, kOffMid + (s >> 2) * kRingChunk + (s & 3) * 32));
            else wgmma_n32<false>(sE, fa[4 * s], fa[4 * s + 1], fa[4 * s + 2], fa[4 * s + 3], desc_at(dsc, kOffMid + (s >> 2) * kRingChunk + (s & 3) * 32));
        wg_commit();
        if (!last) turn_pass(wg);
        TRF(13 + 16 * k);
        wg_wait<1>();
        pin(sB);
        gather_outer(sB, tabu.w, tabv.y, v0, v1);
        wg_wait<0>();
        pin(sE);
        TRF(14 + 16 * k);
        gather_mid(sE, tabu.w, tabv.z, v0, v1);
        const float m0 = quad_max(tree_max(v0)), m1 = quad_max(tree_max(v1));

        uint32_t y[14], pa[12], pb[12];
        exp_route<0, 14>(v0, v1, m0, m1, route, (j & 1) == 0, y);
        float s0 = tree_sum(v0), s1 = tree_sum(v1);
        asm volatile("" : "+f"(s0), "+f"(s1));
        unfold<0, 0, 6>(y, tabv.w, pa);
        if (!last) turn_wait(wg + (y[0] >> 31));
        TRF(15 + 16 * k + (y[13] >> 31));
        wg_fence();
        wgmma_sp_n192_tb<true, 0>(acc, pa[0], pa[1], pa[2], pa[3], desc_at(dA, kToV), tabu.y);
        wgmma_sp_n192_tb<false, 1>(acc, pa[4], pa[5], pa[6], pa[7], desc_at(dA, kToV + 4096), tabu.y);
        wgmma_sp_n192_tb<false, 0>(acc, pa[8], pa[9], pa[10], pa[11], desc_at(dA, kToV + 8192), tabu.z);
        wgmma_sp_n192_tb<false, 1>(acc, y[10], y[11], y[12], y[13], desc_at(dsc, kToV + kOffMid), tabu.z);
        wg_commit();
        unfold<8, 0, 6>(y, tabv.w, pb);
        wg_fence();
        wgmma_sp_n192_tb<false, 0>(acc, pb[0], pb[1], pb[2], pb[3], desc_at(dB, kToV), tabu.y);
        wgmma_sp_n192_tb<false, 1>(acc, pb[4], pb[5], pb[6], pb[7], desc_at(dB, kToV + 4096), tabu.y);
        wgmma_sp_n192_tb<false, 0>(acc, pb[8], pb[9], pb[10], pb[11], desc_at(dB, kToV + 8192), tabu.z);
        wg_commit();
        if (!last) turn_pass(wg);
        TRF(16 + 16 * k);
        if (LDGPOS == 3) load_raw(nxt, x, o0, o1);
        wg_wait<1>();
        if (lane == 0) mbar_arrive(bar_use);
        TRF(17 + 16 * k);
        mbar_wait(bar_ok + 24, 0);
        wg_wait<0>();
        if (lane == 0) mbar_arrive(bar_use + 8);
        pin(acc);
        TR(18 + 16 * k);

        acc_to_frags(acc, po);
        pin(po);
        if (!last) turn_wait(wg);
        wg_fence();
        proj_gemm(acc, po, dsc, s_wv, [](int) {});
        if (!last) turn_pass(wg);
        TRF(19 + 16 * k);
        const uint32_t zero = lds_volatile(s_late);
        const float inv0 = rcp(quad_sum(s0 + __uint_as_float(zero))), inv1 = rcp(quad_sum(s1 + __uint_as_float(zero)));
        raw_to_frags(nxt, zero, fa);
        pin(fa);
#pragma unroll
        for (int q = 0; q < 48; q += 4) keep(wqkv == nullptr, fa[q], fa[q + 1], fa[q + 2], fa[q + 3]);
        keep(wqkv == nullptr, __float_as_uint(inv0), __float_as_uint(inv1), zero, lane);
        TRF(20 + 16 * k);
        tu += du2; tv += dv2;
        wg_wait<0>();
        pin(acc);
        TR(21 + 16 * k);
#pragma unroll
        for (int q = 0; q < 96; q++) acc[q] *= q & 2 ? inv1 : inv0;
        pack_out(acc, po);
#pragma unroll
        for (int n = 0; n < 12; n++) store_one<false>(i + 2 >= w.ntiles, out + c0, out + c1, po, n);
        pin(po);
    }
    TR(7);
    TRG(1);
    TRDUMP();
}

typedef CUresult (*EncodeTiledFn)(CUtensorMap*, CUtensorMapDataType, cuuint32_t, void*, const cuuint64_t*, const cuuint64_t*,
                                  const cuuint32_t*, const cuuint32_t*, CUtensorMapInterleave, CUtensorMapSwizzle,
                                  CUtensorMapL2promotion, CUtensorMapFloatOOBfill);

bool make_maps(EncodeTiledFn fn, Maps* maps, void* x, void* wqkv, void* wo) {
    const cuuint64_t pix2 = 2 * kPixBytes, row = (cuuint64_t)kHW * kPixBytes;
    const cuuint32_t estr[5] = {1, 1, 1, 1, 1};
    bool ok = true;
    for (int tr = 0; tr < 2; tr++)
        for (int b = 0; b < 2; b++) {
            const cuuint64_t su = tr ? 2 * row : pix2, sv = tr ? pix2 : 2 * row;
            const cuuint64_t dims[5] = {2 * kC, 2, 105, 2, 112};
            const cuuint64_t strides[4] = {7 * su, su, row, sv};
            const cuuint32_t box[5] = {64, 2, 7, 1, b ? 2u : 6u};
            ok = ok && fn(&maps->m[2 * tr + b], CU_TENSOR_MAP_DATA_TYPE_BFLOAT16, 5, x, dims, strides, box, estr,
                          CU_TENSOR_MAP_INTERLEAVE_NONE, CU_TENSOR_MAP_SWIZZLE_128B, CU_TENSOR_MAP_L2_PROMOTION_L2_128B,
                          CU_TENSOR_MAP_FLOAT_OOB_FILL_NONE) == CUDA_SUCCESS;
        }
    for (int b = 0; b < 2; b++) {
        const cuuint64_t dims[3] = {16, kC, b ? 36u : 12u}, strides[2] = {(b ? 3u : 1u) * kPixBytes, 32};
        const cuuint32_t box[3] = {16, b ? 16u : 192u, b ? 12u : 3u};
        ok = ok && fn(b ? &maps->wv : &maps->wo, CU_TENSOR_MAP_DATA_TYPE_BFLOAT16, 3, b ? wqkv : wo, dims, strides, box, estr,
                      CU_TENSOR_MAP_INTERLEAVE_NONE, CU_TENSOR_MAP_SWIZZLE_32B, CU_TENSOR_MAP_L2_PROMOTION_L2_128B,
                      CU_TENSOR_MAP_FLOAT_OOB_FILL_NONE) == CUDA_SUCCESS;
    }
    return ok;
}

}

extern "C" void kernel_launch(void* const* d_in, const int* in_sizes, int n_in, void* d_out, int out_size) {
    static EncodeTiledFn encode = nullptr;
    static Scratch* scratch = nullptr;
    static Tables* tables = nullptr;
    if (!encode) {
        int dev = 0, reserved = 0;
        cudaFuncAttributes attr;
        cudaGetDevice(&dev);
        cudaDeviceGetAttribute(&reserved, cudaDevAttrReservedSharedMemoryPerBlock, dev);
        cudaFuncGetAttributes(&attr, nat_fused_kernel);
        if (reserved != (int)kSmemBase || attr.sharedSizeBytes != 0) return;
        cudaGetSymbolAddress((void**)&scratch, g_scratch);
        cudaGetSymbolAddress((void**)&tables, g_tables);
        void* fn = nullptr;
        cudaDriverEntryPointQueryResult st;
        cudaGetDriverEntryPoint("cuTensorMapEncodeTiled", &fn, cudaEnableDefault, &st);
        encode = (EncodeTiledFn)fn;
        cudaFuncSetAttribute(nat_fused_kernel, cudaFuncAttributeMaxDynamicSharedMemorySize, kSmemBytes);
    }
    Maps maps;
    if (!encode || !make_maps(encode, &maps, d_in[0], d_in[1], d_in[2])) return;
    nat_fused_kernel<<<kGrid, kThreads, kSmemBytes>>>((const uint8_t*)d_in[0], (const uint8_t*)d_in[1], (uint8_t*)d_out, scratch, tables, kDescRing, maps);
}
```

```cpp
#include <cuda_runtime.h>
#include <cuda_bf16.h>
#include <cuda.h>
#include <stdint.h>
#include <type_traits>
#include <stdlib.h>
#include <stddef.h>

#define LDGPOS 0
#define INPLACE 1
#define KEEPFA 1
#define ASLOTS 0x3800
#define BSLOTS 0x6
#define QSLOTS 0x78a
#define WUNROLL 2

namespace {

constexpr int kC          = 192;
constexpr int kHW         = 224;
constexpr int kPixBytes   = kC * 2;
constexpr int kSlotBytes  = 84 * 128;
constexpr int kMidBytes   = 28 * 128;
constexpr int kOffMid     = 88 * 128;
constexpr int kSlotStride = 120 * 128;
constexpr int kRingChunk  = 208 * 128;
constexpr int kWChunk     = 192 * 128;
constexpr int kWBytes     = 3 * kWChunk;
constexpr uint32_t kSmemBase = 1024;
constexpr uint32_t s_ring = kSmemBase, s_m = s_ring + 3 * kRingChunk, s_wv = s_m + kWBytes, s_bar = s_wv + kWBytes;
constexpr uint32_t bar_b = s_bar, bar_img = s_bar + 24, bar_redo = s_bar + 72, bar_wop = s_bar + 96, bar_a = s_bar + 104,
                   bar_ok = s_bar + 112, bar_use = s_bar + 144;
constexpr uint32_t s_cnt = s_bar + 160, s_par = s_bar + 176, s_late = s_bar + 180, s_tab = s_bar + 256, s_trace = s_tab + 2048;
constexpr int kSmemBytes  = s_trace + 2048 - kSmemBase;
constexpr int kThreads    = 384, kWUnroll = WUNROLL;
constexpr int kGrid       = 132;
constexpr int kPieces     = 144;
constexpr float kScaleLog2e = 0.07216878364870322f * 1.4426950408889634f;

struct Maps {
    CUtensorMap m[4];
    CUtensorMap wo, wv;
};
#define TN(i, dflt) (dflt)
#define START_TIME (wg ? 1900 + 500 * order : which ? 100 + 500 * order : order ? 2100 + 200 * order : 400)

struct Scratch {
    uint8_t img[2][2][kWBytes];
    uint32_t cnt[4];
};
__device__ __align__(1024) Scratch g_scratch;

struct Table {
    uint32_t route[32][4];
    uint32_t u[8][4][4];
    uint32_t v[16][4][4];
};
struct Tables { Table t[2]; };
constexpr Tables make_tables() {
    Tables r = {};
    for (int rev = 0; rev < 2; rev++)
        for (int j = 0; j < 4; j++) {
            Table& t = r.t[rev];
            for (int q = 0; q < 8; q++) {
                uint32_t* e = t.route[4 * q + j];
                e[0] = 4 * q + 2 * (j & 1) + (j >> 1); e[1] = e[0] ^ 1;
                e[2] = j < 2 ? 0x5410u : 0x1054u; e[3] = e[2] + 0x2222u;
                e = t.u[q][j];
                for (int n = 0; n < 7; n++) e[0] |= ((n + j) % 7 < q ? 1u : 0u) << n;
                e[3] = e[0];
                for (int k = 0; k < 2; k++) {
                    const int step = 2 * k + (j >> 1), p0 = (step < 3 ? 16 * step : 40) + 8 * (j & 1);
                    uint32_t m = 0x8888u;
                    for (int n = 0; n < 8; n++) m |= ((p0 + n) % 7 < q ? 1u : 0u) << (2 * n);
                    e[1 + k] = m * 0x10001u;
                }
            }
            for (int sum = 0; sum < 15; sum++) {
                uint32_t* e = t.v[sum][j];
                for (int row = 0; row < 2; row++)
                    for (int b = 0; b < 14; b++) {
                        const int off = (sum + row) / 2, p = 4 * b + j;
                        const uint32_t bit = 1u << (2 * b + row);
                        if (p < 42 && p >= 7 * off) e[rev] |= bit;
                        if (p < 7 * off - 7) e[1 - rev] |= bit;
                        if (p >= 42 && p >= 7 * off && p < 7 * off + 49) e[2] |= bit;
                    }
                for (int n = 0; n < 6; n++)
                    if (8 * n + 2 * j < 42) e[3] |= 1u << (n + ((8 * n + 2 * j >= 7 * (sum / 2 & ~1)) != rev ? 0 : 8));
            }
        }
    return r;
}
__device__ __align__(128) const Tables g_tables = make_tables();

#define WO4(i) "=f"(d[i]), "=f"(d[i + 1]), "=f"(d[i + 2]), "=f"(d[i + 3])
#define RW4(i) "+f"(d[i]), "+f"(d[i + 1]), "+f"(d[i + 2]), "+f"(d[i + 3])

template <bool FIRST>
__device__ __forceinline__ void wgmma_n192(float (&d)[96], uint32_t a0, uint32_t a1, uint32_t a2, uint32_t a3, uint64_t descb) {
    if constexpr (FIRST) {
        asm volatile(
            "wgmma.mma_async.sync.aligned.m64n192k16.f32.bf16.bf16 "
            "{%0, %1, %2, %3, %4, %5, %6, %7, %8, %9, %10, %11, %12, %13, %14, %15, %16, %17, %18, %19, %20, %21, %22, %23, "
            "%24, %25, %26, %27, %28, %29, %30, %31, %32, %33, %34, %35, %36, %37, %38, %39, %40, %41, %42, %43, %44, %45, %46, %47, "
            "%48, %49, %50, %51, %52, %53, %54, %55, %56, %57, %58, %59, %60, %61, %62, %63, %64, %65, %66, %67, %68, %69, %70, %71, "
            "%72, %73, %74, %75, %76, %77, %78, %79, %80, %81, %82, %83, %84, %85, %86, %87, %88, %89, %90, %91, %92, %93, %94, %95}, "
            "{%96, %97, %98, %99}, %100, 0, 1, 1, 0;"
            : WO4(0), WO4(4), WO4(8), WO4(12), WO4(16), WO4(20), WO4(24), WO4(28), WO4(32), WO4(36), WO4(40), WO4(44),
              WO4(48), WO4(52), WO4(56), WO4(60), WO4(64), WO4(68), WO4(72), WO4(76), WO4(80), WO4(84), WO4(88), WO4(92)
            : "r"(a0), "r"(a1), "r"(a2), "r"(a3), "l"(descb));
    } else {
        asm volatile(
            "wgmma.mma_async.sync.aligned.m64n192k16.f32.bf16.bf16 "
            "{%0, %1, %2, %3, %4, %5, %6, %7, %8, %9, %10, %11, %12, %13, %14, %15, %16, %17, %18, %19, %20, %21, %22, %23, "
            "%24, %25, %26, %27, %28, %29, %30, %31, %32, %33, %34, %35, %36, %37, %38, %39, %40, %41, %42, %43, %44, %45, %46, %47, "
            "%48, %49, %50, %51, %52, %53, %54, %55, %56, %57, %58, %59, %60, %61, %62, %63, %64, %65, %66, %67, %68, %69, %70, %71, "
            "%72, %73, %74, %75, %76, %77, %78, %79, %80, %81, %82, %83, %84, %85, %86, %87, %88, %89, %90, %91, %92, %93, %94, %95}, "
            "{%96, %97, %98, %99}, %100, 1, 1, 1, 0;"
            : RW4(0), RW4(4), RW4(8), RW4(12), RW4(16), RW4(20), RW4(24), RW4(28), RW4(32), RW4(36), RW4(40), RW4(44),
              RW4(48), RW4(52), RW4(56), RW4(60), RW4(64), RW4(68), RW4(72), RW4(76), RW4(80), RW4(84), RW4(88), RW4(92)
            : "r"(a0), "r"(a1), "r"(a2), "r"(a3), "l"(descb));
    }
}

template <bool FIRST>
__device__ __forceinline__ void wgmma_n88(float (&d)[44], uint32_t a0, uint32_t a1, uint32_t a2, uint32_t a3, uint64_t descb) {
    if constexpr (FIRST) {
        asm volatile(
            "wgmma.mma_async.sync.aligned.m64n88k16.f32.bf16.bf16 "
            "{%0, %1, %2, %3, %4, %5, %6, %7, %8, %9, %10, %11, %12, %13, %14, %15, %16, %17, %18, %19, %20, %21, %22, %23, "
            "%24, %25, %26, %27, %28, %29, %30, %31, %32, %33, %34, %35, %36, %37, %38, %39, %40, %41, %42, %43}, "
            "{%44, %45, %46, %47}, %48, 0, 1, 1, 0;"
            : WO4(0), WO4(4), WO4(8), WO4(12), WO4(16), WO4(20), WO4(24), WO4(28), WO4(32), WO4(36), WO4(40)
            : "r"(a0), "r"(a1), "r"(a2), "r"(a3), "l"(descb));
    } else {
        asm volatile(
            "wgmma.mma_async.sync.aligned.m64n88k16.f32.bf16.bf16 "
            "{%0, %1, %2, %3, %4, %5, %6, %7, %8, %9, %10, %11, %12, %13, %14, %15, %16, %17, %18, %19, %20, %21, %22, %23, "
            "%24, %25, %26, %27, %28, %29, %30, %31, %32, %33, %34, %35, %36, %37, %38, %39, %40, %41, %42, %43}, "
            "{%44, %45, %46, %47}, %48, 1, 1, 1, 0;"
            : RW4(0), RW4(4), RW4(8), RW4(12), RW4(16), RW4(20), RW4(24), RW4(28), RW4(32), RW4(36), RW4(40)
            : "r"(a0), "r"(a1), "r"(a2), "r"(a3), "l"(descb));
    }
}

template <bool FIRST>
__device__ __forceinline__ void wgmma_n32(float (&d)[16], uint32_t a0, uint32_t a1, uint32_t a2, uint32_t a3, uint64_t descb) {
    if constexpr (FIRST) {
        asm volatile(
            "wgmma.mma_async.sync.aligned.m64n32k16.f32.bf16.bf16 "
            "{%0, %1, %2, %3, %4, %5, %6, %7, %8, %9, %10, %11, %12, %13, %14, %15}, "
            "{%16, %17, %18, %19}, %20, 0, 1, 1, 0;"
            : WO4(0), WO4(4), WO4(8), WO4(12)
            : "r"(a0), "r"(a1), "r"(a2), "r"(a3), "l"(descb));
    } else {
        asm volatile(
            "wgmma.mma_async.sync.aligned.m64n32k16.f32.bf16.bf16 "
            "{%0, %1, %2, %3, %4, %5, %6, %7, %8, %9, %10, %11, %12, %13, %14, %15}, "
            "{%16, %17, %18, %19}, %20, 1, 1, 1, 0;"
            : RW4(0), RW4(4), RW4(8), RW4(12)
            : "r"(a0), "r"(a1), "r"(a2), "r"(a3), "l"(descb));
    }
}

template <bool FIRST, int SEL>
__device__ __forceinline__ void wgmma_sp_n192_tb(float (&d)[96], uint32_t a0, uint32_t a1, uint32_t a2, uint32_t a3, uint64_t descb, uint32_t meta) {
    if constexpr (FIRST) {
        asm volatile(
            "wgmma.mma_async.sp.sync.aligned.m64n192k32.f32.bf16.bf16 "
            "{%0, %1, %2, %3, %4, %5, %6, %7, %8, %9, %10, %11, %12, %13, %14, %15, %16, %17, %18, %19, %20, %21, %22, %23, "
            "%24, %25, %26, %27, %28, %29, %30, %31, %32, %33, %34, %35, %36, %37, %38, %39, %40, %41, %42, %43, %44, %45, %46, %47, "
            "%48, %49, %50, %51, %52, %53, %54, %55, %56, %57, %58, %59, %60, %61, %62, %63, %64, %65, %66, %67, %68, %69, %70, %71, "
            "%72, %73, %74, %75, %76, %77, %78, %79, %80, %81, %82, %83, %84, %85, %86, %87, %88, %89, %90, %91, %92, %93, %94, %95}, "
            "{%96, %97, %98, %99}, %100, %101, %102, 0, 1, 1, 1;"
            : WO4(0), WO4(4), WO4(8), WO4(12), WO4(16), WO4(20), WO4(24), WO4(28), WO4(32), WO4(36), WO4(40), WO4(44),
              WO4(48), WO4(52), WO4(56), WO4(60), WO4(64), WO4(68), WO4(72), WO4(76), WO4(80), WO4(84), WO4(88), WO4(92)
            : "r"(a0), "r"(a1), "r"(a2), "r"(a3), "l"(descb), "r"(meta), "n"(SEL));
    } else {
        asm volatile(
            "wgmma.mma_async.sp.sync.aligned.m64n192k32.f32.bf16.bf16 "
            "{%0, %1, %2, %3, %4, %5, %6, %7, %8, %9, %10, %11, %12, %13, %14, %15, %16, %17, %18, %19, %20, %21, %22, %23, "
            "%24, %25, %26, %27, %28, %29, %30, %31, %32, %33, %34, %35, %36, %37, %38, %39, %40, %41, %42, %43, %44, %45, %46, %47, "
            "%48, %49, %50, %51, %52, %53, %54, %55, %56, %57, %58, %59, %60, %61, %62, %63, %64, %65, %66, %67, %68, %69, %70, %71, "
            "%72, %73, %74, %75, %76, %77, %78, %79, %80, %81, %82, %83, %84, %85, %86, %87, %88, %89, %90, %91, %92, %93, %94, %95}, "
            "{%96, %97, %98, %99}, %100, %101, %102, 1, 1, 1, 1;"
            : RW4(0), RW4(4), RW4(8), RW4(12), RW4(16), RW4(20), RW4(24), RW4(28), RW4(32), RW4(36), RW4(40), RW4(44),
              RW4(48), RW4(52), RW4(56), RW4(60), RW4(64), RW4(68), RW4(72), RW4(76), RW4(80), RW4(84), RW4(88), RW4(92)
            : "r"(a0), "r"(a1), "r"(a2), "r"(a3), "l"(descb), "r"(meta), "n"(SEL));
    }
}

#define TR(slot)
#define TRT(slot)
#define TRF(slot)
#define TRW(slot)
#define TRG(slot)
#define TRDUMP()

__device__ __forceinline__ void wg_fence() { asm volatile("wgmma.fence.sync.aligned;" ::: "memory"); }
__device__ __forceinline__ void wg_commit() { asm volatile("wgmma.commit_group.sync.aligned;" ::: "memory"); }
template <int N>
__device__ __forceinline__ void wg_wait() { asm volatile("wgmma.wait_group.sync.aligned %0;" ::"n"(N) : "memory"); }

template <int N>
__device__ __forceinline__ void pin(float (&d)[N]) {
#pragma unroll
    for (int i = 0; i < N; i++) asm volatile("" : "+f"(d[i])::"memory");
}
template <int N>
__device__ __forceinline__ void pin(uint32_t (&d)[N]) {
#pragma unroll
    for (int i = 0; i < N; i++) asm volatile("" : "+r"(d[i])::"memory");
}

constexpr uint64_t kDescRing = ((uint64_t)((1u << 30) | (1024u >> 4)) << 32) | (1u << 16) | (s_ring >> 4);
constexpr uint32_t kToV = ((kRingChunk >> 4) - 1) << 20;
__device__ __forceinline__ uint64_t desc_at(uint64_t base, uint32_t byte_off) {
    uint64_t d;
    asm volatile("add.s64 %0, %1, %2;" : "=l"(d) : "l"(base), "l"((uint64_t)(byte_off >> 4)));
    return d;
}

__device__ __forceinline__ void mbar_init(uint32_t bar, uint32_t count) {
    asm volatile("mbarrier.init.shared::cta.b64 [%0], %1;" ::"r"(bar), "r"(count) : "memory");
}
__device__ __forceinline__ void mbar_expect_tx(uint32_t bar, uint32_t bytes) {
    asm volatile("mbarrier.arrive.expect_tx.shared::cta.b64 _, [%0], %1;" ::"r"(bar), "r"(bytes) : "memory");
}
__device__ __forceinline__ void expect_tx_only(uint32_t bar, uint32_t bytes) {
    asm volatile("mbarrier.expect_tx.relaxed.cta.shared::cta.b64 [%0], %1;" ::"r"(bar), "r"(bytes) : "memory");
}
__device__ __forceinline__ void mbar_arrive(uint32_t bar) {
    asm volatile("mbarrier.arrive.shared::cta.b64 _, [%0];" ::"r"(bar) : "memory");
}
__device__ __forceinline__ void mbar_wait(uint32_t bar, uint32_t parity) {
    asm volatile(
        "{\n.reg .pred p;\n"
        "W: mbarrier.try_wait.parity.shared::cta.b64 p, [%0], %1;\n"
        "@!p bra W;\n}\n"
        ::"r"(bar), "r"(parity) : "memory");
}
__device__ __forceinline__ uint32_t clock_now() {
    uint32_t c;
    asm volatile("mov.u32 %0, %%clock;" : "=r"(c)::"memory");
    return c;
}
__device__ __forceinline__ void wait_until(uint32_t t0, int t) {
    if (t == 0) return;
    while ((int)(clock_now() - t0) < t) {}
}
__device__ __forceinline__ bool elect() {
    uint32_t ok;
    asm volatile("{\n.reg .pred p;\nelect.sync _|p, 0xffffffff;\nselp.u32 %0, 1, 0, p;\n}\n" : "=r"(ok));
    return ok != 0;
}
__device__ __forceinline__ void turn_wait(int wg) { asm volatile("bar.sync %0, 256;" ::"r"(1 + wg) : "memory"); }
__device__ __forceinline__ void turn_pass(int wg) { asm volatile("bar.arrive %0, 256;" ::"r"(2 - wg) : "memory"); }

__device__ __forceinline__ void tma_box(uint32_t dst, const CUtensorMap* map, uint32_t bar, int c0, int c2, int c3, int c4) {
    asm volatile(
        "cp.async.bulk.tensor.5d.shared::cluster.global.mbarrier::complete_tx::bytes [%0], [%1, {%3, %4, %5, %6, %7}], [%2];"
        ::"r"(dst), "l"(map), "r"(bar), "r"(c0), "r"(0), "r"(c2), "r"(c3), "r"(c4)
        : "memory");
}
__device__ __forceinline__ void tma_3d(uint32_t dst, const CUtensorMap* map, uint32_t bar, int c1, int c2) {
    asm volatile("cp.async.bulk.tensor.3d.shared::cluster.global.mbarrier::complete_tx::bytes [%0], [%1, {%3, %4, %5}], [%2];"
                 ::"r"(dst), "l"(map), "r"(bar), "r"(0), "r"(c1), "r"(c2)
                 : "memory");
}
__device__ __forceinline__ void prefetch_map(const CUtensorMap* map) {
    asm volatile("prefetch.tensormap [%0];" ::"l"(map) : "memory");
}
__device__ __forceinline__ uint4 ldg(const void* p) {
    uint4 v;
    asm volatile("ld.global.v4.u32 {%0, %1, %2, %3}, [%4];" : "=r"(v.x), "=r"(v.y), "=r"(v.z), "=r"(v.w) : "l"(p) : "memory");
    return v;
}
__device__ __forceinline__ uint32_t pack_bf16(float lo, float hi) {
    uint32_t r;
    asm("cvt.rn.bf16x2.f32 %0, %1, %2;" : "=r"(r) : "f"(hi), "f"(lo));
    return r;
}
__device__ __forceinline__ float ex2(float x) {
    float y;
    asm("ex2.approx.ftz.f32 %0, %1;" : "=f"(y) : "f"(x));
    return y;
}
__device__ __forceinline__ float rcp(float x) {
    float y;
    asm("rcp.approx.ftz.f32 %0, %1;" : "=f"(y) : "f"(x));
    return y;
}
__device__ __forceinline__ void mma16816(float (&d)[4], uint32_t a0, uint32_t a1, uint32_t a2, uint32_t a3, uint32_t b0, uint32_t b1) {
    asm volatile("mma.sync.aligned.m16n8k16.row.col.f32.bf16.bf16.f32 {%0, %1, %2, %3}, {%4, %5, %6, %7}, {%8, %9}, {%0, %1, %2, %3};"
                 : "+f"(d[0]), "+f"(d[1]), "+f"(d[2]), "+f"(d[3])
                 : "r"(a0), "r"(a1), "r"(a2), "r"(a3), "r"(b0), "r"(b1));
}
__device__ __forceinline__ uint4 lds128(uint32_t addr) {
    uint4 v;
    asm volatile("ld.volatile.shared.v4.u32 {%0, %1, %2, %3}, [%4];" : "=r"(v.x), "=r"(v.y), "=r"(v.z), "=r"(v.w) : "r"(addr) : "memory");
    return v;
}
__device__ __forceinline__ uint32_t lds_volatile(uint32_t addr) {
    uint32_t v;
    asm volatile("ld.volatile.shared.u32 %0, [%1];" : "=r"(v) : "r"(addr) : "memory");
    return v;
}

__device__ __forceinline__ int window_start(int n) { return min(max(n, 0), 105); }
__device__ __forceinline__ int origin_u(int u) { return min(max(u, 0), 98); }

struct Work {
    int u, v;
    int step;
    uint32_t su, sv;
    uint32_t base;
    bool corner;
    int ntiles;
    __device__ __forceinline__ void pixel_offsets(int qu, int qv, int j, uint32_t& o0, uint32_t& o1) const {
        const uint32_t b = (qu + window_start(qu)) * su + j * 16 + base;
        o0 = b + (qv + window_start(qv)) * sv;
        o1 = b + (qv + 1 + window_start(qv + 1)) * sv;
    }
};

__device__ __forceinline__ Work decode_work(int c) {
    Work w;
    const bool transposed = (c >> 4) == 7;
    const int px = 6 * (c & 1), py = 3 * (c & 2);
    w.corner = c >= 128;
    w.step = 8 - 4 * (c & 4);
    w.u = (c < 112 ? c & ~7 : 96 + (c & 8)) + (transposed ? py : px) - 6;
    w.v = (w.corner ? 96 : 48 - 2 * (c & 4)) + (transposed ? px : py) - 6;
    w.su = transposed ? kHW * kPixBytes : kPixBytes;
    w.sv = transposed ? kPixBytes : kHW * kPixBytes;
    w.base = px * (kPixBytes / 6) + py * (kHW * kPixBytes / 6) + 6 * (kHW + 1) * kPixBytes;
    w.ntiles = w.corner ? 4 : 6;
    return w;
}

struct RawX { uint4 a[6], b[6]; };
__device__ __forceinline__ void load_raw(RawX& r, const uint8_t* base, uint32_t o0, uint32_t o1) {
    __syncwarp();
#pragma unroll
    for (int c = 0; c < 6; c++) { r.a[c] = ldg(base + o0 + c * 64); r.b[c] = ldg(base + o1 + c * 64); }
    __syncwarp();
}
__device__ __forceinline__ void raw_to_frags(const RawX& r, uint32_t zero, uint32_t (&f)[48]) {
#pragma unroll
    for (int c = 0; c < 6; c++) {
        f[8 * c + 0] = r.a[c].x; f[8 * c + 2] = r.a[c].z; f[8 * c + 4] = r.a[c].y ^ zero; f[8 * c + 6] = r.a[c].w ^ zero;
        f[8 * c + 1] = r.b[c].x ^ zero; f[8 * c + 3] = r.b[c].z ^ zero; f[8 * c + 5] = r.b[c].y ^ zero; f[8 * c + 7] = r.b[c].w ^ zero;
    }
}
__device__ __forceinline__ void acc_to_frags(const float (&d)[96], uint32_t (&f)[48]) {
#pragma unroll
    for (int i = 0; i < 48; i++) f[i] = pack_bf16(d[2 * i], d[2 * i + 1]);
}

template <class F>
__device__ __forceinline__ void proj_gemm(float (&d)[96], const uint32_t (&a)[48], uint64_t dsc, uint32_t img, F after) {
#pragma unroll
    for (int s = 0; s < 12; s++) {
        if (s == 0) wgmma_n192<true>(d, a[4 * s], a[4 * s + 1], a[4 * s + 2], a[4 * s + 3], desc_at(dsc, img - s_ring + (s >> 2) * kWChunk + (s & 3) * 32));
        else wgmma_n192<false>(d, a[4 * s], a[4 * s + 1], a[4 * s + 2], a[4 * s + 3], desc_at(dsc, img - s_ring + (s >> 2) * kWChunk + (s & 3) * 32));
        if (s == 11) wg_commit();
        after(s);
    }
}
__device__ __forceinline__ void pack_out(const float (&acc)[96], uint32_t (&po)[48]) {
#pragma unroll
    for (int g = 0; g < 6; g++)
#pragma unroll
        for (int q = 0; q < 4; q++) {
            po[8 * g + q] = pack_bf16(acc[16 * g + 4 * q], acc[16 * g + 4 * q + 1]);
            po[8 * g + 4 + q] = pack_bf16(acc[16 * g + 4 * q + 2], acc[16 * g + 4 * q + 3]);
        }
}
template <bool PINNED = true>
__device__ __forceinline__ void store_one(bool on, uint8_t* p0, uint8_t* p1, const uint32_t (&po)[48], int n) {
    if (PINNED) __syncwarp();
    asm volatile("{\n.reg .pred p;\nsetp.ne.u32 p, %5, 0;\n@p st.global.v4.u32 [%0], {%1, %2, %3, %4};\n}\n"
                 ::"l"(((n & 1) ? p1 : p0) + (n >> 1) * 64), "r"(po[4 * n]), "r"(po[4 * n + 1]), "r"(po[4 * n + 2]), "r"(po[4 * n + 3]), "r"((uint32_t)on) : "memory");
}

template <int N>
__device__ __forceinline__ float tree_max(const float (&v)[N]) {
    float t[N];
#pragma unroll
    for (int i = 0; i < N; i++) t[i] = v[i];
#pragma unroll
    for (int w = 1; w < N; w *= 2)
#pragma unroll
        for (int i = 0; i + w < N; i += 2 * w) t[i] = fmaxf(t[i], t[i + w]);
    return t[0];
}
template <int N>
__device__ __forceinline__ float tree_sum(const float (&v)[N]) {
    float t[N];
#pragma unroll
    for (int i = 0; i < N; i++) t[i] = v[i];
#pragma unroll
    for (int w = 1; w < N; w *= 2)
#pragma unroll
        for (int i = 0; i + w < N; i += 2 * w) t[i] += t[i + w];
    return t[0];
}

template <int B>
__device__ __forceinline__ void pick(uint32_t h, uint32_t ok, const float* s, float& v0, float& v1) {
    asm("{\n.reg .pred p, q0, q1;\n.reg .b32 t;\nand.b32 t, %6, %7;\nsetp.ne.u32 p, t, 0;\n"
        "and.b32 t, %8, %9;\nsetp.ne.u32 q0, t, 0;\nand.b32 t, %8, %10;\nsetp.ne.u32 q1, t, 0;\n"
        "@q0 selp.f32 %0, %3, %2, p;\n@q1 selp.f32 %1, %5, %4, p;\n}\n"
        : "+f"(v0), "+f"(v1)
        : "f"(s[0]), "f"(s[1]), "f"(s[2]), "f"(s[3]), "r"(h), "n"(1 << ((4 * B) % 7)), "r"(ok), "n"(1 << (2 * B)), "n"(2 << (2 * B)));
}
template <int B, class F>
__device__ __forceinline__ void for_blocks(F f) {
    if constexpr (B > 0) { for_blocks<B - 1>(f); f(std::integral_constant<int, B - 1>{}); }
}
__device__ __forceinline__ void gather_outer(const float (&s)[44], uint32_t h, uint32_t ok, float (&v0)[14], float (&v1)[14]) {
    for_blocks<11>([&](auto B) {
        constexpr int b = B.value < 8 ? (B.value >> 1) + 7 * (B.value & 1) : B.value - 4;
        pick<b>(h, ok, &s[4 * b], v0[b], v1[b]);
    });
}
__device__ __forceinline__ void gather_mid(const float (&sE)[16], uint32_t h, uint32_t ok, float (&v0)[14], float (&v1)[14]) {
    for_blocks<4>([&](auto B) { pick<10 + B.value>(h, ok, &sE[4 * B.value], v0[10 + B.value], v1[10 + B.value]); });
}
__device__ __forceinline__ float quad_max(float m) {
    m = fmaxf(m, __shfl_xor_sync(0xffffffffu, m, 1));
    return fmaxf(m, __shfl_xor_sync(0xffffffffu, m, 2));
}
__device__ __forceinline__ float quad_sum(float s) {
    s += __shfl_xor_sync(0xffffffffu, s, 1);
    return s + __shfl_xor_sync(0xffffffffu, s, 2);
}
template <int B0, int B1>
__device__ __forceinline__ void exp_route(float (&v0)[14], float (&v1)[14], float m0, float m1, const uint4& r, bool even, uint32_t (&y)[14]) {
#pragma unroll
    for (int b = B0; b < B1; b++) { v0[b] = ex2(v0[b] - m0); v1[b] = ex2(v1[b] - m1); }
#pragma unroll
    for (int b = B0; b < B1; b += 2) {
        const uint32_t x0 = pack_bf16(v0[b], v1[b]), x1 = pack_bf16(v0[b + 1], v1[b + 1]);
        const uint32_t u = __shfl_sync(0xffffffffu, even ? x0 : x1, r.x);
        const uint32_t w = __shfl_sync(0xffffffffu, even ? x1 : x0, r.y);
        y[b] = __byte_perm(u, w, r.z); y[b + 1] = __byte_perm(u, w, r.w);
    }
}
template <int BIT0, int N0, int N1>
__device__ __forceinline__ void unfold(const uint32_t (&y)[14], uint32_t fold, uint32_t (&p)[12]) {
    for_blocks<N1 - N0>([&](auto N) {
        constexpr int n = N0 + N.value;
        asm("{\n.reg .pred p;\n.reg .b32 t;\nand.b32 t, %4, %5;\nsetp.ne.u32 p, t, 0;\nselp.b32 %0, %2, 0, p;\nselp.b32 %1, %3, 0, p;\n}\n"
            : "=r"(p[2 * n]), "=r"(p[2 * n + 1]) : "r"(y[2 * n]), "r"(y[2 * n + 1]), "r"(fold), "n"(1 << (BIT0 + n)));
    });
}
__device__ __forceinline__ void keep(bool never, uint32_t a, uint32_t b, uint32_t c, uint32_t d) {
    asm volatile("{\n.reg .pred p;\nsetp.ne.u32 p, %4, 0;\n@p st.volatile.shared.v4.u32 [%5], {%0, %1, %2, %3};\n}\n"
                 ::"r"(a), "r"(b), "r"(c), "r"(d), "r"((uint32_t)never), "r"(s_trace) : "memory");
}

__device__ __forceinline__ uint32_t wimg_offset(uint32_t row, uint32_t s, uint32_t j) {
    return (s >> 2) * kWChunk + row * 128 + (((2 * (s & 3) + (j >> 1)) ^ (row & 7)) << 4) + (j & 1) * 8;
}

__device__ __forceinline__ void ldsm4(uint32_t (&r)[4], uint32_t addr) {
    asm volatile("ldmatrix.sync.aligned.m8n8.x4.shared.b16 {%0, %1, %2, %3}, [%4];" : "=r"(r[0]), "=r"(r[1]), "=r"(r[2]), "=r"(r[3]) : "r"(addr) : "memory");
}
__device__ __forceinline__ void ldsm4_t(uint32_t (&r)[4], uint32_t addr) {
    asm volatile("ldmatrix.sync.aligned.m8n8.x4.trans.shared.b16 {%0, %1, %2, %3}, [%4];" : "=r"(r[0]), "=r"(r[1]), "=r"(r[2]), "=r"(r[3]) : "r"(addr) : "memory");
}
__device__ __forceinline__ void m_partial(const uint8_t* wqkv, uint32_t mt, uint32_t s, uint32_t q, uint32_t lane, uint32_t zero) {
    const uint32_t r8 = lane >> 2, col = q * 128 + (lane & 3) * 16;
    const uint8_t* pa = wqkv + (16 * mt + r8) * 1152 + col;
    const uint8_t* pb = wqkv + (16 * s + 8 * (r8 & 2) + (r8 & 5)) * 1152 + col;
    uint4 A[2][2], B[4][2];
#pragma unroll
    for (int c = 0; c < 2; c++) {
#pragma unroll
        for (int h = 0; h < 2; h++) A[h][c] = ldg(pa + 384 + h * 8 * 1152 + c * 64);
#pragma unroll
        for (int n = 0; n < 4; n++) B[n][c] = ldg(pb + ((n & 1) * 8 + (n & 2)) * 1152 + c * 64);
    }
#pragma unroll
    for (int i = 0; i < 4; i++) { uint4& a = A[i >> 1][i & 1]; a.x ^= zero; a.y ^= zero; a.z ^= zero; a.w ^= zero; }
#pragma unroll
    for (int n = 0; n < 4; n++) {
        float d[4] = {0.f, 0.f, 0.f, 0.f};
#pragma unroll
        for (int c = 0; c < 2; c++) {
            mma16816(d, A[0][c].x, A[1][c].x, A[0][c].y, A[1][c].y, B[n][c].x, B[n][c].y);
            mma16816(d, A[0][c].z, A[1][c].z, A[0][c].w, A[1][c].w, B[n][c].z, B[n][c].w);
        }
        asm volatile("st.shared.v4.f32 [%0], {%1, %2, %3, %4};" ::"r"(s_wv + q * 2048 + n * 512 + lane * 16), "f"(d[0]), "f"(d[1]), "f"(d[2]), "f"(d[3]) : "memory");
    }
}
__device__ __forceinline__ void m_reduce(uint32_t e, uint32_t lane, float (&d)[2][4]) {
#pragma unroll
    for (int n = 0; n < 2; n++) {
        float t[3][4];
#pragma unroll
        for (int q = 0; q < 3; q++)
            asm volatile("ld.shared.v4.f32 {%0, %1, %2, %3}, [%4];" : "=f"(t[q][0]), "=f"(t[q][1]), "=f"(t[q][2]), "=f"(t[q][3]) : "r"(s_wv + q * 2048 + e * 1024 + n * 512 + lane * 16) : "memory");
#pragma unroll
        for (int i = 0; i < 4; i++) d[n][i] = (t[0][i] + t[1][i] + t[2][i]) * kScaleLog2e;
    }
}
__device__ __forceinline__ void w_piece(uint32_t q, uint32_t lane, float (&d)[2][4]) {
    const uint32_t rr = lane & 7, mi = lane >> 3, kr = 4 * (rr >> 1) + (mi & 2) + (rr & 1);
    const uint32_t pa = s_wv + q * 6144 + (4 * (mi & 2) + rr) * 32 + (((mi ^ (rr >> 2)) & 1) << 4);
    const uint32_t pb = s_wv + 3 * 6144 + kr * 32 + (((mi ^ (kr >> 2)) & 1) << 4);
#pragma unroll
    for (int i = 0; i < 8; i++) (&d[0][0])[i] = 0.f;
#pragma unroll kWUnroll
    for (int k = 0; k < 12; k++) {
        uint32_t aq[4], bq[4];
        ldsm4_t(aq, pa + k * 512);
        ldsm4(bq, pb + k * 512);
        mma16816(d[0], aq[0], aq[1], aq[2], aq[3], bq[0], bq[1]);
        mma16816(d[1], aq[0], aq[1], aq[2], aq[3], bq[2], bq[3]);
    }
}
__device__ __forceinline__ uint32_t piece_offset(uint32_t which, uint32_t s, uint32_t mt, uint32_t lane) {
    const uint32_t r8 = lane >> 2;
    return which * kWBytes + wimg_offset(which ? 32 * (mt >> 1) + 8 * (r8 >> 1) + 4 * (mt & 1) + (r8 & 1) : 16 * mt + r8, s, lane & 3);
}
__device__ __forceinline__ void piece_store(Scratch* g, uint32_t par, uint32_t off0, uint32_t which, const float (&d)[2][4]) {
#pragma unroll
    for (int hf = 0; hf < 2; hf++) {
        const uint32_t off = off0 ^ (hf ? which ? 288 : 1024 : 0);
        const uint32_t a = pack_bf16(d[0][2 * hf], d[0][2 * hf + 1]), b = pack_bf16(d[1][2 * hf], d[1][2 * hf + 1]);
        asm volatile("st.relaxed.gpu.global.v2.u32 [%0], {%1, %2};" ::"l"(g->img[0][0] + (par + off)), "r"(a ? a : 0x8000u), "r"(b) : "memory");
        asm volatile("st.relaxed.gpu.global.v2.u32 [%0], {%1, %1};" ::"l"(g->img[1][0] + (int)(off - par)), "r"(0) : "memory");
    }
}

__device__ __forceinline__ uint32_t ld_relaxed(const uint32_t* p) {
    uint32_t v;
    asm volatile("ld.relaxed.gpu.global.u32 %0, [%1];" : "=r"(v) : "l"(p) : "memory");
    return v;
}
__device__ __forceinline__ void count_up(uint32_t* p) {
    asm volatile("red.relaxed.gpu.global.add.u32 [%0], %1;" ::"l"(p), "r"(1) : "memory");
}
__device__ __forceinline__ void bulk_g2s(uint32_t dst, const void* src, uint32_t bytes, uint32_t bar) {
    asm volatile("cp.async.bulk.shared::cluster.global.mbarrier::complete_tx::bytes [%0], [%1], %2, [%3];"
                 ::"r"(dst), "l"(src), "r"(bytes), "r"(bar)
                 : "memory");
}

__global__ void __launch_bounds__(kThreads, 1)
nat_fused_kernel(const uint8_t* __restrict__ x, const uint8_t* __restrict__ wqkv, uint8_t* __restrict__ out, Scratch* g,
                 const Tables* tables, uint64_t dsc, const __grid_constant__ Maps maps) {
    const int tid = threadIdx.x, lane = tid & 31;
    const int warp = __shfl_sync(0xffffffffu, tid >> 5, 0);
    const int wg = warp >> 2, wq = warp & 3, r8 = lane >> 2, j = lane & 3;
    const int cta = blockIdx.x;
    const Work w = decode_work(cta);
    const uint32_t which = cta >= 72, job = which ? cta - 72 : 2 * cta, jhi = job / 12, jlo = job % 12;
    if (wg == 1 && wq < 3) {
#pragma unroll
        for (int r = 0; r < 3; r++)
            asm volatile("st.shared.v4.u32 [%0], {%1, %1, %1, %1};" ::"r"(s_ring + wq * kRingChunk + (r == 0 ? 84 : r == 1 ? 88 : 204) * 128 + lane * 16), "r"(0) : "memory");
        asm volatile("fence.proxy.async.shared::cta;" ::: "memory");
    }
    if (x == nullptr) return;
    const uint32_t t_start = clock_now();
    if (wg == 2) {
        if (wq < 3 && !which) m_partial(wqkv, jhi, jlo, wq, lane, (uint32_t)dsc & 1);
        asm volatile("setmaxnreg.dec.sync.aligned.u32 40;");
        if (wq < 3) {
            const uint32_t off = piece_offset(which, which ? jlo : jlo + wq, which ? 3 * jhi + wq : jhi, lane);
            asm volatile("bar.sync %0, 128;" ::"r"(5 + (off >> 31)) : "memory");
            const uint32_t par = lds_volatile(s_par);
            if (cta < 120 && wq < 2 + which) {
                float d[2][4];
                if (wq == 0) TRW(which ? 1 : 18);
                if (which) {
                    mbar_wait(bar_wop, 0);
                    if (wq == 0) TRW(2);
                    w_piece(wq, lane, d);
                } else {
                    m_reduce(wq, lane, d);
                }
                piece_store(g, par, off, which, d);
                __syncwarp();
                if (!which && lane == 0) count_up(&g->cnt[0]);
                if (wq == 0) TRW(which ? 3 : 0);
            }
            asm volatile("bar.arrive 6, 128;" ::: "memory");
            uint32_t phase = 0;
#pragma unroll 1
            for (uint32_t c = 0; c < 6; c++) {
                const uint32_t part = c * kWChunk + wq * (kWChunk / 3), img = 8 * min(c, 3u);
                mbar_wait(bar_img + 8 * c, 0);
                if (wq == 0) TRW(10 + c);
#pragma unroll 1
                while (true) {
                    uint32_t lo = ~0u;
#pragma unroll
                    for (int q = 0; q < 8; q++) lo = min(lo, lds_volatile(s_m + part + lane * 32 + (lane & 12) * 2 + q * 1024));
                    if (__all_sync(0xffffffffu, lo) || phase > 65535) break;
                    if (elect()) {
                        mbar_expect_tx(bar_redo + 8 * wq, kWChunk / 3);
                        bulk_g2s(s_m + part, g->img[0][0] + par + part, kWChunk / 3, bar_redo + 8 * wq);
                    }
                    mbar_wait(bar_redo + 8 * wq, phase++ & 1);
                }
                if (c != 3 && c != 4 && lane == 0) mbar_arrive(bar_ok + img);
            }
        } else {
            uint32_t launch = ld_relaxed(&g->cnt[1]);
            const CUtensorMap* map = &maps.m[w.sv == kPixBytes ? 2 : 0];
            if (elect()) {
#pragma unroll
                for (int i = 0; i < 20; i++) mbar_init(s_bar + 8 * i, i < 13 ? 1 : i < 18 ? 3 : 4);
                asm volatile("fence.mbarrier_init.release.cluster;" ::: "memory");
                prefetch_map(map + 1);
                expect_tx_only(bar_a, sizeof(Table));
                bulk_g2s(s_tab, &tables->t[w.step < 0], sizeof(Table), bar_a);
            }
            if (which && cta < 120 && elect()) {
                mbar_expect_tx(bar_wop, 4 * 6144);
                tma_3d(s_wv, &maps.wo, bar_wop, 0, 3 * jhi);
                tma_3d(s_wv + 3 * 6144, &maps.wv, bar_wop, 16 * jlo, 24);
            }
            int u = w.u, v = w.v;
            uint32_t wait_bar = bar_use, wait_par = 1, slot = 0;
#pragma unroll 1
            for (int step = 0; step < 7 - w.corner; step++) {
                const bool first = step == 0 || (w.corner && step == 4);
                const int row = v + 4 + (first ? -w.step : w.step) / 2, ou = origin_u(u);
                uint32_t dst = s_ring + (first ? 0 : slot), mid = s_ring + kOffMid + 512, bar = first ? bar_a : bar_b;
                mbar_wait(wait_bar, wait_par);
#pragma unroll 1
                for (int ch = (cta & 1) * kC; mid < s_m; ch += 64, dst += kRingChunk, mid += kRingChunk) {
                    if (elect()) {
                        mbar_expect_tx(bar, first ? kSlotBytes : kSlotBytes + kMidBytes);
                        tma_box(dst, map, bar, ch, ou, (cta >> 1) & 1, row);
                    }
                    if (!first) {
                        if (elect()) tma_box(mid, map + 1, bar, ch, ou, (cta >> 1) & 1, v + 6);
                        bar += 8;
                    }
                }
                if (step == 0) {
                    launch /= kGrid;
                    asm volatile("st.shared.u32 [%0], %2;\nst.shared.v2.u32 [%0 + 16], {%1, %2};" ::"r"(s_cnt), "r"((launch & 1) * 2 * kWBytes), "r"(0) : "memory");
                    if (lane == 0) count_up(&g->cnt[1]);
                    asm volatile("bar.arrive 5, 128;\nbar.arrive 3, 160;\nbar.arrive 4, 160;" ::: "memory");
#pragma unroll 1
                    for (int t = TN(6, 2000); t < (1 << 24);) {
                        if (__shfl_sync(0xffffffffu, lds_volatile(s_cnt), 0) >= (launch + 1) * kPieces) break;
                        if ((int)(clock_now() - t_start) < t) continue;
                        t += TN(7, 200);
                        if (elect()) {
                            expect_tx_only(bar_use + 8, 16);
                            bulk_g2s(s_cnt, g->cnt, 16, bar_use + 8);
                        }
                    }
                }
                if (step == 1) {
                    asm volatile("bar.sync 6, 128;" ::: "memory");
                    wait_until(t_start, TN(5, 6000));
                }
                if (step < 2) {
                    TRW(5 + 4 * step);
#pragma unroll 1
                    for (int c = 3 * step; c < 3 + 3 * step; c++)
                        if (elect()) {
                            mbar_expect_tx(bar_img + 8 * c, kWChunk);
                            bulk_g2s(s_m + c * kWChunk, g->img[launch & 1][0] + c * kWChunk, kWChunk, bar_img + 8 * c);
                        }
                }
                const bool again = w.corner && step == 3;
                wait_bar = step == 0 ? bar_img + 8 * TN(1, 1) : again ? bar_use + 8 : bar_use;
                if (!again) {
                    wait_par = slot ? 0 : step != 0;
                    slot ^= kSlotStride;
                    if (w.corner && step == 2) { u += 8; v -= 8; } else if (step) v += w.step;
                }
            }
        }
        TRDUMP();
        return;
    }
    const int order = w.step < 0 ? warp ^ 3 : warp;
    wait_until(t_start, START_TIME);
    asm volatile("setmaxnreg.inc.sync.aligned.u32 232;");
    int tu = w.u, tv = w.v + w.step * wg;
    const int du2 = w.corner ? 8 : 0, dv2 = w.corner ? 0 : 2 * w.step;
    uint32_t o0, o1;
    w.pixel_offsets(tu + r8, tv + 2 * wq, j, o0, o1);
    uint32_t fa[48];
    {
        RawX raw;
        load_raw(raw, x, o0, o1);
        asm volatile("bar.sync %0, 160;" ::"r"(3 + wg) : "memory");
        raw_to_frags(raw, 0, fa);
        pin(fa);
    }
    mbar_wait(bar_ok, 0);
    const uint64_t dA = dsc + wg * (kSlotStride >> 4), dB = dsc + (wg ^ 1) * (kSlotStride >> 4);

    float acc[96];
    uint32_t po[48];
    uint32_t c0, c1;
    asm volatile("" : "=r"(c0), "=r"(c1));
#pragma unroll
    for (int q = 0; q < 48; q++) asm volatile("" : "=r"(po[q]));
#pragma unroll 1
    for (int i = wg; i < w.ntiles; i += 2) {
        const bool first = i == 0, last = i == w.ntiles - 1;

        TRF(8 + 16 * k);
        wg_fence();
        if (!first) turn_wait(wg);
        proj_gemm(acc, fa, dsc, s_m, [&](int s) {
            if (s == 11 && !first) turn_pass(wg);
            const int n = __builtin_popcount(QSLOTS & ((1 << s) - 1));
            if (((QSLOTS >> s) & 1) && n < 12) store_one(i >= 2, out + c0, out + c1, po, n);
            if (s == 3 || s == 7) { mbar_wait(bar_ok + 2 * s + 2, 0); wg_fence(); }
        });
        __syncwarp();
        TRF(9 + 16 * k);
        uint8_t *p0 = out + c0, *p1 = out + c1;
        c0 = o0; c1 = o1;
        w.pixel_offsets(tu + du2 + r8, tv + dv2 + 2 * wq, j, o0, o1);
        if (i + 2 >= w.ntiles) o0 = o1 = 0;
        wg_wait<0>();
        pin(acc);
        TR(11 + 16 * k); TRT(80 + k);
#pragma unroll
        for (int n = __builtin_popcount(QSLOTS); n < 12 - __builtin_popcount(ASLOTS) - __builtin_popcount(BSLOTS); n++) store_one(i >= 2, p0, p1, po, n);
        acc_to_frags(acc, fa);
        pin(fa);

        float sA[44], sE[16], sB[44];
        RawX nxt;
        if (!first) turn_wait(wg);
        mbar_wait(bar_a, w.corner ? i >> 1 : 0);
        if (i == 0) TR(12);
        wg_fence();
#pragma unroll
        for (int s = 0; s < 12; s++) {
            if (s == 0) wgmma_n88<true>(sA, fa[4 * s], fa[4 * s + 1], fa[4 * s + 2], fa[4 * s + 3], desc_at(dA, (s >> 2) * kRingChunk + (s & 3) * 32));
            else wgmma_n88<false>(sA, fa[4 * s], fa[4 * s + 1], fa[4 * s + 2], fa[4 * s + 3], desc_at(dA, (s >> 2) * kRingChunk + (s & 3) * 32));
            if (s == 11) { wg_commit(); if (!first) turn_pass(wg); }
            if ((ASLOTS >> s) & 1) store_one(i >= 2, p0, p1, po, 12 - __builtin_popcount(BSLOTS) - __builtin_popcount(ASLOTS >> s));
        }
#pragma unroll
        for (int s = 12; s < 16; s++)
            if ((ASLOTS >> s) & 1) store_one(i >= 2, p0, p1, po, 12 - __builtin_popcount(BSLOTS) - __builtin_popcount(ASLOTS >> s));
        TRF(12 + 16 * k);
        const int vq = tv + 2 * wq;
        const uint4 tabu = lds128(s_tab + offsetof(Table, u) + (window_start(tu + r8) - origin_u(tu)) * 64 + j * 16);
        const uint4 tabv = lds128(s_tab + offsetof(Table, v) + (window_start(vq) + window_start(vq + 1) - 2 * tv) * 64 + j * 16);
        const uint4 route = lds128(s_tab + lane * 16);
        if (LDGPOS == 0) load_raw(nxt, x, o0, o1);
        float v0[14], v1[14];
#pragma unroll
        for (int b = 0; b < 14; b++) v0[b] = v1[b] = __int_as_float(0xff800000);
        wg_wait<0>();
        pin(sA);
        gather_outer(sA, tabu.x, tabv.x, v0, v1);
        pin(v0); pin(v1);
        if (!first) turn_wait(wg);
#pragma unroll
        for (int c = 0; c < 3; c++) {
            mbar_wait(bar_b + 8 * c, wg);
            if (i == 0 && c != 1) TR(13 + c);
            wg_fence();
#pragma unroll
            for (int s = 4 * c; s < 4 * c + 4; s++) {
                if (s == 0) wgmma_n88<true>(sB, fa[4 * s], fa[4 * s + 1], fa[4 * s + 2], fa[4 * s + 3], desc_at(dB, c * kRingChunk + (s & 3) * 32));
                else wgmma_n88<false>(sB, fa[4 * s], fa[4 * s + 1], fa[4 * s + 2], fa[4 * s + 3], desc_at(dB, c * kRingChunk + (s & 3) * 32));
                if ((BSLOTS >> s) & 1) store_one(i >= 2, p0, p1, po, 12 - __builtin_popcount(BSLOTS >> s));
            }
        }
        wg_commit();
#pragma unroll
        for (int s = 0; s < 12; s++)
            if (s == 0) wgmma_n32<true>(sE, fa[4 * s], fa[4 * s + 1], fa[4 * s + 2], fa[4 * s + 3], desc_at(dsc, kOffMid + (s >> 2) * kRingChunk + (s & 3) * 32));
            else wgmma_n32<false>(sE, fa[4 * s], fa[4 * s + 1], fa[4 * s + 2], fa[4 * s + 3], desc_at(dsc, kOffMid + (s >> 2) * kRingChunk + (s & 3) * 32));
        wg_commit();
        if (!last) turn_pass(wg);
        TRF(13 + 16 * k);
        wg_wait<1>();
        pin(sB);
        gather_outer(sB, tabu.w, tabv.y, v0, v1);
        wg_wait<0>();
        pin(sE);
        TRF(14 + 16 * k);
        gather_mid(sE, tabu.w, tabv.z, v0, v1);
        const float m0 = quad_max(tree_max(v0)), m1 = quad_max(tree_max(v1));

        uint32_t y[14], pa[12], pb[12];
        exp_route<0, 14>(v0, v1, m0, m1, route, (j & 1) == 0, y);
        float s0 = tree_sum(v0), s1 = tree_sum(v1);
        asm volatile("" : "+f"(s0), "+f"(s1));
        unfold<0, 0, 6>(y, tabv.w, pa);
        if (!last) turn_wait(wg + (y[0] >> 31));
        TRF(15 + 16 * k + (y[13] >> 31));
        wg_fence();
        wgmma_sp_n192_tb<true, 0>(acc, pa[0], pa[1], pa[2], pa[3], desc_at(dA, kToV), tabu.y);
        wgmma_sp_n192_tb<false, 1>(acc, pa[4], pa[5], pa[6], pa[7], desc_at(dA, kToV + 4096), tabu.y);
        wgmma_sp_n192_tb<false, 0>(acc, pa[8], pa[9], pa[10], pa[11], desc_at(dA, kToV + 8192), tabu.z);
        wgmma_sp_n192_tb<false, 1>(acc, y[10], y[11], y[12], y[13], desc_at(dsc, kToV + kOffMid), tabu.z);
        wg_commit();
        unfold<8, 0, 6>(y, tabv.w, pb);
        wg_fence();
        wgmma_sp_n192_tb<false, 0>(acc, pb[0], pb[1], pb[2], pb[3], desc_at(dB, kToV), tabu.y);
        wgmma_sp_n192_tb<false, 1>(acc, pb[4], pb[5], pb[6], pb[7], desc_at(dB, kToV + 4096), tabu.y);
        wgmma_sp_n192_tb<false, 0>(acc, pb[8], pb[9], pb[10], pb[11], desc_at(dB, kToV + 8192), tabu.z);
        wg_commit();
        if (!last) turn_pass(wg);
        TRF(16 + 16 * k);
        if (LDGPOS == 3) load_raw(nxt, x, o0, o1);
        wg_wait<1>();
        if (lane == 0) mbar_arrive(bar_use);
        TRF(17 + 16 * k);
        mbar_wait(bar_ok + 24, 0);
        wg_wait<0>();
        if (lane == 0) mbar_arrive(bar_use + 8);
        pin(acc);
        TR(18 + 16 * k);

        acc_to_frags(acc, po);
        pin(po);
        if (!last) turn_wait(wg);
        wg_fence();
        proj_gemm(acc, po, dsc, s_wv, [](int) {});
        if (!last) turn_pass(wg);
        TRF(19 + 16 * k);
        const uint32_t zero = lds_volatile(s_late);
        const float inv0 = rcp(quad_sum(s0 + __uint_as_float(zero))), inv1 = rcp(quad_sum(s1 + __uint_as_float(zero)));
        raw_to_frags(nxt, zero, fa);
        pin(fa);
#pragma unroll
        for (int q = 0; q < 48; q += 4) keep(wqkv == nullptr, fa[q], fa[q + 1], fa[q + 2], fa[q + 3]);
        keep(wqkv == nullptr, __float_as_uint(inv0), __float_as_uint(inv1), zero, lane);
        TRF(20 + 16 * k);
        tu += du2; tv += dv2;
        wg_wait<0>();
        pin(acc);
        TR(21 + 16 * k);
#pragma unroll
        for (int q = 0; q < 96; q++) acc[q] *= q & 2 ? inv1 : inv0;
        pack_out(acc, po);
#pragma unroll
        for (int n = 0; n < 12; n++) store_one<false>(i + 2 >= w.ntiles, out + c0, out + c1, po, n);
        pin(po);
    }
    TR(7);
    TRG(1);
    TRDUMP();
}

typedef CUresult (*EncodeTiledFn)(CUtensorMap*, CUtensorMapDataType, cuuint32_t, void*, const cuuint64_t*, const cuuint64_t*,
                                  const cuuint32_t*, const cuuint32_t*, CUtensorMapInterleave, CUtensorMapSwizzle,
                                  CUtensorMapL2promotion, CUtensorMapFloatOOBfill);

bool make_maps(EncodeTiledFn fn, Maps* maps, void* x, void* wqkv, void* wo) {
    const cuuint64_t pix2 = 2 * kPixBytes, row = (cuuint64_t)kHW * kPixBytes;
    const cuuint32_t estr[5] = {1, 1, 1, 1, 1};
    bool ok = true;
    for (int tr = 0; tr < 2; tr++)
        for (int b = 0; b < 2; b++) {
            const cuuint64_t su = tr ? 2 * row : pix2, sv = tr ? pix2 : 2 * row;
            const cuuint64_t dims[5] = {2 * kC, 2, 105, 2, 112};
            const cuuint64_t strides[4] = {7 * su, su, row, sv};
            const cuuint32_t box[5] = {64, 2, 7, 1, b ? 2u : 6u};
            ok = ok && fn(&maps->m[2 * tr + b], CU_TENSOR_MAP_DATA_TYPE_BFLOAT16, 5, x, dims, strides, box, estr,
                          CU_TENSOR_MAP_INTERLEAVE_NONE, CU_TENSOR_MAP_SWIZZLE_128B, CU_TENSOR_MAP_L2_PROMOTION_L2_128B,
                          CU_TENSOR_MAP_FLOAT_OOB_FILL_NONE) == CUDA_SUCCESS;
        }
    for (int b = 0; b < 2; b++) {
        const cuuint64_t dims[3] = {16, kC, b ? 36u : 12u}, strides[2] = {(b ? 3u : 1u) * kPixBytes, 32};
        const cuuint32_t box[3] = {16, b ? 16u : 192u, b ? 12u : 3u};
        ok = ok && fn(b ? &maps->wv : &maps->wo, CU_TENSOR_MAP_DATA_TYPE_BFLOAT16, 3, b ? wqkv : wo, dims, strides, box, estr,
                      CU_TENSOR_MAP_INTERLEAVE_NONE, CU_TENSOR_MAP_SWIZZLE_32B, CU_TENSOR_MAP_L2_PROMOTION_L2_128B,
                      CU_TENSOR_MAP_FLOAT_OOB_FILL_NONE) == CUDA_SUCCESS;
    }
    return ok;
}

}

extern "C" void kernel_launch(void* const* d_in, const int* in_sizes, int n_in, void* d_out, int out_size) {
    static EncodeTiledFn encode = nullptr;
    static Scratch* scratch = nullptr;
    static Tables* tables = nullptr;
    if (!encode) {
        int dev = 0, reserved = 0;
        cudaFuncAttributes attr;
        cudaGetDevice(&dev);
        cudaDeviceGetAttribute(&reserved, cudaDevAttrReservedSharedMemoryPerBlock, dev);
        cudaFuncGetAttributes(&attr, nat_fused_kernel);
        if (reserved != (int)kSmemBase || attr.sharedSizeBytes != 0) return;
        cudaGetSymbolAddress((void**)&scratch, g_scratch);
        cudaGetSymbolAddress((void**)&tables, g_tables);
        void* fn = nullptr;
        cudaDriverEntryPointQueryResult st;
        cudaGetDriverEntryPoint("cuTensorMapEncodeTiled", &fn, cudaEnableDefault, &st);
        encode = (EncodeTiledFn)fn;
        cudaFuncSetAttribute(nat_fused_kernel, cudaFuncAttributeMaxDynamicSharedMemorySize, kSmemBytes);
    }
    Maps maps;
    if (!encode || !make_maps(encode, &maps, d_in[0], d_in[1], d_in[2])) return;
    nat_fused_kernel<<<kGrid, kThreads, kSmemBytes>>>((const uint8_t*)d_in[0], (const uint8_t*)d_in[1], (uint8_t*)d_out, scratch, tables, kDescRing, maps);
}
```

```cpp
#include <cuda_runtime.h>
#include <cuda_bf16.h>
#include <cuda.h>
#include <stdint.h>
#include <type_traits>
#include <stdlib.h>
#include <stddef.h>

#define LDGPOS 0
#define INPLACE 2
#define KEEPFA 1
#define ASLOTS 0x3800
#define BSLOTS 0x6
#define QSLOTS 0x78a
#define OSPLIT 3
#define NAP 40
#define NAP1 NAP
#define NAP0 0
#define WUNROLL 2

namespace {

constexpr int kC          = 192;
constexpr int kHW         = 224;
constexpr int kPixBytes   = kC * 2;
constexpr int kSlotBytes  = 84 * 128;
constexpr int kMidBytes   = 28 * 128;
constexpr int kOffMid     = 88 * 128;
constexpr int kSlotStride = 120 * 128;
constexpr int kRingChunk  = 208 * 128;
constexpr int kWChunk     = 192 * 128;
constexpr int kWBytes     = 3 * kWChunk;
constexpr uint32_t kSmemBase = 1024;
constexpr uint32_t s_ring = kSmemBase, s_m = s_ring + 3 * kRingChunk, s_wv = s_m + kWBytes, s_bar = s_wv + kWBytes;
constexpr uint32_t bar_b = s_bar, bar_img = s_bar + 24, bar_redo = s_bar + 72, bar_wop = s_bar + 96, bar_a = s_bar + 104,
                   bar_ok = s_bar + 112, bar_use = s_bar + 144;
constexpr uint32_t s_cnt = s_bar + 160, s_par = s_bar + 176, s_late = s_bar + 180, s_tab = s_bar + 256, s_trace = s_tab + 2048;
constexpr int kSmemBytes  = s_trace + 2048 - kSmemBase;
constexpr int kThreads    = 384, kWUnroll = WUNROLL;
constexpr int kGrid       = 132;
constexpr int kPieces     = 144;
constexpr float kScaleLog2e = 0.07216878364870322f * 1.4426950408889634f;

struct Maps {
    CUtensorMap m[4];
    CUtensorMap wo, wv;
};
#define TN(i, dflt) (dflt)
#define START_TIME (wg ? 1900 + 500 * order : which ? 100 + 500 * order : order ? 2100 + 200 * order : 400)

struct Scratch {
    uint8_t img[2][2][kWBytes];
    uint32_t cnt[4];
};
__device__ __align__(1024) Scratch g_scratch;

struct Table {
    uint32_t route[32][4];
    uint32_t u[8][4][4];
    uint32_t v[16][4][4];
};
struct Tables { Table t[2]; };
constexpr Tables make_tables() {
    Tables r = {};
    for (int rev = 0; rev < 2; rev++)
        for (int j = 0; j < 4; j++) {
            Table& t = r.t[rev];
            for (int q = 0; q < 8; q++) {
                uint32_t* e = t.route[4 * q + j];
                e[0] = 4 * q + 2 * (j & 1) + (j >> 1); e[1] = e[0] ^ 1;
                e[2] = j < 2 ? 0x5410u : 0x1054u; e[3] = e[2] + 0x2222u;
                e = t.u[q][j];
                for (int n = 0; n < 7; n++) e[0] |= ((n + j) % 7 < q ? 1u : 0u) << n;
                e[3] = e[0];
                for (int k = 0; k < 2; k++) {
                    const int step = 2 * k + (j >> 1), p0 = (step < 3 ? 16 * step : 40) + 8 * (j & 1);
                    uint32_t m = 0x8888u;
                    for (int n = 0; n < 8; n++) m |= ((p0 + n) % 7 < q ? 1u : 0u) << (2 * n);
                    e[1 + k] = m * 0x10001u;
                }
            }
            for (int sum = 0; sum < 15; sum++) {
                uint32_t* e = t.v[sum][j];
                for (int row = 0; row < 2; row++)
                    for (int b = 0; b < 14; b++) {
                        const int off = (sum + row) / 2, p = 4 * b + j;
                        const uint32_t bit = 1u << (2 * b + row);
                        if (p < 42 && p >= 7 * off) e[rev] |= bit;
                        if (p < 7 * off - 7) e[1 - rev] |= bit;
                        if (p >= 42 && p >= 7 * off && p < 7 * off + 49) e[2] |= bit;
                    }
                for (int n = 0; n < 6; n++)
                    if (8 * n + 2 * j < 42) e[3] |= 1u << (n + ((8 * n + 2 * j >= 7 * (sum / 2 & ~1)) != rev ? 0 : 8));
            }
        }
    return r;
}
__device__ __align__(128) const Tables g_tables = make_tables();

#define WO4(i) "=f"(d[i]), "=f"(d[i + 1]), "=f"(d[i + 2]), "=f"(d[i + 3])
#define RW4(i) "+f"(d[i]), "+f"(d[i + 1]), "+f"(d[i + 2]), "+f"(d[i + 3])

template <bool FIRST>
__device__ __forceinline__ void wgmma_n192(float (&d)[96], uint32_t a0, uint32_t a1, uint32_t a2, uint32_t a3, uint64_t descb) {
    if constexpr (FIRST) {
        asm volatile(
            "wgmma.mma_async.sync.aligned.m64n192k16.f32.bf16.bf16 "
            "{%0, %1, %2, %3, %4, %5, %6, %7, %8, %9, %10, %11, %12, %13, %14, %15, %16, %17, %18, %19, %20, %21, %22, %23, "
            "%24, %25, %26, %27, %28, %29, %30, %31, %32, %33, %34, %35, %36, %37, %38, %39, %40, %41, %42, %43, %44, %45, %46, %47, "
            "%48, %49, %50, %51, %52, %53, %54, %55, %56, %57, %58, %59, %60, %61, %62, %63, %64, %65, %66, %67, %68, %69, %70, %71, "
            "%72, %73, %74, %75, %76, %77, %78, %79, %80, %81, %82, %83, %84, %85, %86, %87, %88, %89, %90, %91, %92, %93, %94, %95}, "
            "{%96, %97, %98, %99}, %100, 0, 1, 1, 0;"
            : WO4(0), WO4(4), WO4(8), WO4(12), WO4(16), WO4(20), WO4(24), WO4(28), WO4(32), WO4(36), WO4(40), WO4(44),
              WO4(48), WO4(52), WO4(56), WO4(60), WO4(64), WO4(68), WO4(72), WO4(76), WO4(80), WO4(84), WO4(88), WO4(92)
            : "r"(a0), "r"(a1), "r"(a2), "r"(a3), "l"(descb));
    } else {
        asm volatile(
            "wgmma.mma_async.sync.aligned.m64n192k16.f32.bf16.bf16 "
            "{%0, %1, %2, %3, %4, %5, %6, %7, %8, %9, %10, %11, %12, %13, %14, %15, %16, %17, %18, %19, %20, %21, %22, %23, "
            "%24, %25, %26, %27, %28, %29, %30, %31, %32, %33, %34, %35, %36, %37, %38, %39, %40, %41, %42, %43, %44, %45, %46, %47, "
            "%48, %49, %50, %51, %52, %53, %54, %55, %56, %57, %58, %59, %60, %61, %62, %63, %64, %65, %66, %67, %68, %69, %70, %71, "
            "%72, %73, %74, %75, %76, %77, %78, %79, %80, %81, %82, %83, %84, %85, %86, %87, %88, %89, %90, %91, %92, %93, %94, %95}, "
            "{%96, %97, %98, %99}, %100, 1, 1, 1, 0;"
            : RW4(0), RW4(4), RW4(8), RW4(12), RW4(16), RW4(20), RW4(24), RW4(28), RW4(32), RW4(36), RW4(40), RW4(44),
              RW4(48), RW4(52), RW4(56), RW4(60), RW4(64), RW4(68), RW4(72), RW4(76), RW4(80), RW4(84), RW4(88), RW4(92)
            : "r"(a0), "r"(a1), "r"(a2), "r"(a3), "l"(descb));
    }
}

template <bool FIRST>
__device__ __forceinline__ void wgmma_n88(float (&d)[44], uint32_t a0, uint32_t a1, uint32_t a2, uint32_t a3, uint64_t descb) {
    if constexpr (FIRST) {
        asm volatile(
            "wgmma.mma_async.sync.aligned.m64n88k16.f32.bf16.bf16 "
            "{%0, %1, %2, %3, %4, %5, %6, %7, %8, %9, %10, %11, %12, %13, %14, %15, %16, %17, %18, %19, %20, %21, %22, %23, "
            "%24, %25, %26, %27, %28, %29, %30, %31, %32, %33, %34, %35, %36, %37, %38, %39, %40, %41, %42, %43}, "
            "{%44, %45, %46, %47}, %48, 0, 1, 1, 0;"
            : WO4(0), WO4(4), WO4(8), WO4(12), WO4(16), WO4(20), WO4(24), WO4(28), WO4(32), WO4(36), WO4(40)
            : "r"(a0), "r"(a1), "r"(a2), "r"(a3), "l"(descb));
    } else {
        asm volatile(
            "wgmma.mma_async.sync.aligned.m64n88k16.f32.bf16.bf16 "
            "{%0, %1, %2, %3, %4, %5, %6, %7, %8, %9, %10, %11, %12, %13, %14, %15, %16, %17, %18, %19, %20, %21, %22, %23, "
            "%24, %25, %26, %27, %28, %29, %30, %31, %32, %33, %34, %35, %36, %37, %38, %39, %40, %41, %42, %43}, "
            "{%44, %45, %46, %47}, %48, 1, 1, 1, 0;"
            : RW4(0), RW4(4), RW4(8), RW4(12), RW4(16), RW4(20), RW4(24), RW4(28), RW4(32), RW4(36), RW4(40)
            : "r"(a0), "r"(a1), "r"(a2), "r"(a3), "l"(descb));
    }
}

template <bool FIRST>
__device__ __forceinline__ void wgmma_n32(float (&d)[16], uint32_t a0, uint32_t a1, uint32_t a2, uint32_t a3, uint64_t descb) {
    if constexpr (FIRST) {
        asm volatile(
            "wgmma.mma_async.sync.aligned.m64n32k16.f32.bf16.bf16 "
            "{%0, %1, %2, %3, %4, %5, %6, %7, %8, %9, %10, %11, %12, %13, %14, %15}, "
            "{%16, %17, %18, %19}, %20, 0, 1, 1, 0;"
            : WO4(0), WO4(4), WO4(8), WO4(12)
            : "r"(a0), "r"(a1), "r"(a2), "r"(a3), "l"(descb));
    } else {
        asm volatile(
            "wgmma.mma_async.sync.aligned.m64n32k16.f32.bf16.bf16 "
            "{%0, %1, %2, %3, %4, %5, %6, %7, %8, %9, %10, %11, %12, %13, %14, %15}, "
            "{%16, %17, %18, %19}, %20, 1, 1, 1, 0;"
            : RW4(0), RW4(4), RW4(8), RW4(12)
            : "r"(a0), "r"(a1), "r"(a2), "r"(a3), "l"(descb));
    }
}

template <bool FIRST, int SEL>
__device__ __forceinline__ void wgmma_sp_n192_tb(float (&d)[96], uint32_t a0, uint32_t a1, uint32_t a2, uint32_t a3, uint64_t descb, uint32_t meta) {
    if constexpr (FIRST) {
        asm volatile(
            "wgmma.mma_async.sp.sync.aligned.m64n192k32.f32.bf16.bf16 "
            "{%0, %1, %2, %3, %4, %5, %6, %7, %8, %9, %10, %11, %12, %13, %14, %15, %16, %17, %18, %19, %20, %21, %22, %23, "
            "%24, %25, %26, %27, %28, %29, %30, %31, %32, %33, %34, %35, %36, %37, %38, %39, %40, %41, %42, %43, %44, %45, %46, %47, "
            "%48, %49, %50, %51, %52, %53, %54, %55, %56, %57, %58, %59, %60, %61, %62, %63, %64, %65, %66, %67, %68, %69, %70, %71, "
            "%72, %73, %74, %75, %76, %77, %78, %79, %80, %81, %82, %83, %84, %85, %86, %87, %88, %89, %90, %91, %92, %93, %94, %95}, "
            "{%96, %97, %98, %99}, %100, %101, %102, 0, 1, 1, 1;"
            : WO4(0), WO4(4), WO4(8), WO4(12), WO4(16), WO4(20), WO4(24), WO4(28), WO4(32), WO4(36), WO4(40), WO4(44),
              WO4(48), WO4(52), WO4(56), WO4(60), WO4(64), WO4(68), WO4(72), WO4(76), WO4(80), WO4(84), WO4(88), WO4(92)
            : "r"(a0), "r"(a1), "r"(a2), "r"(a3), "l"(descb), "r"(meta), "n"(SEL));
    } else {
        asm volatile(
            "wgmma.mma_async.sp.sync.aligned.m64n192k32.f32.bf16.bf16 "
            "{%0, %1, %2, %3, %4, %5, %6, %7, %8, %9, %10, %11, %12, %13, %14, %15, %16, %17, %18, %19, %20, %21, %22, %23, "
            "%24, %25, %26, %27, %28, %29, %30, %31, %32, %33, %34, %35, %36, %37, %38, %39, %40, %41, %42, %43, %44, %45, %46, %47, "
            "%48, %49, %50, %51, %52, %53, %54, %55, %56, %57, %58, %59, %60, %61, %62, %63, %64, %65, %66, %67, %68, %69, %70, %71, "
            "%72, %73, %74, %75, %76, %77, %78, %79, %80, %81, %82, %83, %84, %85, %86, %87, %88, %89, %90, %91, %92, %93, %94, %95}, "
            "{%96, %97, %98, %99}, %100, %101, %102, 1, 1, 1, 1;"
            : RW4(0), RW4(4), RW4(8), RW4(12), RW4(16), RW4(20), RW4(24), RW4(28), RW4(32), RW4(36), RW4(40), RW4(44),
              RW4(48), RW4(52), RW4(56), RW4(60), RW4(64), RW4(68), RW4(72), RW4(76), RW4(80), RW4(84), RW4(88), RW4(92)
            : "r"(a0), "r"(a1), "r"(a2), "r"(a3), "l"(descb), "r"(meta), "n"(SEL));
    }
}

#define TR(slot)
#define TRT(slot)
#define TRF(slot)
#define TRW(slot)
#define TRG(slot)
#define TRDUMP()

__device__ __forceinline__ void wg_fence() { asm volatile("wgmma.fence.sync.aligned;" ::: "memory"); }
__device__ __forceinline__ void wg_commit() { asm volatile("wgmma.commit_group.sync.aligned;" ::: "memory"); }
template <int N>
__device__ __forceinline__ void wg_wait() { asm volatile("wgmma.wait_group.sync.aligned %0;" ::"n"(N) : "memory"); }

template <int N>
__device__ __forceinline__ void pin(float (&d)[N]) {
#pragma unroll
    for (int i = 0; i < N; i++) asm volatile("" : "+f"(d[i])::"memory");
}
template <int N>
__device__ __forceinline__ void pin(uint32_t (&d)[N]) {
#pragma unroll
    for (int i = 0; i < N; i++) asm volatile("" : "+r"(d[i])::"memory");
}

constexpr uint64_t kDescRing = ((uint64_t)((1u << 30) | (1024u >> 4)) << 32) | (1u << 16) | (s_ring >> 4);
constexpr uint32_t kToV = ((kRingChunk >> 4) - 1) << 20;
__device__ __forceinline__ uint64_t desc_at(uint64_t base, uint32_t byte_off) {
    uint64_t d;
    asm volatile("add.s64 %0, %1, %2;" : "=l"(d) : "l"(base), "l"((uint64_t)(byte_off >> 4)));
    return d;
}

__device__ __forceinline__ void mbar_init(uint32_t bar, uint32_t count) {
    asm volatile("mbarrier.init.shared::cta.b64 [%0], %1;" ::"r"(bar), "r"(count) : "memory");
}
__device__ __forceinline__ void mbar_expect_tx(uint32_t bar, uint32_t bytes) {
    asm volatile("mbarrier.arrive.expect_tx.shared::cta.b64 _, [%0], %1;" ::"r"(bar), "r"(bytes) : "memory");
}
__device__ __forceinline__ void expect_tx_only(uint32_t bar, uint32_t bytes) {
    asm volatile("mbarrier.expect_tx.relaxed.cta.shared::cta.b64 [%0], %1;" ::"r"(bar), "r"(bytes) : "memory");
}
__device__ __forceinline__ void mbar_arrive(uint32_t bar) {
    asm volatile("mbarrier.arrive.shared::cta.b64 _, [%0];" ::"r"(bar) : "memory");
}
__device__ __forceinline__ void mbar_wait(uint32_t bar, uint32_t parity) {
    asm volatile(
        "{\n.reg .pred p;\n"
        "W: mbarrier.try_wait.parity.shared::cta.b64 p, [%0], %1;\n"
        "@!p bra W;\n}\n"
        ::"r"(bar), "r"(parity) : "memory");
}
__device__ __forceinline__ uint32_t clock_now() {
    uint32_t c;
    asm volatile("mov.u32 %0, %%clock;" : "=r"(c)::"memory");
    return c;
}
__device__ __forceinline__ void wait_until(uint32_t t0, int t) {
    if (t == 0) return;
    while ((int)(clock_now() - t0) < t) {}
}
__device__ __forceinline__ bool elect() {
    uint32_t ok;
    asm volatile("{\n.reg .pred p;\nelect.sync _|p, 0xffffffff;\nselp.u32 %0, 1, 0, p;\n}\n" : "=r"(ok));
    return ok != 0;
}
__device__ __forceinline__ void turn_wait(int wg) { asm volatile("bar.sync %0, 256;" ::"r"(1 + wg) : "memory"); }
__device__ __forceinline__ void turn_pass(int wg) { asm volatile("bar.arrive %0, 256;" ::"r"(2 - wg) : "memory"); }

__device__ __forceinline__ void tma_box(uint32_t dst, const CUtensorMap* map, uint32_t bar, int c0, int c2, int c3, int c4) {
    asm volatile(
        "cp.async.bulk.tensor.5d.shared::cluster.global.mbarrier::complete_tx::bytes [%0], [%1, {%3, %4, %5, %6, %7}], [%2];"
        ::"r"(dst), "l"(map), "r"(bar), "r"(c0), "r"(0), "r"(c2), "r"(c3), "r"(c4)
        : "memory");
}
__device__ __forceinline__ void tma_3d(uint32_t dst, const CUtensorMap* map, uint32_t bar, int c1, int c2) {
    asm volatile("cp.async.bulk.tensor.3d.shared::cluster.global.mbarrier::complete_tx::bytes [%0], [%1, {%3, %4, %5}], [%2];"
                 ::"r"(dst), "l"(map), "r"(bar), "r"(0), "r"(c1), "r"(c2)
                 : "memory");
}
__device__ __forceinline__ void prefetch_map(const CUtensorMap* map) {
    asm volatile("prefetch.tensormap [%0];" ::"l"(map) : "memory");
}
__device__ __forceinline__ uint4 ldg(const void* p) {
    uint4 v;
    asm volatile("ld.global.v4.u32 {%0, %1, %2, %3}, [%4];" : "=r"(v.x), "=r"(v.y), "=r"(v.z), "=r"(v.w) : "l"(p) : "memory");
    return v;
}
__device__ __forceinline__ uint32_t pack_bf16(float lo, float hi) {
    uint32_t r;
    asm("cvt.rn.bf16x2.f32 %0, %1, %2;" : "=r"(r) : "f"(hi), "f"(lo));
    return r;
}
__device__ __forceinline__ float ex2(float x) {
    float y;
    asm("ex2.approx.ftz.f32 %0, %1;" : "=f"(y) : "f"(x));
    return y;
}
__device__ __forceinline__ float rcp(float x) {
    float y;
    asm("rcp.approx.ftz.f32 %0, %1;" : "=f"(y) : "f"(x));
    return y;
}
__device__ __forceinline__ void mma16816(float (&d)[4], uint32_t a0, uint32_t a1, uint32_t a2, uint32_t a3, uint32_t b0, uint32_t b1) {
    asm volatile("mma.sync.aligned.m16n8k16.row.col.f32.bf16.bf16.f32 {%0, %1, %2, %3}, {%4, %5, %6, %7}, {%8, %9}, {%0, %1, %2, %3};"
                 : "+f"(d[0]), "+f"(d[1]), "+f"(d[2]), "+f"(d[3])
                 : "r"(a0), "r"(a1), "r"(a2), "r"(a3), "r"(b0), "r"(b1));
}
__device__ __forceinline__ uint4 lds128(uint32_t addr) {
    uint4 v;
    asm volatile("ld.volatile.shared.v4.u32 {%0, %1, %2, %3}, [%4];" : "=r"(v.x), "=r"(v.y), "=r"(v.z), "=r"(v.w) : "r"(addr) : "memory");
    return v;
}
__device__ __forceinline__ uint32_t lds_volatile(uint32_t addr) {
    uint32_t v;
    asm volatile("ld.volatile.shared.u32 %0, [%1];" : "=r"(v) : "r"(addr) : "memory");
    return v;
}

__device__ __forceinline__ int window_start(int n) { return min(max(n, 0), 105); }
__device__ __forceinline__ int origin_u(int u) { return min(max(u, 0), 98); }

struct Work {
    int u, v;
    int step;
    uint32_t su, sv;
    uint32_t base;
    bool corner;
    int ntiles;
    __device__ __forceinline__ void pixel_offsets(int qu, int qv, int j, uint32_t& o0, uint32_t& o1) const {
        const uint32_t b = (qu + window_start(qu)) * su + j * 16 + base;
        o0 = b + (qv + window_start(qv)) * sv;
        o1 = b + (qv + 1 + window_start(qv + 1)) * sv;
    }
};

__device__ __forceinline__ Work decode_work(int c) {
    Work w;
    const bool transposed = (c >> 4) == 7;
    const int px = 6 * (c & 1), py = 3 * (c & 2);
    w.corner = c >= 128;
    w.step = 8 - 4 * (c & 4);
    w.u = (c < 112 ? c & ~7 : 96 + (c & 8)) + (transposed ? py : px) - 6;
    w.v = (w.corner ? 96 : 48 - 2 * (c & 4)) + (transposed ? px : py) - 6;
    w.su = transposed ? kHW * kPixBytes : kPixBytes;
    w.sv = transposed ? kPixBytes : kHW * kPixBytes;
    w.base = px * (kPixBytes / 6) + py * (kHW * kPixBytes / 6) + 6 * (kHW + 1) * kPixBytes;
    w.ntiles = w.corner ? 4 : 6;
    return w;
}

struct RawX { uint4 a[6], b[6]; };
__device__ __forceinline__ void load_raw(RawX& r, const uint8_t* base, uint32_t o0, uint32_t o1) {
    __syncwarp();
#pragma unroll
    for (int c = 0; c < 6; c++) { r.a[c] = ldg(base + o0 + c * 64); r.b[c] = ldg(base + o1 + c * 64); }
    __syncwarp();
}
__device__ __forceinline__ void raw_to_frags(const RawX& r, uint32_t zero, uint32_t (&f)[48]) {
#pragma unroll
    for (int c = 0; c < 6; c++) {
        asm volatile("{\n.reg .b32 t, u;\nadd.u32 t, %4, %8;\nadd.u32 u, %5, %8;\nxor.b32 %0, %6, %8;\nxor.b32 %1, %7, %8;\n"
                     "xor.b32 %2, t, %8;\nxor.b32 %3, u, %8;\n}\n"
                     : "=&r"(f[8 * c + 1]), "=&r"(f[8 * c + 3]), "=&r"(f[8 * c + 4]), "=&r"(f[8 * c + 6])
                     : "r"(r.a[c].y), "r"(r.a[c].w), "r"(r.b[c].x), "r"(r.b[c].z), "r"(zero));
        f[8 * c + 0] = r.a[c].x; f[8 * c + 2] = r.a[c].z; f[8 * c + 5] = r.b[c].y; f[8 * c + 7] = r.b[c].w;
    }
}
__device__ __forceinline__ void acc_to_frags(const float (&d)[96], uint32_t (&f)[48]) {
#pragma unroll
    for (int i = 0; i < 48; i++) f[i] = pack_bf16(d[2 * i], d[2 * i + 1]);
}

template <class F>
__device__ __forceinline__ void proj_gemm(float (&d)[96], const uint32_t (&a)[48], uint64_t dsc, uint32_t img, F after) {
#pragma unroll
    for (int s = 0; s < 12; s++) {
        if (s == 0) wgmma_n192<true>(d, a[4 * s], a[4 * s + 1], a[4 * s + 2], a[4 * s + 3], desc_at(dsc, img - s_ring + (s >> 2) * kWChunk + (s & 3) * 32));
        else wgmma_n192<false>(d, a[4 * s], a[4 * s + 1], a[4 * s + 2], a[4 * s + 3], desc_at(dsc, img - s_ring + (s >> 2) * kWChunk + (s & 3) * 32));
        if (s == 11) wg_commit();
        after(s);
    }
}
__device__ __forceinline__ void pack_out(const float (&acc)[96], uint32_t (&po)[48]) {
#pragma unroll
    for (int g = 0; g < 6; g++)
#pragma unroll
        for (int q = 0; q < 4; q++) {
            po[8 * g + q] = pack_bf16(acc[16 * g + 4 * q], acc[16 * g + 4 * q + 1]);
            po[8 * g + 4 + q] = pack_bf16(acc[16 * g + 4 * q + 2], acc[16 * g + 4 * q + 3]);
        }
}
template <bool PINNED = true>
__device__ __forceinline__ void store_one(bool on, uint8_t* p0, uint8_t* p1, const uint32_t (&po)[48], int n) {
    if (PINNED) __syncwarp();
    asm volatile("{\n.reg .pred p;\nsetp.ne.u32 p, %5, 0;\n@p st.global.v4.u32 [%0], {%1, %2, %3, %4};\n}\n"
                 ::"l"(((n & 1) ? p1 : p0) + (n >> 1) * 64), "r"(po[4 * n]), "r"(po[4 * n + 1]), "r"(po[4 * n + 2]), "r"(po[4 * n + 3]), "r"((uint32_t)on) : "memory");
}

template <int N>
__device__ __forceinline__ float tree_max(const float (&v)[N]) {
    float t[N];
#pragma unroll
    for (int i = 0; i < N; i++) t[i] = v[i];
#pragma unroll
    for (int w = 1; w < N; w *= 2)
#pragma unroll
        for (int i = 0; i + w < N; i += 2 * w) t[i] = fmaxf(t[i], t[i + w]);
    return t[0];
}
template <int N>
__device__ __forceinline__ float tree_sum(const float (&v)[N]) {
    float t[N];
#pragma unroll
    for (int i = 0; i < N; i++) t[i] = v[i];
#pragma unroll
    for (int w = 1; w < N; w *= 2)
#pragma unroll
        for (int i = 0; i + w < N; i += 2 * w) t[i] += t[i + w];
    return t[0];
}

template <int B>
__device__ __forceinline__ void pick(uint32_t h, uint32_t ok, const float* s, float& v0, float& v1) {
    asm("{\n.reg .pred p, q0, q1;\n.reg .b32 t;\nand.b32 t, %6, %7;\nsetp.ne.u32 p, t, 0;\n"
        "and.b32 t, %8, %9;\nsetp.ne.u32 q0, t, 0;\nand.b32 t, %8, %10;\nsetp.ne.u32 q1, t, 0;\n"
        "@q0 selp.f32 %0, %3, %2, p;\n@q1 selp.f32 %1, %5, %4, p;\n}\n"
        : "+f"(v0), "+f"(v1)
        : "f"(s[0]), "f"(s[1]), "f"(s[2]), "f"(s[3]), "r"(h), "n"(1 << ((4 * B) % 7)), "r"(ok), "n"(1 << (2 * B)), "n"(2 << (2 * B)));
}
template <int B, class F>
__device__ __forceinline__ void for_blocks(F f) {
    if constexpr (B > 0) { for_blocks<B - 1>(f); f(std::integral_constant<int, B - 1>{}); }
}
__device__ __forceinline__ void gather_outer(const float (&s)[44], uint32_t h, uint32_t ok, float (&v0)[14], float (&v1)[14]) {
    for_blocks<11>([&](auto B) {
        constexpr int b = B.value < 8 ? (B.value >> 1) + 7 * (B.value & 1) : B.value - 4;
        pick<b>(h, ok, &s[4 * b], v0[b], v1[b]);
    });
}
__device__ __forceinline__ void gather_mid(const float (&sE)[16], uint32_t h, uint32_t ok, float (&v0)[14], float (&v1)[14]) {
    for_blocks<4>([&](auto B) { pick<10 + B.value>(h, ok, &sE[4 * B.value], v0[10 + B.value], v1[10 + B.value]); });
}
__device__ __forceinline__ float quad_max(float m) {
    m = fmaxf(m, __shfl_xor_sync(0xffffffffu, m, 1));
    return fmaxf(m, __shfl_xor_sync(0xffffffffu, m, 2));
}
__device__ __forceinline__ float quad_sum(float s) {
    s += __shfl_xor_sync(0xffffffffu, s, 1);
    return s + __shfl_xor_sync(0xffffffffu, s, 2);
}
template <int B0, int B1>
__device__ __forceinline__ void exp_route(float (&v0)[14], float (&v1)[14], float m0, float m1, const uint4& r, bool even, uint32_t (&y)[14]) {
#pragma unroll
    for (int b = B0; b < B1; b++) { v0[b] = ex2(v0[b] - m0); v1[b] = ex2(v1[b] - m1); }
#pragma unroll
    for (int b = B0; b < B1; b += 2) {
        const uint32_t x0 = pack_bf16(v0[b], v1[b]), x1 = pack_bf16(v0[b + 1], v1[b + 1]);
        const uint32_t u = __shfl_sync(0xffffffffu, even ? x0 : x1, r.x);
        const uint32_t w = __shfl_sync(0xffffffffu, even ? x1 : x0, r.y);
        y[b] = __byte_perm(u, w, r.z); y[b + 1] = __byte_perm(u, w, r.w);
    }
}
template <int BIT0, int N0, int N1>
__device__ __forceinline__ void unfold(const uint32_t (&y)[14], uint32_t fold, uint32_t (&p)[12]) {
    for_blocks<N1 - N0>([&](auto N) {
        constexpr int n = N0 + N.value;
        asm("{\n.reg .pred p;\n.reg .b32 t;\nand.b32 t, %4, %5;\nsetp.ne.u32 p, t, 0;\nselp.b32 %0, %2, 0, p;\nselp.b32 %1, %3, 0, p;\n}\n"
            : "=r"(p[2 * n]), "=r"(p[2 * n + 1]) : "r"(y[2 * n]), "r"(y[2 * n + 1]), "r"(fold), "n"(1 << (BIT0 + n)));
    });
}
__device__ __forceinline__ void keep(bool never, uint32_t a, uint32_t b, uint32_t c, uint32_t d) {
    asm volatile("{\n.reg .pred p;\nsetp.ne.u32 p, %4, 0;\n@p st.volatile.shared.v4.u32 [%5], {%0, %1, %2, %3};\n}\n"
                 ::"r"(a), "r"(b), "r"(c), "r"(d), "r"((uint32_t)never), "r"(s_trace) : "memory");
}

__device__ __forceinline__ uint32_t wimg_offset(uint32_t row, uint32_t s, uint32_t j) {
    return (s >> 2) * kWChunk + row * 128 + (((2 * (s & 3) + (j >> 1)) ^ (row & 7)) << 4) + (j & 1) * 8;
}

__device__ __forceinline__ void ldsm4(uint32_t (&r)[4], uint32_t addr) {
    asm volatile("ldmatrix.sync.aligned.m8n8.x4.shared.b16 {%0, %1, %2, %3}, [%4];" : "=r"(r[0]), "=r"(r[1]), "=r"(r[2]), "=r"(r[3]) : "r"(addr) : "memory");
}
__device__ __forceinline__ void ldsm4_t(uint32_t (&r)[4], uint32_t addr) {
    asm volatile("ldmatrix.sync.aligned.m8n8.x4.trans.shared.b16 {%0, %1, %2, %3}, [%4];" : "=r"(r[0]), "=r"(r[1]), "=r"(r[2]), "=r"(r[3]) : "r"(addr) : "memory");
}
__device__ __forceinline__ void m_partial(const uint8_t* wqkv, uint32_t mt, uint32_t s, uint32_t q, uint32_t lane, uint32_t zero) {
    const uint32_t r8 = lane >> 2, col = q * 128 + (lane & 3) * 16;
    const uint8_t* pa = wqkv + (16 * mt + r8) * 1152 + col;
    const uint8_t* pb = wqkv + (16 * s + 8 * (r8 & 2) + (r8 & 5)) * 1152 + col;
    uint4 A[2][2], B[4][2];
#pragma unroll
    for (int c = 0; c < 2; c++) {
#pragma unroll
        for (int h = 0; h < 2; h++) A[h][c] = ldg(pa + 384 + h * 8 * 1152 + c * 64);
#pragma unroll
        for (int n = 0; n < 4; n++) B[n][c] = ldg(pb + ((n & 1) * 8 + (n & 2)) * 1152 + c * 64);
    }
#pragma unroll
    for (int i = 0; i < 4; i++) { uint4& a = A[i >> 1][i & 1]; a.x ^= zero; a.y ^= zero; a.z ^= zero; a.w ^= zero; }
#pragma unroll
    for (int n = 0; n < 4; n++) {
        float d[4] = {0.f, 0.f, 0.f, 0.f};
#pragma unroll
        for (int c = 0; c < 2; c++) {
            mma16816(d, A[0][c].x, A[1][c].x, A[0][c].y, A[1][c].y, B[n][c].x, B[n][c].y);
            mma16816(d, A[0][c].z, A[1][c].z, A[0][c].w, A[1][c].w, B[n][c].z, B[n][c].w);
        }
        asm volatile("st.shared.v4.f32 [%0], {%1, %2, %3, %4};" ::"r"(s_wv + q * 2048 + n * 512 + lane * 16), "f"(d[0]), "f"(d[1]), "f"(d[2]), "f"(d[3]) : "memory");
    }
}
__device__ __forceinline__ void m_reduce(uint32_t e, uint32_t lane, float (&d)[2][4]) {
#pragma unroll
    for (int n = 0; n < 2; n++) {
        float t[3][4];
#pragma unroll
        for (int q = 0; q < 3; q++)
            asm volatile("ld.shared.v4.f32 {%0, %1, %2, %3}, [%4];" : "=f"(t[q][0]), "=f"(t[q][1]), "=f"(t[q][2]), "=f"(t[q][3]) : "r"(s_wv + q * 2048 + e * 1024 + n * 512 + lane * 16) : "memory");
#pragma unroll
        for (int i = 0; i < 4; i++) d[n][i] = (t[0][i] + t[1][i] + t[2][i]) * kScaleLog2e;
    }
}
__device__ __forceinline__ void w_piece(uint32_t q, uint32_t lane, float (&d)[2][4]) {
    const uint32_t rr = lane & 7, mi = lane >> 3, kr = 4 * (rr >> 1) + (mi & 2) + (rr & 1);
    const uint32_t pa = s_wv + q * 6144 + (4 * (mi & 2) + rr) * 32 + (((mi ^ (rr >> 2)) & 1) << 4);
    const uint32_t pb = s_wv + 3 * 6144 + kr * 32 + (((mi ^ (kr >> 2)) & 1) << 4);
#pragma unroll
    for (int i = 0; i < 8; i++) (&d[0][0])[i] = 0.f;
#pragma unroll kWUnroll
    for (int k = 0; k < 12; k++) {
        uint32_t aq[4], bq[4];
        ldsm4_t(aq, pa + k * 512);
        ldsm4(bq, pb + k * 512);
        mma16816(d[0], aq[0], aq[1], aq[2], aq[3], bq[0], bq[1]);
        mma16816(d[1], aq[0], aq[1], aq[2], aq[3], bq[2], bq[3]);
    }
}
__device__ __forceinline__ uint32_t piece_offset(uint32_t which, uint32_t s, uint32_t mt, uint32_t lane) {
    const uint32_t r8 = lane >> 2;
    return which * kWBytes + wimg_offset(which ? 32 * (mt >> 1) + 8 * (r8 >> 1) + 4 * (mt & 1) + (r8 & 1) : 16 * mt + r8, s, lane & 3);
}
__device__ __forceinline__ void piece_store(Scratch* g, uint32_t par, uint32_t off0, uint32_t which, const float (&d)[2][4]) {
#pragma unroll
    for (int hf = 0; hf < 2; hf++) {
        const uint32_t off = off0 ^ (hf ? which ? 288 : 1024 : 0);
        const uint32_t a = pack_bf16(d[0][2 * hf], d[0][2 * hf + 1]), b = pack_bf16(d[1][2 * hf], d[1][2 * hf + 1]);
        asm volatile("st.relaxed.gpu.global.v2.u32 [%0], {%1, %2};" ::"l"(g->img[0][0] + (par + off)), "r"(a ? a : 0x8000u), "r"(b) : "memory");
        asm volatile("st.relaxed.gpu.global.v2.u32 [%0], {%1, %1};" ::"l"(g->img[1][0] + (int)(off - par)), "r"(0) : "memory");
    }
}

__device__ __forceinline__ uint32_t ld_relaxed(const uint32_t* p) {
    uint32_t v;
    asm volatile("ld.relaxed.gpu.global.u32 %0, [%1];" : "=r"(v) : "l"(p) : "memory");
    return v;
}
__device__ __forceinline__ void count_up(uint32_t* p) {
    asm volatile("red.relaxed.gpu.global.add.u32 [%0], %1;" ::"l"(p), "r"(1) : "memory");
}
__device__ __forceinline__ void bulk_g2s(uint32_t dst, const void* src, uint32_t bytes, uint32_t bar) {
    asm volatile("cp.async.bulk.shared::cluster.global.mbarrier::complete_tx::bytes [%0], [%1], %2, [%3];"
                 ::"r"(dst), "l"(src), "r"(bytes), "r"(bar)
                 : "memory");
}

__global__ void __launch_bounds__(kThreads, 1)
nat_fused_kernel(const uint8_t* __restrict__ x, const uint8_t* __restrict__ wqkv, uint8_t* __restrict__ out, Scratch* g,
                 const Tables* tables, uint64_t dsc, const __grid_constant__ Maps maps) {
    const int tid = threadIdx.x, lane = tid & 31;
    const int warp = __shfl_sync(0xffffffffu, tid >> 5, 0);
    const int wg = warp >> 2, wq = warp & 3, r8 = lane >> 2, j = lane & 3;
    const int cta = blockIdx.x;
    const Work w = decode_work(cta);
    const uint32_t which = cta >= 72, job = which ? cta - 72 : 2 * cta, jhi = job / 12, jlo = job % 12;
    if (wg == 1 && wq < 3) {
#pragma unroll
        for (int r = 0; r < 3; r++)
            asm volatile("st.shared.v4.u32 [%0], {%1, %1, %1, %1};" ::"r"(s_ring + wq * kRingChunk + (r == 0 ? 84 : r == 1 ? 88 : 204) * 128 + lane * 16), "r"(0) : "memory");
        asm volatile("fence.proxy.async.shared::cta;" ::: "memory");
    }
    if (x == nullptr) return;
    const uint32_t t_start = clock_now();
    if (wg == 2) {
        if (wq < 3 && !which) m_partial(wqkv, jhi, jlo, wq, lane, (uint32_t)dsc & 1);
        asm volatile("setmaxnreg.dec.sync.aligned.u32 40;");
        if (wq < 3) {
            const uint32_t off = piece_offset(which, which ? jlo : jlo + wq, which ? 3 * jhi + wq : jhi, lane);
            asm volatile("bar.sync %0, 128;" ::"r"(5 + (off >> 31)) : "memory");
            const uint32_t par = lds_volatile(s_par);
            if (cta < 120 && wq < 2 + which) {
                float d[2][4];
                if (wq == 0) TRW(which ? 1 : 18);
                if (which) {
                    mbar_wait(bar_wop, 0);
                    if (wq == 0) TRW(2);
                    w_piece(wq, lane, d);
                } else {
                    m_reduce(wq, lane, d);
                }
                piece_store(g, par, off, which, d);
                __syncwarp();
                if (!which && lane == 0) count_up(&g->cnt[0]);
                if (wq == 0) TRW(which ? 3 : 0);
            }
            asm volatile("bar.arrive 6, 128;" ::: "memory");
            uint32_t phase = 0;
#pragma unroll 1
            for (uint32_t c = 0; c < 6; c++) {
                const uint32_t part = c * kWChunk + wq * (kWChunk / 3), img = 8 * min(c, 3u);
                mbar_wait(bar_img + 8 * c, 0);
                if (wq == 0) TRW(10 + c);
#pragma unroll 1
                while (true) {
                    uint32_t lo = ~0u;
#pragma unroll
                    for (int q = 0; q < 8; q++) lo = min(lo, lds_volatile(s_m + part + lane * 32 + (lane & 12) * 2 + q * 1024));
                    if (__all_sync(0xffffffffu, lo) || phase > 65535) break;
                    if (elect()) {
                        mbar_expect_tx(bar_redo + 8 * wq, kWChunk / 3);
                        bulk_g2s(s_m + part, g->img[0][0] + par + part, kWChunk / 3, bar_redo + 8 * wq);
                    }
                    mbar_wait(bar_redo + 8 * wq, phase++ & 1);
                }
                if (c != 3 && c != 4 && lane == 0) mbar_arrive(bar_ok + img);
            }
        } else {
            uint32_t launch = ld_relaxed(&g->cnt[1]);
            const CUtensorMap* map = &maps.m[w.sv == kPixBytes ? 2 : 0];
            if (elect()) {
#pragma unroll
                for (int i = 0; i < 20; i++) mbar_init(s_bar + 8 * i, i < 13 ? 1 : i < 18 ? 3 : 4);
                asm volatile("fence.mbarrier_init.release.cluster;" ::: "memory");
                prefetch_map(map + 1);
                expect_tx_only(bar_a, sizeof(Table));
                bulk_g2s(s_tab, &tables->t[w.step < 0], sizeof(Table), bar_a);
            }
            if (which && cta < 120 && elect()) {
                mbar_expect_tx(bar_wop, 4 * 6144);
                tma_3d(s_wv, &maps.wo, bar_wop, 0, 3 * jhi);
                tma_3d(s_wv + 3 * 6144, &maps.wv, bar_wop, 16 * jlo, 24);
            }
            int u = w.u, v = w.v;
            uint32_t wait_bar = bar_use, wait_par = 1, slot = 0;
#pragma unroll 1
            for (int step = 0; step < 7 - w.corner; step++) {
                const bool first = step == 0 || (w.corner && step == 4);
                const int row = v + 4 + (first ? -w.step : w.step) / 2, ou = origin_u(u);
                uint32_t dst = s_ring + (first ? 0 : slot), mid = s_ring + kOffMid + 512, bar = first ? bar_a : bar_b;
                mbar_wait(wait_bar, wait_par);
#pragma unroll 1
                for (int ch = (cta & 1) * kC; mid < s_m; ch += 64, dst += kRingChunk, mid += kRingChunk) {
                    if (elect()) {
                        mbar_expect_tx(bar, first ? kSlotBytes : kSlotBytes + kMidBytes);
                        tma_box(dst, map, bar, ch, ou, (cta >> 1) & 1, row);
                    }
                    if (!first) {
                        if (elect()) tma_box(mid, map + 1, bar, ch, ou, (cta >> 1) & 1, v + 6);
                        bar += 8;
                    }
                }
                if (step == 0) {
                    launch /= kGrid;
                    asm volatile("st.shared.u32 [%0], %2;\nst.shared.v2.u32 [%0 + 16], {%1, %2};" ::"r"(s_cnt), "r"((launch & 1) * 2 * kWBytes), "r"(0) : "memory");
                    if (lane == 0) count_up(&g->cnt[1]);
                    asm volatile("bar.arrive 5, 128;\nbar.arrive 3, 160;\nbar.arrive 4, 160;" ::: "memory");
#pragma unroll 1
                    for (int t = TN(6, 2000); t < (1 << 24);) {
                        if (__shfl_sync(0xffffffffu, lds_volatile(s_cnt), 0) >= (launch + 1) * kPieces) break;
                        if ((int)(clock_now() - t_start) < t) continue;
                        t += TN(7, 200);
                        if (elect()) {
                            expect_tx_only(bar_use + 8, 16);
                            bulk_g2s(s_cnt, g->cnt, 16, bar_use + 8);
                        }
                    }
                }
                if (step == 1) {
                    asm volatile("bar.sync 6, 128;" ::: "memory");
                    wait_until(t_start, TN(5, 6000));
                }
                if (step < 2) {
                    TRW(5 + 4 * step);
#pragma unroll 1
                    for (int c = 3 * step; c < 3 + 3 * step; c++)
                        if (elect()) {
                            mbar_expect_tx(bar_img + 8 * c, kWChunk);
                            bulk_g2s(s_m + c * kWChunk, g->img[launch & 1][0] + c * kWChunk, kWChunk, bar_img + 8 * c);
                        }
                }
                const bool again = w.corner && step == 3;
                wait_bar = step == 0 ? bar_img + 8 * TN(1, 1) : again ? bar_use + 8 : bar_use;
                if (!again) {
                    wait_par = slot ? 0 : step != 0;
                    slot ^= kSlotStride;
                    if (w.corner && step == 2) { u += 8; v -= 8; } else if (step) v += w.step;
                }
            }
        }
        TRDUMP();
        return;
    }
    const int order = w.step < 0 ? warp ^ 3 : warp;
    wait_until(t_start, START_TIME);
    asm volatile("setmaxnreg.inc.sync.aligned.u32 232;");
    int tu = w.u, tv = w.v + w.step * wg;
    const int du2 = w.corner ? 8 : 0, dv2 = w.corner ? 0 : 2 * w.step;
    uint32_t o0, o1;
    w.pixel_offsets(tu + r8, tv + 2 * wq, j, o0, o1);
    uint32_t fa[48];
    {
        RawX raw;
        load_raw(raw, x, o0, o1);
        asm volatile("bar.sync %0, 160;" ::"r"(3 + wg) : "memory");
        raw_to_frags(raw, 0, fa);
        pin(fa);
    }
    mbar_wait(bar_ok, 0);
    const uint64_t dA = dsc + wg * (kSlotStride >> 4), dB = dsc + (wg ^ 1) * (kSlotStride >> 4);

    float acc[96];
    uint32_t po[48];
    uint32_t c0, c1;
    asm volatile("" : "=r"(c0), "=r"(c1));
#pragma unroll
    for (int q = 0; q < 48; q++) asm volatile("" : "=r"(po[q]));
#pragma unroll 1
    for (int i = wg; i < w.ntiles; i += 2) {
        const bool first = i == 0, last = i == w.ntiles - 1;

        TRF(8 + 16 * k);
        wg_fence();
        if (!first) turn_wait(wg);
        proj_gemm(acc, fa, dsc, s_m, [&](int s) {
            if (s == 11 && !first) turn_pass(wg);
            const int n = __builtin_popcount(QSLOTS & ((1 << s) - 1));
            if (((QSLOTS >> s) & 1) && n < 12) store_one(i >= 2, out + c0, out + c1, po, n);
            if (s == 3 || s == 7) { mbar_wait(bar_ok + 2 * s + 2, 0); wg_fence(); }
        });
        __syncwarp();
        TRF(9 + 16 * k);
        uint8_t *p0 = out + c0, *p1 = out + c1;
        c0 = o0; c1 = o1;
        w.pixel_offsets(tu + du2 + r8, tv + dv2 + 2 * wq, j, o0, o1);
        if (i + 2 >= w.ntiles) o0 = o1 = 0;
        wg_wait<0>();
        pin(acc);
        TR(11 + 16 * k); TRT(80 + k);
#pragma unroll
        for (int n = __builtin_popcount(QSLOTS); n < 12 - __builtin_popcount(ASLOTS) - __builtin_popcount(BSLOTS); n++) store_one(i >= 2, p0, p1, po, n);
        acc_to_frags(acc, fa);
        pin(fa);

        float sA[44], sE[16], sB[44];
        RawX nxt;
        if (!first) turn_wait(wg);
        mbar_wait(bar_a, w.corner ? i >> 1 : 0);
        if (i == 0) TR(12);
        wg_fence();
#pragma unroll
        for (int s = 0; s < 12; s++) {
            if (s == 0) wgmma_n88<true>(sA, fa[4 * s], fa[4 * s + 1], fa[4 * s + 2], fa[4 * s + 3], desc_at(dA, (s >> 2) * kRingChunk + (s & 3) * 32));
            else wgmma_n88<false>(sA, fa[4 * s], fa[4 * s + 1], fa[4 * s + 2], fa[4 * s + 3], desc_at(dA, (s >> 2) * kRingChunk + (s & 3) * 32));
            if (s == 11) { wg_commit(); if (!first) turn_pass(wg); }
            if ((ASLOTS >> s) & 1) store_one(i >= 2, p0, p1, po, 12 - __builtin_popcount(BSLOTS) - __builtin_popcount(ASLOTS >> s));
        }
#pragma unroll
        for (int s = 12; s < 16; s++)
            if ((ASLOTS >> s) & 1) store_one(i >= 2, p0, p1, po, 12 - __builtin_popcount(BSLOTS) - __builtin_popcount(ASLOTS >> s));
        TRF(12 + 16 * k);
        const int vq = tv + 2 * wq;
        const uint4 tabu = lds128(s_tab + offsetof(Table, u) + (window_start(tu + r8) - origin_u(tu)) * 64 + j * 16);
        const uint4 tabv = lds128(s_tab + offsetof(Table, v) + (window_start(vq) + window_start(vq + 1) - 2 * tv) * 64 + j * 16);
        const uint4 route = lds128(s_tab + lane * 16);
        if (LDGPOS == 0) load_raw(nxt, x, o0, o1);
        float v0[14], v1[14];
#pragma unroll
        for (int b = 0; b < 14; b++) v0[b] = v1[b] = __int_as_float(0xff800000);
        wg_wait<0>();
        pin(sA);
        gather_outer(sA, tabu.x, tabv.x, v0, v1);
        pin(v0); pin(v1);
        if (!first) turn_wait(wg);
#pragma unroll
        for (int c = 0; c < 3; c++) {
            mbar_wait(bar_b + 8 * c, wg);
            if (i == 0 && c != 1) TR(13 + c);
            wg_fence();
#pragma unroll
            for (int s = 4 * c; s < 4 * c + 4; s++) {
                if (s == 0) wgmma_n88<true>(sB, fa[4 * s], fa[4 * s + 1], fa[4 * s + 2], fa[4 * s + 3], desc_at(dB, c * kRingChunk + (s & 3) * 32));
                else wgmma_n88<false>(sB, fa[4 * s], fa[4 * s + 1], fa[4 * s + 2], fa[4 * s + 3], desc_at(dB, c * kRingChunk + (s & 3) * 32));
                if ((BSLOTS >> s) & 1) store_one(i >= 2, p0, p1, po, 12 - __builtin_popcount(BSLOTS >> s));
            }
        }
        wg_commit();
#pragma unroll
        for (int s = 0; s < 12; s++)
            if (s == 0) wgmma_n32<true>(sE, fa[4 * s], fa[4 * s + 1], fa[4 * s + 2], fa[4 * s + 3], desc_at(dsc, kOffMid + (s >> 2) * kRingChunk + (s & 3) * 32));
            else wgmma_n32<false>(sE, fa[4 * s], fa[4 * s + 1], fa[4 * s + 2], fa[4 * s + 3], desc_at(dsc, kOffMid + (s >> 2) * kRingChunk + (s & 3) * 32));
        wg_commit();
        if (OSPLIT || !last) turn_pass(wg);
        TRF(13 + 16 * k);
        wg_wait<1>();
        pin(sB);
        gather_outer(sB, tabu.w, tabv.y, v0, v1);
        wg_wait<0>();
        pin(sE);
        TRF(14 + 16 * k);
        gather_mid(sE, tabu.w, tabv.z, v0, v1);
        const float m0 = quad_max(tree_max(v0)), m1 = quad_max(tree_max(v1));

        uint32_t y[14], pa[12], pb[12];
        exp_route<0, 14>(v0, v1, m0, m1, route, (j & 1) == 0, y);
        float s0 = tree_sum(v0), s1 = tree_sum(v1);
        asm volatile("" : "+f"(s0), "+f"(s1));
        unfold<0, 0, 6>(y, tabv.w, pa);
        if (OSPLIT || !last) turn_wait(wg + (y[0] >> 31));
        TRF(15 + 16 * k + (y[13] >> 31));
        wg_fence();
        wgmma_sp_n192_tb<true, 0>(acc, pa[0], pa[1], pa[2], pa[3], desc_at(dA, kToV), tabu.y);
        wgmma_sp_n192_tb<false, 1>(acc, pa[4], pa[5], pa[6], pa[7], desc_at(dA, kToV + 4096), tabu.y);
        wgmma_sp_n192_tb<false, 0>(acc, pa[8], pa[9], pa[10], pa[11], desc_at(dA, kToV + 8192), tabu.z);
        wgmma_sp_n192_tb<false, 1>(acc, y[10], y[11], y[12], y[13], desc_at(dsc, kToV + kOffMid), tabu.z);
        wg_commit();
        unfold<8, 0, 6>(y, tabv.w, pb);
        wg_fence();
        wgmma_sp_n192_tb<false, 0>(acc, pb[0], pb[1], pb[2], pb[3], desc_at(dB, kToV), tabu.y);
        wgmma_sp_n192_tb<false, 1>(acc, pb[4], pb[5], pb[6], pb[7], desc_at(dB, kToV + 4096), tabu.y);
        wgmma_sp_n192_tb<false, 0>(acc, pb[8], pb[9], pb[10], pb[11], desc_at(dB, kToV + 8192), tabu.z);
        wg_commit();
        if (!last) turn_pass(wg);
        TRF(16 + 16 * k);
        if (LDGPOS == 3) load_raw(nxt, x, o0, o1);
        wg_wait<1>();
        if (lane == 0) mbar_arrive(bar_use);
        TRF(17 + 16 * k);
        mbar_wait(bar_ok + 24, 0);
        wg_wait<0>();
        if (lane == 0) mbar_arrive(bar_use + 8);
        pin(acc);
        TR(18 + 16 * k);

        acc_to_frags(acc, po);
        pin(po);
        if (!last) turn_wait(wg);
        wg_fence();
        proj_gemm(acc, po, dsc, s_wv, [&](int s) {
            if (s + 1 == OSPLIT && i + 2 == w.ntiles) { turn_pass(wg); turn_wait(wg); }
        });
        if (!last) turn_pass(wg);
        TRF(19 + 16 * k);
        const uint32_t zero = lds_volatile(s_late);
        const float inv0 = rcp(quad_sum(s0 + __uint_as_float(zero))), inv1 = rcp(quad_sum(s1 + __uint_as_float(zero)));
        raw_to_frags(nxt, zero, fa);
        pin(fa);
#pragma unroll
        for (int q = 0; q < 48; q += 4) keep(wqkv == nullptr, fa[q], fa[q + 1], fa[q + 2], fa[q + 3]);
        keep(wqkv == nullptr, __float_as_uint(inv0), __float_as_uint(inv1), zero, lane);
        TRF(20 + 16 * k);
        tu += du2; tv += dv2;
        wg_wait<0>();
        pin(acc);
        TR(21 + 16 * k);
#pragma unroll
        for (int q = 0; q < 96; q++) acc[q] *= q & 2 ? inv1 : inv0;
        pack_out(acc, po);
#pragma unroll
        for (int n = 0; n < 12; n++) store_one<false>(NAP && n >= NAP0 ? last : i + 2 >= w.ntiles, out + c0, out + c1, po, n);
        pin(po);
    }
    if (NAP && wg == 0) {
#pragma unroll
        for (int n = NAP0; n < 12; n++) {
            if (n == NAP0) asm volatile("nanosleep.u32 %0;" ::"n"(NAP1) : "memory"); else asm volatile("nanosleep.u32 %0;" ::"n"(NAP) : "memory");
            store_one<false>(true, out + c0, out + c1, po, n);
        }
    }
    TR(7);
    TRG(1);
    TRDUMP();
}

typedef CUresult (*EncodeTiledFn)(CUtensorMap*, CUtensorMapDataType, cuuint32_t, void*, const cuuint64_t*, const cuuint64_t*,
                                  const cuuint32_t*, const cuuint32_t*, CUtensorMapInterleave, CUtensorMapSwizzle,
                                  CUtensorMapL2promotion, CUtensorMapFloatOOBfill);

bool make_maps(EncodeTiledFn fn, Maps* maps, void* x, void* wqkv, void* wo) {
    const cuuint64_t pix2 = 2 * kPixBytes, row = (cuuint64_t)kHW * kPixBytes;
    const cuuint32_t estr[5] = {1, 1, 1, 1, 1};
    bool ok = true;
    for (int tr = 0; tr < 2; tr++)
        for (int b = 0; b < 2; b++) {
            const cuuint64_t su = tr ? 2 * row : pix2, sv = tr ? pix2 : 2 * row;
            const cuuint64_t dims[5] = {2 * kC, 2, 105, 2, 112};
            const cuuint64_t strides[4] = {7 * su, su, row, sv};
            const cuuint32_t box[5] = {64, 2, 7, 1, b ? 2u : 6u};
            ok = ok && fn(&maps->m[2 * tr + b], CU_TENSOR_MAP_DATA_TYPE_BFLOAT16, 5, x, dims, strides, box, estr,
                          CU_TENSOR_MAP_INTERLEAVE_NONE, CU_TENSOR_MAP_SWIZZLE_128B, CU_TENSOR_MAP_L2_PROMOTION_L2_128B,
                          CU_TENSOR_MAP_FLOAT_OOB_FILL_NONE) == CUDA_SUCCESS;
        }
    for (int b = 0; b < 2; b++) {
        const cuuint64_t dims[3] = {16, kC, b ? 36u : 12u}, strides[2] = {(b ? 3u : 1u) * kPixBytes, 32};
        const cuuint32_t box[3] = {16, b ? 16u : 192u, b ? 12u : 3u};
        ok = ok && fn(b ? &maps->wv : &maps->wo, CU_TENSOR_MAP_DATA_TYPE_BFLOAT16, 3, b ? wqkv : wo, dims, strides, box, estr,
                      CU_TENSOR_MAP_INTERLEAVE_NONE, CU_TENSOR_MAP_SWIZZLE_32B, CU_TENSOR_MAP_L2_PROMOTION_L2_128B,
                      CU_TENSOR_MAP_FLOAT_OOB_FILL_NONE) == CUDA_SUCCESS;
    }
    return ok;
}

}

extern "C" void kernel_launch(void* const* d_in, const int* in_sizes, int n_in, void* d_out, int out_size) {
    static EncodeTiledFn encode = nullptr;
    static Scratch* scratch = nullptr;
    static Tables* tables = nullptr;
    if (!encode) {
        int dev = 0, reserved = 0;
        cudaFuncAttributes attr;
        cudaGetDevice(&dev);
        cudaDeviceGetAttribute(&reserved, cudaDevAttrReservedSharedMemoryPerBlock, dev);
        cudaFuncGetAttributes(&attr, nat_fused_kernel);
        if (reserved != (int)kSmemBase || attr.sharedSizeBytes != 0) return;
        cudaGetSymbolAddress((void**)&scratch, g_scratch);
        cudaGetSymbolAddress((void**)&tables, g_tables);
        void* fn = nullptr;
        cudaDriverEntryPointQueryResult st;
        cudaGetDriverEntryPoint("cuTensorMapEncodeTiled", &fn, cudaEnableDefault, &st);
        encode = (EncodeTiledFn)fn;
        cudaFuncSetAttribute(nat_fused_kernel, cudaFuncAttributeMaxDynamicSharedMemorySize, kSmemBytes);
    }
    Maps maps;
    if (!encode || !make_maps(encode, &maps, d_in[0], d_in[1], d_in[2])) return;
    nat_fused_kernel<<<kGrid, kThreads, kSmemBytes>>>((const uint8_t*)d_in[0], (const uint8_t*)d_in[1], (uint8_t*)d_out, scratch, tables, kDescRing, maps);
}
```

```cpp
#include <cuda_runtime.h>
#include <cuda_bf16.h>
#include <cuda.h>
#include <stdint.h>
#include <type_traits>
#include <stdlib.h>
#include <stddef.h>

#define KEEPFA 1
#define ASLOTS 0x3800
#define BSLOTS 0x6
#define QSLOTS 0x78a
#define OSPLIT 3
#define NAP 40
#define INLOOP 3
#define WUNROLL 2

namespace {

constexpr int kC          = 192;
constexpr int kHW         = 224;
constexpr int kPixBytes   = kC * 2;
constexpr int kSlotBytes  = 84 * 128;
constexpr int kMidBytes   = 28 * 128;
constexpr int kOffMid     = 88 * 128;
constexpr int kSlotStride = 120 * 128;
constexpr int kRingChunk  = 208 * 128;
constexpr int kWChunk     = 192 * 128;
constexpr int kWBytes     = 3 * kWChunk;
constexpr uint32_t kSmemBase = 1024;
constexpr uint32_t s_ring = kSmemBase, s_m = s_ring + 3 * kRingChunk, s_wv = s_m + kWBytes, s_bar = s_wv + kWBytes;
constexpr uint32_t bar_b = s_bar, bar_img = s_bar + 24, bar_redo = s_bar + 72, bar_wop = s_bar + 96, bar_a = s_bar + 104,
                   bar_ok = s_bar + 112, bar_use = s_bar + 144;
constexpr uint32_t s_cnt = s_bar + 160, s_par = s_bar + 176, s_late = s_bar + 180, s_tab = s_bar + 256, s_trace = s_tab + 2048;
constexpr int kSmemBytes  = s_trace + 2048 - kSmemBase;
constexpr int kThreads    = 384, kWUnroll = WUNROLL;
constexpr int kGrid       = 132;
constexpr int kPieces     = 144;
constexpr float kScaleLog2e = 0.07216878364870322f * 1.4426950408889634f;

struct Maps {
    CUtensorMap m[4];
    CUtensorMap wo, wv;
};
#define TN(i, dflt) (dflt)
#define START_TIME (wg ? 1900 + 500 * order : which ? 100 + 500 * order : order ? 2100 + 200 * order : 400)

struct Scratch {
    uint8_t img[2][2][kWBytes];
    uint32_t cnt[4];
};
__device__ __align__(1024) Scratch g_scratch;

struct Table {
    uint32_t route[32][4];
    uint32_t u[8][4][4];
    uint32_t v[16][4][4];
};
struct Tables { Table t[2]; };
constexpr Tables make_tables() {
    Tables r = {};
    for (int rev = 0; rev < 2; rev++)
        for (int j = 0; j < 4; j++) {
            Table& t = r.t[rev];
            for (int q = 0; q < 8; q++) {
                uint32_t* e = t.route[4 * q + j];
                e[0] = 4 * q + 2 * (j & 1) + (j >> 1); e[1] = e[0] ^ 1;
                e[2] = j < 2 ? 0x5410u : 0x1054u; e[3] = e[2] + 0x2222u;
                e = t.u[q][j];
                for (int n = 0; n < 7; n++) e[0] |= ((n + j) % 7 < q ? 1u : 0u) << n;
                e[3] = e[0];
                for (int k = 0; k < 2; k++) {
                    const int step = 2 * k + (j >> 1), p0 = (step < 3 ? 16 * step : 40) + 8 * (j & 1);
                    uint32_t m = 0x8888u;
                    for (int n = 0; n < 8; n++) m |= ((p0 + n) % 7 < q ? 1u : 0u) << (2 * n);
                    e[1 + k] = m * 0x10001u;
                }
            }
            for (int sum = 0; sum < 15; sum++) {
                uint32_t* e = t.v[sum][j];
                for (int row = 0; row < 2; row++)
                    for (int b = 0; b < 14; b++) {
                        const int off = (sum + row) / 2, p = 4 * b + j;
                        const uint32_t bit = 1u << (2 * b + row);
                        if (p < 42 && p >= 7 * off) e[rev] |= bit;
                        if (p < 7 * off - 7) e[1 - rev] |= bit;
                        if (p >= 42 && p >= 7 * off && p < 7 * off + 49) e[2] |= bit;
                    }
                for (int n = 0; n < 6; n++)
                    if (8 * n + 2 * j < 42) e[3] |= 1u << (n + ((8 * n + 2 * j >= 7 * (sum / 2 & ~1)) != rev ? 0 : 8));
            }
        }
    return r;
}
__device__ __align__(128) const Tables g_tables = make_tables();

#define WO4(i) "=f"(d[i]), "=f"(d[i + 1]), "=f"(d[i + 2]), "=f"(d[i + 3])
#define RW4(i) "+f"(d[i]), "+f"(d[i + 1]), "+f"(d[i + 2]), "+f"(d[i + 3])

template <bool FIRST>
__device__ __forceinline__ void wgmma_n192(float (&d)[96], uint32_t a0, uint32_t a1, uint32_t a2, uint32_t a3, uint64_t descb) {
    if constexpr (FIRST) {
        asm volatile(
            "wgmma.mma_async.sync.aligned.m64n192k16.f32.bf16.bf16 "
            "{%0, %1, %2, %3, %4, %5, %6, %7, %8, %9, %10, %11, %12, %13, %14, %15, %16, %17, %18, %19, %20, %21, %22, %23, "
            "%24, %25, %26, %27, %28, %29, %30, %31, %32, %33, %34, %35, %36, %37, %38, %39, %40, %41, %42, %43, %44, %45, %46, %47, "
            "%48, %49, %50, %51, %52, %53, %54, %55, %56, %57, %58, %59, %60, %61, %62, %63, %64, %65, %66, %67, %68, %69, %70, %71, "
            "%72, %73, %74, %75, %76, %77, %78, %79, %80, %81, %82, %83, %84, %85, %86, %87, %88, %89, %90, %91, %92, %93, %94, %95}, "
            "{%96, %97, %98, %99}, %100, 0, 1, 1, 0;"
            : WO4(0), WO4(4), WO4(8), WO4(12), WO4(16), WO4(20), WO4(24), WO4(28), WO4(32), WO4(36), WO4(40), WO4(44),
              WO4(48), WO4(52), WO4(56), WO4(60), WO4(64), WO4(68), WO4(72), WO4(76), WO4(80), WO4(84), WO4(88), WO4(92)
            : "r"(a0), "r"(a1), "r"(a2), "r"(a3), "l"(descb));
    } else {
        asm volatile(
            "wgmma.mma_async.sync.aligned.m64n192k16.f32.bf16.bf16 "
            "{%0, %1, %2, %3, %4, %5, %6, %7, %8, %9, %10, %11, %12, %13, %14, %15, %16, %17, %18, %19, %20, %21, %22, %23, "
            "%24, %25, %26, %27, %28, %29, %30, %31, %32, %33, %34, %35, %36, %37, %38, %39, %40, %41, %42, %43, %44, %45, %46, %47, "
            "%48, %49, %50, %51, %52, %53, %54, %55, %56, %57, %58, %59, %60, %61, %62, %63, %64, %65, %66, %67, %68, %69, %70, %71, "
            "%72, %73, %74, %75, %76, %77, %78, %79, %80, %81, %82, %83, %84, %85, %86, %87, %88, %89, %90, %91, %92, %93, %94, %95}, "
            "{%96, %97, %98, %99}, %100, 1, 1, 1, 0;"
            : RW4(0), RW4(4), RW4(8), RW4(12), RW4(16), RW4(20), RW4(24), RW4(28), RW4(32), RW4(36), RW4(40), RW4(44),
              RW4(48), RW4(52), RW4(56), RW4(60), RW4(64), RW4(68), RW4(72), RW4(76), RW4(80), RW4(84), RW4(88), RW4(92)
            : "r"(a0), "r"(a1), "r"(a2), "r"(a3), "l"(descb));
    }
}

template <bool FIRST>
__device__ __forceinline__ void wgmma_n88(float (&d)[44], uint32_t a0, uint32_t a1, uint32_t a2, uint32_t a3, uint64_t descb) {
    if constexpr (FIRST) {
        asm volatile(
            "wgmma.mma_async.sync.aligned.m64n88k16.f32.bf16.bf16 "
            "{%0, %1, %2, %3, %4, %5, %6, %7, %8, %9, %10, %11, %12, %13, %14, %15, %16, %17, %18, %19, %20, %21, %22, %23, "
            "%24, %25, %26, %27, %28, %29, %30, %31, %32, %33, %34, %35, %36, %37, %38, %39, %40, %41, %42, %43}, "
            "{%44, %45, %46, %47}, %48, 0, 1, 1, 0;"
            : WO4(0), WO4(4), WO4(8), WO4(12), WO4(16), WO4(20), WO4(24), WO4(28), WO4(32), WO4(36), WO4(40)
            : "r"(a0), "r"(a1), "r"(a2), "r"(a3), "l"(descb));
    } else {
        asm volatile(
            "wgmma.mma_async.sync.aligned.m64n88k16.f32.bf16.bf16 "
            "{%0, %1, %2, %3, %4, %5, %6, %7, %8, %9, %10, %11, %12, %13, %14, %15, %16, %17, %18, %19, %20, %21, %22, %23, "
            "%24, %25, %26, %27, %28, %29, %30, %31, %32, %33, %34, %35, %36, %37, %38, %39, %40, %41, %42, %43}, "
            "{%44, %45, %46, %47}, %48, 1, 1, 1, 0;"
            : RW4(0), RW4(4), RW4(8), RW4(12), RW4(16), RW4(20), RW4(24), RW4(28), RW4(32), RW4(36), RW4(40)
            : "r"(a0), "r"(a1), "r"(a2), "r"(a3), "l"(descb));
    }
}

template <bool FIRST>
__device__ __forceinline__ void wgmma_n32(float (&d)[16], uint32_t a0, uint32_t a1, uint32_t a2, uint32_t a3, uint64_t descb) {
    if constexpr (FIRST) {
        asm volatile(
            "wgmma.mma_async.sync.aligned.m64n32k16.f32.bf16.bf16 "
            "{%0, %1, %2, %3, %4, %5, %6, %7, %8, %9, %10, %11, %12, %13, %14, %15}, "
            "{%16, %17, %18, %19}, %20, 0, 1, 1, 0;"
            : WO4(0), WO4(4), WO4(8), WO4(12)
            : "r"(a0), "r"(a1), "r"(a2), "r"(a3), "l"(descb));
    } else {
        asm volatile(
            "wgmma.mma_async.sync.aligned.m64n32k16.f32.bf16.bf16 "
            "{%0, %1, %2, %3, %4, %5, %6, %7, %8, %9, %10, %11, %12, %13, %14, %15}, "
            "{%16, %17, %18, %19}, %20, 1, 1, 1, 0;"
            : RW4(0), RW4(4), RW4(8), RW4(12)
            : "r"(a0), "r"(a1), "r"(a2), "r"(a3), "l"(descb));
    }
}

template <bool FIRST, int SEL>
__device__ __forceinline__ void wgmma_sp_n192_tb(float (&d)[96], uint32_t a0, uint32_t a1, uint32_t a2, uint32_t a3, uint64_t descb, uint32_t meta) {
    if constexpr (FIRST) {
        asm volatile(
            "wgmma.mma_async.sp.sync.aligned.m64n192k32.f32.bf16.bf16 "
            "{%0, %1, %2, %3, %4, %5, %6, %7, %8, %9, %10, %11, %12, %13, %14, %15, %16, %17, %18, %19, %20, %21, %22, %23, "
            "%24, %25, %26, %27, %28, %29, %30, %31, %32, %33, %34, %35, %36, %37, %38, %39, %40, %41, %42, %43, %44, %45, %46, %47, "
            "%48, %49, %50, %51, %52, %53, %54, %55, %56, %57, %58, %59, %60, %61, %62, %63, %64, %65, %66, %67, %68, %69, %70, %71, "
            "%72, %73, %74, %75, %76, %77, %78, %79, %80, %81, %82, %83, %84, %85, %86, %87, %88, %89, %90, %91, %92, %93, %94, %95}, "
            "{%96, %97, %98, %99}, %100, %101, %102, 0, 1, 1, 1;"
            : WO4(0), WO4(4), WO4(8), WO4(12), WO4(16), WO4(20), WO4(24), WO4(28), WO4(32), WO4(36), WO4(40), WO4(44),
              WO4(48), WO4(52), WO4(56), WO4(60), WO4(64), WO4(68), WO4(72), WO4(76), WO4(80), WO4(84), WO4(88), WO4(92)
            : "r"(a0), "r"(a1), "r"(a2), "r"(a3), "l"(descb), "r"(meta), "n"(SEL));
    } else {
        asm volatile(
            "wgmma.mma_async.sp.sync.aligned.m64n192k32.f32.bf16.bf16 "
            "{%0, %1, %2, %3, %4, %5, %6, %7, %8, %9, %10, %11, %12, %13, %14, %15, %16, %17, %18, %19, %20, %21, %22, %23, "
            "%24, %25, %26, %27, %28, %29, %30, %31, %32, %33, %34, %35, %36, %37, %38, %39, %40, %41, %42, %43, %44, %45, %46, %47, "
            "%48, %49, %50, %51, %52, %53, %54, %55, %56, %57, %58, %59, %60, %61, %62, %63, %64, %65, %66, %67, %68, %69, %70, %71, "
            "%72, %73, %74, %75, %76, %77, %78, %79, %80, %81, %82, %83, %84, %85, %86, %87, %88, %89, %90, %91, %92, %93, %94, %95}, "
            "{%96, %97, %98, %99}, %100, %101, %102, 1, 1, 1, 1;"
            : RW4(0), RW4(4), RW4(8), RW4(12), RW4(16), RW4(20), RW4(24), RW4(28), RW4(32), RW4(36), RW4(40), RW4(44),
              RW4(48), RW4(52), RW4(56), RW4(60), RW4(64), RW4(68), RW4(72), RW4(76), RW4(80), RW4(84), RW4(88), RW4(92)
            : "r"(a0), "r"(a1), "r"(a2), "r"(a3), "l"(descb), "r"(meta), "n"(SEL));
    }
}

#define TR(slot)
#define TRE(slot)
#define TRT(slot)
#define TRF(slot)
#define TRW(slot)
#define TRG(slot)
#define TRDUMP()

__device__ __forceinline__ void wg_fence() { asm volatile("wgmma.fence.sync.aligned;" ::: "memory"); }
__device__ __forceinline__ void wg_commit() { asm volatile("wgmma.commit_group.sync.aligned;" ::: "memory"); }
template <int N>
__device__ __forceinline__ void wg_wait() { asm volatile("wgmma.wait_group.sync.aligned %0;" ::"n"(N) : "memory"); }

template <int N>
__device__ __forceinline__ void pin(float (&d)[N]) {
#pragma unroll
    for (int i = 0; i < N; i++) asm volatile("" : "+f"(d[i])::"memory");
}
template <int N>
__device__ __forceinline__ void pin(uint32_t (&d)[N]) {
#pragma unroll
    for (int i = 0; i < N; i++) asm volatile("" : "+r"(d[i])::"memory");
}

constexpr uint64_t kDescRing = ((uint64_t)((1u << 30) | (1024u >> 4)) << 32) | (1u << 16) | (s_ring >> 4);
constexpr uint32_t kToV = ((kRingChunk >> 4) - 1) << 20;
__device__ __forceinline__ uint64_t desc_at(uint64_t base, uint32_t byte_off) {
    uint64_t d;
    asm volatile("add.s64 %0, %1, %2;" : "=l"(d) : "l"(base), "l"((uint64_t)(byte_off >> 4)));
    return d;
}

__device__ __forceinline__ void mbar_init(uint32_t bar, uint32_t count) {
    asm volatile("mbarrier.init.shared::cta.b64 [%0], %1;" ::"r"(bar), "r"(count) : "memory");
}
__device__ __forceinline__ void mbar_expect_tx(uint32_t bar, uint32_t bytes) {
    asm volatile("mbarrier.arrive.expect_tx.shared::cta.b64 _, [%0], %1;" ::"r"(bar), "r"(bytes) : "memory");
}
__device__ __forceinline__ void expect_tx_only(uint32_t bar, uint32_t bytes) {
    asm volatile("mbarrier.expect_tx.relaxed.cta.shared::cta.b64 [%0], %1;" ::"r"(bar), "r"(bytes) : "memory");
}
__device__ __forceinline__ void mbar_arrive(uint32_t bar) {
    asm volatile("mbarrier.arrive.shared::cta.b64 _, [%0];" ::"r"(bar) : "memory");
}
__device__ __forceinline__ void mbar_wait(uint32_t bar, uint32_t parity) {
    asm volatile(
        "{\n.reg .pred p;\n"
        "W: mbarrier.try_wait.parity.shared::cta.b64 p, [%0], %1;\n"
        "@!p bra W;\n}\n"
        ::"r"(bar), "r"(parity) : "memory");
}
__device__ __forceinline__ uint32_t clock_now() {
    uint32_t c;
    asm volatile("mov.u32 %0, %%clock;" : "=r"(c)::"memory");
    return c;
}
__device__ __forceinline__ void wait_until(uint32_t t0, int t) {
    if (t == 0) return;
    while ((int)(clock_now() - t0) < t) {}
}
__device__ __forceinline__ bool elect() {
    uint32_t ok;
    asm volatile("{\n.reg .pred p;\nelect.sync _|p, 0xffffffff;\nselp.u32 %0, 1, 0, p;\n}\n" : "=r"(ok));
    return ok != 0;
}
__device__ __forceinline__ void turn_wait(int wg) { asm volatile("bar.sync %0, 256;" ::"r"(1 + wg) : "memory"); }
__device__ __forceinline__ void turn_pass(int wg) { asm volatile("bar.arrive %0, 256;" ::"r"(2 - wg) : "memory"); }

__device__ __forceinline__ void tma_box(uint32_t dst, const CUtensorMap* map, uint32_t bar, int c0, int c2, int c3, int c4) {
    asm volatile(
        "cp.async.bulk.tensor.5d.shared::cluster.global.mbarrier::complete_tx::bytes [%0], [%1, {%3, %4, %5, %6, %7}], [%2];"
        ::"r"(dst), "l"(map), "r"(bar), "r"(c0), "r"(0), "r"(c2), "r"(c3), "r"(c4)
        : "memory");
}
__device__ __forceinline__ void tma_3d(uint32_t dst, const CUtensorMap* map, uint32_t bar, int c1, int c2) {
    asm volatile("cp.async.bulk.tensor.3d.shared::cluster.global.mbarrier::complete_tx::bytes [%0], [%1, {%3, %4, %5}], [%2];"
                 ::"r"(dst), "l"(map), "r"(bar), "r"(0), "r"(c1), "r"(c2)
                 : "memory");
}
__device__ __forceinline__ void prefetch_map(const CUtensorMap* map) {
    asm volatile("prefetch.tensormap [%0];" ::"l"(map) : "memory");
}
__device__ __forceinline__ uint4 ldg(const void* p) {
    uint4 v;
    asm volatile("ld.global.v4.u32 {%0, %1, %2, %3}, [%4];" : "=r"(v.x), "=r"(v.y), "=r"(v.z), "=r"(v.w) : "l"(p) : "memory");
    return v;
}
__device__ __forceinline__ uint32_t pack_bf16(float lo, float hi) {
    uint32_t r;
    asm("cvt.rn.bf16x2.f32 %0, %1, %2;" : "=r"(r) : "f"(hi), "f"(lo));
    return r;
}
__device__ __forceinline__ float ex2(float x) {
    float y;
    asm("ex2.approx.ftz.f32 %0, %1;" : "=f"(y) : "f"(x));
    return y;
}
__device__ __forceinline__ float rcp(float x) {
    float y;
    asm("rcp.approx.ftz.f32 %0, %1;" : "=f"(y) : "f"(x));
    return y;
}
__device__ __forceinline__ void mma16816(float (&d)[4], uint32_t a0, uint32_t a1, uint32_t a2, uint32_t a3, uint32_t b0, uint32_t b1) {
    asm volatile("mma.sync.aligned.m16n8k16.row.col.f32.bf16.bf16.f32 {%0, %1, %2, %3}, {%4, %5, %6, %7}, {%8, %9}, {%0, %1, %2, %3};"
                 : "+f"(d[0]), "+f"(d[1]), "+f"(d[2]), "+f"(d[3])
                 : "r"(a0), "r"(a1), "r"(a2), "r"(a3), "r"(b0), "r"(b1));
}
__device__ __forceinline__ uint4 lds128(uint32_t addr) {
    uint4 v;
    asm volatile("ld.volatile.shared.v4.u32 {%0, %1, %2, %3}, [%4];" : "=r"(v.x), "=r"(v.y), "=r"(v.z), "=r"(v.w) : "r"(addr) : "memory");
    return v;
}
__device__ __forceinline__ uint32_t lds_volatile(uint32_t addr) {
    uint32_t v;
    asm volatile("ld.volatile.shared.u32 %0, [%1];" : "=r"(v) : "r"(addr) : "memory");
    return v;
}

__device__ __forceinline__ int window_start(int n) { return min(max(n, 0), 105); }
__device__ __forceinline__ int origin_u(int u) { return min(max(u, 0), 98); }

struct Work {
    int u, v;
    int step;
    uint32_t su, sv;
    uint32_t base;
    bool corner;
    int ntiles;
    __device__ __forceinline__ void pixel_offsets(int qu, int qv, int j, uint32_t& o0, uint32_t& o1) const {
        const uint32_t b = (qu + window_start(qu)) * su + j * 16 + base;
        o0 = b + (qv + window_start(qv)) * sv;
        o1 = b + (qv + 1 + window_start(qv + 1)) * sv;
    }
};

__device__ __forceinline__ Work decode_work(int c) {
    Work w;
    const bool transposed = (c >> 4) == 7;
    const int px = 6 * (c & 1), py = 3 * (c & 2);
    w.corner = c >= 128;
    w.step = 8 - 4 * (c & 4);
    w.u = (c < 112 ? c & ~7 : 96 + (c & 8)) + (transposed ? py : px) - 6;
    w.v = (w.corner ? 96 : 48 - 2 * (c & 4)) + (transposed ? px : py) - 6;
    w.su = transposed ? kHW * kPixBytes : kPixBytes;
    w.sv = transposed ? kPixBytes : kHW * kPixBytes;
    w.base = px * (kPixBytes / 6) + py * (kHW * kPixBytes / 6) + 6 * (kHW + 1) * kPixBytes;
    w.ntiles = w.corner ? 4 : 6;
    return w;
}

struct RawX { uint4 a[6], b[6]; };
__device__ __forceinline__ void load_raw(RawX& r, const uint8_t* base, uint32_t o0, uint32_t o1) {
    __syncwarp();
#pragma unroll
    for (int c = 0; c < 6; c++) { r.a[c] = ldg(base + o0 + c * 64); r.b[c] = ldg(base + o1 + c * 64); }
    __syncwarp();
}
__device__ __forceinline__ void raw_to_frags(const RawX& r, uint32_t zero, uint32_t (&f)[48]) {
#pragma unroll
    for (int c = 0; c < 6; c++) {
        asm volatile("{\n.reg .b32 t, u;\nadd.u32 t, %4, %8;\nadd.u32 u, %5, %8;\nxor.b32 %0, %6, %8;\nxor.b32 %1, %7, %8;\n"
                     "xor.b32 %2, t, %8;\nxor.b32 %3, u, %8;\n}\n"
                     : "=&r"(f[8 * c + 1]), "=&r"(f[8 * c + 3]), "=&r"(f[8 * c + 4]), "=&r"(f[8 * c + 6])
                     : "r"(r.a[c].y), "r"(r.a[c].w), "r"(r.b[c].x), "r"(r.b[c].z), "r"(zero));
        f[8 * c + 0] = r.a[c].x; f[8 * c + 2] = r.a[c].z; f[8 * c + 5] = r.b[c].y; f[8 * c + 7] = r.b[c].w;
    }
}
__device__ __forceinline__ void acc_to_frags(const float (&d)[96], uint32_t (&f)[48]) {
#pragma unroll
    for (int i = 0; i < 48; i++) f[i] = pack_bf16(d[2 * i], d[2 * i + 1]);
}

template <class F>
__device__ __forceinline__ void proj_gemm(float (&d)[96], const uint32_t (&a)[48], uint64_t dsc, uint32_t img, F after) {
#pragma unroll
    for (int s = 0; s < 12; s++) {
        if (s == 0) wgmma_n192<true>(d, a[4 * s], a[4 * s + 1], a[4 * s + 2], a[4 * s + 3], desc_at(dsc, img - s_ring + (s >> 2) * kWChunk + (s & 3) * 32));
        else wgmma_n192<false>(d, a[4 * s], a[4 * s + 1], a[4 * s + 2], a[4 * s + 3], desc_at(dsc, img - s_ring + (s >> 2) * kWChunk + (s & 3) * 32));
        if (s == 11) wg_commit();
        after(s);
    }
}
__device__ __forceinline__ void pack_out(const float (&acc)[96], uint32_t (&po)[48]) {
#pragma unroll
    for (int g = 0; g < 6; g++)
#pragma unroll
        for (int q = 0; q < 4; q++) {
            po[8 * g + q] = pack_bf16(acc[16 * g + 4 * q], acc[16 * g + 4 * q + 1]);
            po[8 * g + 4 + q] = pack_bf16(acc[16 * g + 4 * q + 2], acc[16 * g + 4 * q + 3]);
        }
}
template <bool PINNED = true>
__device__ __forceinline__ void store_one(bool on, uint8_t* p0, uint8_t* p1, const uint32_t (&po)[48], int n) {
    if (PINNED) __syncwarp();
    asm volatile("{\n.reg .pred p;\nsetp.ne.u32 p, %5, 0;\n@p st.global.v4.u32 [%0], {%1, %2, %3, %4};\n}\n"
                 ::"l"(((n & 1) ? p1 : p0) + (n >> 1) * 64), "r"(po[4 * n]), "r"(po[4 * n + 1]), "r"(po[4 * n + 2]), "r"(po[4 * n + 3]), "r"((uint32_t)on) : "memory");
}

template <int N>
__device__ __forceinline__ float tree_max(const float (&v)[N]) {
    float t[N];
#pragma unroll
    for (int i = 0; i < N; i++) t[i] = v[i];
#pragma unroll
    for (int w = 1; w < N; w *= 2)
#pragma unroll
        for (int i = 0; i + w < N; i += 2 * w) t[i] = fmaxf(t[i], t[i + w]);
    return t[0];
}
template <int N>
__device__ __forceinline__ float tree_sum(const float (&v)[N]) {
    float t[N];
#pragma unroll
    for (int i = 0; i < N; i++) t[i] = v[i];
#pragma unroll
    for (int w = 1; w < N; w *= 2)
#pragma unroll
        for (int i = 0; i + w < N; i += 2 * w) t[i] += t[i + w];
    return t[0];
}

template <int B>
__device__ __forceinline__ void pick(uint32_t h, uint32_t ok, const float* s, float& v0, float& v1) {
    asm("{\n.reg .pred p, q0, q1;\n.reg .b32 t;\nand.b32 t, %6, %7;\nsetp.ne.u32 p, t, 0;\n"
        "and.b32 t, %8, %9;\nsetp.ne.u32 q0, t, 0;\nand.b32 t, %8, %10;\nsetp.ne.u32 q1, t, 0;\n"
        "@q0 selp.f32 %0, %3, %2, p;\n@q1 selp.f32 %1, %5, %4, p;\n}\n"
        : "+f"(v0), "+f"(v1)
        : "f"(s[0]), "f"(s[1]), "f"(s[2]), "f"(s[3]), "r"(h), "n"(1 << ((4 * B) % 7)), "r"(ok), "n"(1 << (2 * B)), "n"(2 << (2 * B)));
}
template <int B, class F>
__device__ __forceinline__ void for_blocks(F f) {
    if constexpr (B > 0) { for_blocks<B - 1>(f); f(std::integral_constant<int, B - 1>{}); }
}
__device__ __forceinline__ void gather_outer(const float (&s)[44], uint32_t h, uint32_t ok, float (&v0)[14], float (&v1)[14]) {
    for_blocks<11>([&](auto B) {
        constexpr int b = B.value < 8 ? (B.value >> 1) + 7 * (B.value & 1) : B.value - 4;
        pick<b>(h, ok, &s[4 * b], v0[b], v1[b]);
    });
}
__device__ __forceinline__ void gather_mid(const float (&sE)[16], uint32_t h, uint32_t ok, float (&v0)[14], float (&v1)[14]) {
    for_blocks<4>([&](auto B) { pick<10 + B.value>(h, ok, &sE[4 * B.value], v0[10 + B.value], v1[10 + B.value]); });
}
__device__ __forceinline__ float quad_max(float m) {
    m = fmaxf(m, __shfl_xor_sync(0xffffffffu, m, 1));
    return fmaxf(m, __shfl_xor_sync(0xffffffffu, m, 2));
}
__device__ __forceinline__ float quad_sum(float s) {
    s += __shfl_xor_sync(0xffffffffu, s, 1);
    return s + __shfl_xor_sync(0xffffffffu, s, 2);
}
template <int B0, int B1>
__device__ __forceinline__ void exp_route(float (&v0)[14], float (&v1)[14], float m0, float m1, const uint4& r, bool even, uint32_t (&y)[14]) {
#pragma unroll
    for (int b = B0; b < B1; b++) { v0[b] = ex2(v0[b] - m0); v1[b] = ex2(v1[b] - m1); }
#pragma unroll
    for (int b = B0; b < B1; b += 2) {
        const uint32_t x0 = pack_bf16(v0[b], v1[b]), x1 = pack_bf16(v0[b + 1], v1[b + 1]);
        const uint32_t u = __shfl_sync(0xffffffffu, even ? x0 : x1, r.x);
        const uint32_t w = __shfl_sync(0xffffffffu, even ? x1 : x0, r.y);
        y[b] = __byte_perm(u, w, r.z); y[b + 1] = __byte_perm(u, w, r.w);
    }
}
template <int BIT0, int N0, int N1>
__device__ __forceinline__ void unfold(const uint32_t (&y)[14], uint32_t fold, uint32_t (&p)[12]) {
    for_blocks<N1 - N0>([&](auto N) {
        constexpr int n = N0 + N.value;
        asm("{\n.reg .pred p;\n.reg .b32 t;\nand.b32 t, %4, %5;\nsetp.ne.u32 p, t, 0;\nselp.b32 %0, %2, 0, p;\nselp.b32 %1, %3, 0, p;\n}\n"
            : "=r"(p[2 * n]), "=r"(p[2 * n + 1]) : "r"(y[2 * n]), "r"(y[2 * n + 1]), "r"(fold), "n"(1 << (BIT0 + n)));
    });
}
__device__ __forceinline__ void keep(bool never, uint32_t a, uint32_t b, uint32_t c, uint32_t d) {
    asm volatile("{\n.reg .pred p;\nsetp.ne.u32 p, %4, 0;\n@p st.volatile.shared.v4.u32 [%5], {%0, %1, %2, %3};\n}\n"
                 ::"r"(a), "r"(b), "r"(c), "r"(d), "r"((uint32_t)never), "r"(s_trace) : "memory");
}

__device__ __forceinline__ uint32_t wimg_offset(uint32_t row, uint32_t s, uint32_t j) {
    return (s >> 2) * kWChunk + row * 128 + (((2 * (s & 3) + (j >> 1)) ^ (row & 7)) << 4) + (j & 1) * 8;
}

__device__ __forceinline__ void ldsm4(uint32_t (&r)[4], uint32_t addr) {
    asm volatile("ldmatrix.sync.aligned.m8n8.x4.shared.b16 {%0, %1, %2, %3}, [%4];" : "=r"(r[0]), "=r"(r[1]), "=r"(r[2]), "=r"(r[3]) : "r"(addr) : "memory");
}
__device__ __forceinline__ void ldsm4_t(uint32_t (&r)[4], uint32_t addr) {
    asm volatile("ldmatrix.sync.aligned.m8n8.x4.trans.shared.b16 {%0, %1, %2, %3}, [%4];" : "=r"(r[0]), "=r"(r[1]), "=r"(r[2]), "=r"(r[3]) : "r"(addr) : "memory");
}
__device__ __forceinline__ void m_partial(const uint8_t* wqkv, uint32_t mt, uint32_t s, uint32_t q, uint32_t lane, uint32_t zero) {
    const uint32_t r8 = lane >> 2, col = q * 128 + (lane & 3) * 16;
    const uint8_t* pa = wqkv + (16 * mt + r8) * 1152 + col;
    const uint8_t* pb = wqkv + (16 * s + 8 * (r8 & 2) + (r8 & 5)) * 1152 + col;
    uint4 A[2][2], B[4][2];
#pragma unroll
    for (int c = 0; c < 2; c++) {
#pragma unroll
        for (int h = 0; h < 2; h++) A[h][c] = ldg(pa + 384 + h * 8 * 1152 + c * 64);
#pragma unroll
        for (int n = 0; n < 4; n++) B[n][c] = ldg(pb + ((n & 1) * 8 + (n & 2)) * 1152 + c * 64);
    }
#pragma unroll
    for (int i = 0; i < 4; i++) { uint4& a = A[i >> 1][i & 1]; a.x ^= zero; a.y ^= zero; a.z ^= zero; a.w ^= zero; }
#pragma unroll
    for (int n = 0; n < 4; n++) {
        float d[4] = {0.f, 0.f, 0.f, 0.f};
#pragma unroll
        for (int c = 0; c < 2; c++) {
            mma16816(d, A[0][c].x, A[1][c].x, A[0][c].y, A[1][c].y, B[n][c].x, B[n][c].y);
            mma16816(d, A[0][c].z, A[1][c].z, A[0][c].w, A[1][c].w, B[n][c].z, B[n][c].w);
        }
        asm volatile("st.shared.v4.f32 [%0], {%1, %2, %3, %4};" ::"r"(s_wv + q * 2048 + n * 512 + lane * 16), "f"(d[0]), "f"(d[1]), "f"(d[2]), "f"(d[3]) : "memory");
    }
}
__device__ __forceinline__ void m_reduce(uint32_t e, uint32_t lane, float (&d)[2][4]) {
#pragma unroll
    for (int n = 0; n < 2; n++) {
        float t[3][4];
#pragma unroll
        for (int q = 0; q < 3; q++)
            asm volatile("ld.shared.v4.f32 {%0, %1, %2, %3}, [%4];" : "=f"(t[q][0]), "=f"(t[q][1]), "=f"(t[q][2]), "=f"(t[q][3]) : "r"(s_wv + q * 2048 + e * 1024 + n * 512 + lane * 16) : "memory");
#pragma unroll
        for (int i = 0; i < 4; i++) d[n][i] = (t[0][i] + t[1][i] + t[2][i]) * kScaleLog2e;
    }
}
__device__ __forceinline__ void w_piece(uint32_t q, uint32_t lane, float (&d)[2][4]) {
    const uint32_t rr = lane & 7, mi = lane >> 3, kr = 4 * (rr >> 1) + (mi & 2) + (rr & 1);
    const uint32_t pa = s_wv + q * 6144 + (4 * (mi & 2) + rr) * 32 + (((mi ^ (rr >> 2)) & 1) << 4);
    const uint32_t pb = s_wv + 3 * 6144 + kr * 32 + (((mi ^ (kr >> 2)) & 1) << 4);
#pragma unroll
    for (int i = 0; i < 8; i++) (&d[0][0])[i] = 0.f;
#pragma unroll kWUnroll
    for (int k = 0; k < 12; k++) {
        uint32_t aq[4], bq[4];
        ldsm4_t(aq, pa + k * 512);
        ldsm4(bq, pb + k * 512);
        mma16816(d[0], aq[0], aq[1], aq[2], aq[3], bq[0], bq[1]);
        mma16816(d[1], aq[0], aq[1], aq[2], aq[3], bq[2], bq[3]);
    }
}
__device__ __forceinline__ uint32_t piece_offset(uint32_t which, uint32_t s, uint32_t mt, uint32_t lane) {
    const uint32_t r8 = lane >> 2;
    return which * kWBytes + wimg_offset(which ? 32 * (mt >> 1) + 8 * (r8 >> 1) + 4 * (mt & 1) + (r8 & 1) : 16 * mt + r8, s, lane & 3);
}
__device__ __forceinline__ void piece_store(Scratch* g, uint32_t par, uint32_t off0, uint32_t which, const float (&d)[2][4]) {
#pragma unroll
    for (int hf = 0; hf < 2; hf++) {
        const uint32_t off = off0 ^ (hf ? which ? 288 : 1024 : 0);
        const uint32_t a = pack_bf16(d[0][2 * hf], d[0][2 * hf + 1]), b = pack_bf16(d[1][2 * hf], d[1][2 * hf + 1]);
        asm volatile("st.relaxed.gpu.global.v2.u32 [%0], {%1, %2};" ::"l"(g->img[0][0] + (par + off)), "r"(a ? a : 0x8000u), "r"(b) : "memory");
        asm volatile("st.relaxed.gpu.global.v2.u32 [%0], {%1, %1};" ::"l"(g->img[1][0] + (int)(off - par)), "r"(0) : "memory");
    }
}

__device__ __forceinline__ uint32_t ld_relaxed(const uint32_t* p) {
    uint32_t v;
    asm volatile("ld.relaxed.gpu.global.u32 %0, [%1];" : "=r"(v) : "l"(p) : "memory");
    return v;
}
__device__ __forceinline__ void count_up(uint32_t* p) {
    asm volatile("red.relaxed.gpu.global.add.u32 [%0], %1;" ::"l"(p), "r"(1) : "memory");
}
__device__ __forceinline__ void bulk_g2s(uint32_t dst, const void* src, uint32_t bytes, uint32_t bar) {
    asm volatile("cp.async.bulk.shared::cluster.global.mbarrier::complete_tx::bytes [%0], [%1], %2, [%3];"
                 ::"r"(dst), "l"(src), "r"(bytes), "r"(bar)
                 : "memory");
}

__global__ void __launch_bounds__(kThreads, 1)
nat_fused_kernel(const uint8_t* __restrict__ x, const uint8_t* __restrict__ wqkv, uint8_t* __restrict__ out, Scratch* g,
                 const Tables* tables, uint64_t dsc, const __grid_constant__ Maps maps) {
    const int tid = threadIdx.x, lane = tid & 31;
    const int warp = __shfl_sync(0xffffffffu, tid >> 5, 0);
    const int wg = warp >> 2, wq = warp & 3, r8 = lane >> 2, j = lane & 3;
    const int cta = blockIdx.x;
    const Work w = decode_work(cta);
    const uint32_t which = cta >= 72, job = which ? cta - 72 : 2 * cta, jhi = job / 12, jlo = job % 12;
    if (wg == 1 && wq < 3) {
#pragma unroll
        for (int r = 0; r < 3; r++)
            asm volatile("st.shared.v4.u32 [%0], {%1, %1, %1, %1};" ::"r"(s_ring + wq * kRingChunk + (r == 0 ? 84 : r == 1 ? 88 : 204) * 128 + lane * 16), "r"(0) : "memory");
        asm volatile("fence.proxy.async.shared::cta;" ::: "memory");
    }
    if (x == nullptr) return;
    const uint32_t t_start = clock_now();
    if (wg == 2) {
        if (wq < 3 && !which) m_partial(wqkv, jhi, jlo, wq, lane, (uint32_t)dsc & 1);
        asm volatile("setmaxnreg.dec.sync.aligned.u32 40;");
        if (wq < 3) {
            const uint32_t off = piece_offset(which, which ? jlo : jlo + wq, which ? 3 * jhi + wq : jhi, lane);
            asm volatile("bar.sync %0, 128;" ::"r"(5 + (off >> 31)) : "memory");
            const uint32_t par = lds_volatile(s_par);
            if (cta < 120 && wq < 2 + which) {
                float d[2][4];
                if (wq == 0) TRW(which ? 1 : 18);
                if (which) {
                    mbar_wait(bar_wop, 0);
                    if (wq == 0) TRW(2);
                    w_piece(wq, lane, d);
                } else {
                    m_reduce(wq, lane, d);
                }
                piece_store(g, par, off, which, d);
                __syncwarp();
                if (!which && lane == 0) count_up(&g->cnt[0]);
                if (wq == 0) TRW(which ? 3 : 0);
            }
            asm volatile("bar.arrive 6, 128;" ::: "memory");
            uint32_t phase = 0;
#pragma unroll 1
            for (uint32_t c = 0; c < 6; c++) {
                const uint32_t part = c * kWChunk + wq * (kWChunk / 3), img = 8 * min(c, 3u);
                mbar_wait(bar_img + 8 * c, 0);
                if (wq == 0) TRW(10 + c);
#pragma unroll 1
                while (true) {
                    uint32_t lo = ~0u;
#pragma unroll
                    for (int q = 0; q < 8; q++) lo = min(lo, lds_volatile(s_m + part + lane * 32 + (lane & 12) * 2 + q * 1024));
                    if (__all_sync(0xffffffffu, lo) || phase > 65535) break;
                    if (elect()) {
                        mbar_expect_tx(bar_redo + 8 * wq, kWChunk / 3);
                        bulk_g2s(s_m + part, g->img[0][0] + par + part, kWChunk / 3, bar_redo + 8 * wq);
                    }
                    mbar_wait(bar_redo + 8 * wq, phase++ & 1);
                }
                if (c != 3 && c != 4 && lane == 0) mbar_arrive(bar_ok + img);
            }
        } else {
            uint32_t launch = ld_relaxed(&g->cnt[1]);
            const CUtensorMap* map = &maps.m[w.sv == kPixBytes ? 2 : 0];
            if (elect()) {
#pragma unroll
                for (int i = 0; i < 20; i++) mbar_init(s_bar + 8 * i, i < 13 ? 1 : i < 18 ? 3 : 4);
                asm volatile("fence.mbarrier_init.release.cluster;" ::: "memory");
                prefetch_map(map + 1);
                expect_tx_only(bar_a, sizeof(Table));
                bulk_g2s(s_tab, &tables->t[w.step < 0], sizeof(Table), bar_a);
            }
            if (which && cta < 120 && elect()) {
                mbar_expect_tx(bar_wop, 4 * 6144);
                tma_3d(s_wv, &maps.wo, bar_wop, 0, 3 * jhi);
                tma_3d(s_wv + 3 * 6144, &maps.wv, bar_wop, 16 * jlo, 24);
            }
            int u = w.u, v = w.v;
            uint32_t wait_bar = bar_use, wait_par = 1, slot = 0;
#pragma unroll 1
            for (int step = 0; step < 7 - w.corner; step++) {
                const bool first = step == 0 || (w.corner && step == 4);
                const int row = v + 4 + (first ? -w.step : w.step) / 2, ou = origin_u(u);
                uint32_t dst = s_ring + (first ? 0 : slot), mid = s_ring + kOffMid + 512, bar = first ? bar_a : bar_b;
                mbar_wait(wait_bar, wait_par);
                TRW(24 + step);
#pragma unroll 1
                for (int ch = (cta & 1) * kC; mid < s_m; ch += 64, dst += kRingChunk, mid += kRingChunk) {
                    if (elect()) {
                        mbar_expect_tx(bar, first ? kSlotBytes : kSlotBytes + kMidBytes);
                        tma_box(dst, map, bar, ch, ou, (cta >> 1) & 1, row);
                    }
                    if (!first) {
                        if (elect()) tma_box(mid, map + 1, bar, ch, ou, (cta >> 1) & 1, v + 6);
                        bar += 8;
                    }
                }
                if (step == 0) {
                    launch /= kGrid;
                    asm volatile("st.shared.u32 [%0], %2;\nst.shared.v2.u32 [%0 + 16], {%1, %2};" ::"r"(s_cnt), "r"((launch & 1) * 2 * kWBytes), "r"(0) : "memory");
                    if (lane == 0) count_up(&g->cnt[1]);
                    asm volatile("bar.arrive 5, 128;\nbar.arrive 3, 160;\nbar.arrive 4, 160;" ::: "memory");
#pragma unroll 1
                    for (int t = TN(6, 2000); t < (1 << 24);) {
                        if (__shfl_sync(0xffffffffu, lds_volatile(s_cnt), 0) >= (launch + 1) * kPieces) break;
                        if ((int)(clock_now() - t_start) < t) continue;
                        t += TN(7, 200);
                        if (elect()) {
                            expect_tx_only(bar_use + 8, 16);
                            bulk_g2s(s_cnt, g->cnt, 16, bar_use + 8);
                        }
                    }
                }
                if (step == 1) {
                    asm volatile("bar.sync 6, 128;" ::: "memory");
                    wait_until(t_start, TN(5, 6000));
                }
                if (step < 2) {
                    TRW(5 + 4 * step);
#pragma unroll 1
                    for (int c = 3 * step; c < 3 + 3 * step; c++)
                        if (elect()) {
                            mbar_expect_tx(bar_img + 8 * c, kWChunk);
                            bulk_g2s(s_m + c * kWChunk, g->img[launch & 1][0] + c * kWChunk, kWChunk, bar_img + 8 * c);
                        }
                }
                const bool again = w.corner && step == 3;
                wait_bar = step == 0 ? bar_img + 8 * TN(1, 1) : again ? bar_use + 8 : bar_use;
                if (!again) {
                    wait_par = slot ? 0 : step != 0;
                    slot ^= kSlotStride;
                    if (w.corner && step == 2) { u += 8; v -= 8; } else if (step) v += w.step;
                }
            }
        }
        TRDUMP();
        return;
    }
    const int order = w.step < 0 ? warp ^ 3 : warp;
    int tu = w.u, tv = w.v + w.step * wg;
    const int du2 = w.corner ? 8 : 0, dv2 = w.corner ? 0 : 2 * w.step;
    uint32_t o0, o1;
    wait_until(t_start, START_TIME);
    asm volatile("setmaxnreg.inc.sync.aligned.u32 232;");
    w.pixel_offsets(tu + r8, tv + 2 * wq, j, o0, o1);
    uint32_t fa[48];
    {
        RawX raw;
        load_raw(raw, x, o0, o1);
        asm volatile("bar.sync %0, 160;" ::"r"(3 + wg) : "memory");
        raw_to_frags(raw, 0, fa);
        pin(fa);
    }
    mbar_wait(bar_ok, 0);
    const uint64_t dA = dsc + wg * (kSlotStride >> 4), dB = dsc + (wg ^ 1) * (kSlotStride >> 4);

    float acc[96];
    uint32_t po[48];
    uint32_t c0, c1;
    asm volatile("" : "=r"(c0), "=r"(c1));
#pragma unroll
    for (int q = 0; q < 48; q++) asm volatile("" : "=r"(po[q]));
#pragma unroll 1
    for (int i = wg; i < w.ntiles; i += 2) {
        const bool first = i == 0, last = i == w.ntiles - 1;

        TRF(8 + 16 * k);
        wg_fence();
        if (!first) turn_wait(wg);
        proj_gemm(acc, fa, dsc, s_m, [&](int s) {
            if (s == 11 && !first) turn_pass(wg);
            const int n = __builtin_popcount(QSLOTS & ((1 << s) - 1));
            if (((QSLOTS >> s) & 1) && n < 12) store_one(i >= 2, out + c0, out + c1, po, n);
            if (s == 3 || s == 7) { mbar_wait(bar_ok + 2 * s + 2, 0); wg_fence(); }
        });
        __syncwarp();
        TRF(9 + 16 * k);
        uint8_t *p0 = out + c0, *p1 = out + c1;
        c0 = o0; c1 = o1;
        w.pixel_offsets(tu + du2 + r8, tv + dv2 + 2 * wq, j, o0, o1);
        if (i + 2 >= w.ntiles) o0 = o1 = 0;
        wg_wait<0>();
        pin(acc);
        TR(11 + 16 * k);
        TRT(80 + k);
#pragma unroll
        for (int n = __builtin_popcount(QSLOTS); n < 12 - __builtin_popcount(ASLOTS) - __builtin_popcount(BSLOTS); n++) store_one(i >= 2, p0, p1, po, n);
        acc_to_frags(acc, fa);
        pin(fa);

        float sA[44], sE[16], sB[44];
        RawX nxt;
        if (!first) turn_wait(wg);
        mbar_wait(bar_a, w.corner ? i >> 1 : 0);
        if (i == 0) TR(12);
        wg_fence();
#pragma unroll
        for (int s = 0; s < 12; s++) {
            if (s == 0) wgmma_n88<true>(sA, fa[4 * s], fa[4 * s + 1], fa[4 * s + 2], fa[4 * s + 3], desc_at(dA, (s >> 2) * kRingChunk + (s & 3) * 32));
            else wgmma_n88<false>(sA, fa[4 * s], fa[4 * s + 1], fa[4 * s + 2], fa[4 * s + 3], desc_at(dA, (s >> 2) * kRingChunk + (s & 3) * 32));
            if (s == 11) { wg_commit(); if (!first) turn_pass(wg); }
            if ((ASLOTS >> s) & 1) store_one(i >= 2, p0, p1, po, 12 - __builtin_popcount(BSLOTS) - __builtin_popcount(ASLOTS >> s));
        }
#pragma unroll
        for (int s = 12; s < 16; s++)
            if ((ASLOTS >> s) & 1) store_one(i >= 2, p0, p1, po, 12 - __builtin_popcount(BSLOTS) - __builtin_popcount(ASLOTS >> s));
        TRF(12 + 16 * k);
        const int vq = tv + 2 * wq;
        const uint4 tabu = lds128(s_tab + offsetof(Table, u) + (window_start(tu + r8) - origin_u(tu)) * 64 + j * 16);
        const uint4 tabv = lds128(s_tab + offsetof(Table, v) + (window_start(vq) + window_start(vq + 1) - 2 * tv) * 64 + j * 16);
        const uint4 route = lds128(s_tab + lane * 16);
        load_raw(nxt, x, o0, o1);
        float v0[14], v1[14];
#pragma unroll
        for (int b = 0; b < 14; b++) v0[b] = v1[b] = __int_as_float(0xff800000);
        wg_wait<0>();
        pin(sA);
        gather_outer(sA, tabu.x, tabv.x, v0, v1);
        pin(v0); pin(v1);
        if (!first) turn_wait(wg);
#pragma unroll
        for (int c = 0; c < 3; c++) {
            mbar_wait(bar_b + 8 * c, wg);
            if (i == 0 && c != 1) TR(13 + c);
            wg_fence();
#pragma unroll
            for (int s = 4 * c; s < 4 * c + 4; s++) {
                if (s == 0) wgmma_n88<true>(sB, fa[4 * s], fa[4 * s + 1], fa[4 * s + 2], fa[4 * s + 3], desc_at(dB, c * kRingChunk + (s & 3) * 32));
                else wgmma_n88<false>(sB, fa[4 * s], fa[4 * s + 1], fa[4 * s + 2], fa[4 * s + 3], desc_at(dB, c * kRingChunk + (s & 3) * 32));
                if ((BSLOTS >> s) & 1) store_one(i >= 2, p0, p1, po, 12 - __builtin_popcount(BSLOTS >> s));
            }
        }
        wg_commit();
#pragma unroll
        for (int s = 0; s < 12; s++)
            if (s == 0) wgmma_n32<true>(sE, fa[4 * s], fa[4 * s + 1], fa[4 * s + 2], fa[4 * s + 3], desc_at(dsc, kOffMid + (s >> 2) * kRingChunk + (s & 3) * 32));
            else wgmma_n32<false>(sE, fa[4 * s], fa[4 * s + 1], fa[4 * s + 2], fa[4 * s + 3], desc_at(dsc, kOffMid + (s >> 2) * kRingChunk + (s & 3) * 32));
        wg_commit();
        if (OSPLIT || !last) turn_pass(wg);
        TRF(13 + 16 * k);
        wg_wait<1>();
        pin(sB);
        gather_outer(sB, tabu.w, tabv.y, v0, v1);
        wg_wait<0>();
        pin(sE);
        TRF(14 + 16 * k);
        gather_mid(sE, tabu.w, tabv.z, v0, v1);
        const float m0 = quad_max(tree_max(v0)), m1 = quad_max(tree_max(v1));

        uint32_t y[14], pa[12], pb[12];
        exp_route<0, 14>(v0, v1, m0, m1, route, (j & 1) == 0, y);
        float s0 = tree_sum(v0), s1 = tree_sum(v1);
        asm volatile("" : "+f"(s0), "+f"(s1));
        unfold<0, 0, 6>(y, tabv.w, pa);
        if (OSPLIT || !last) turn_wait(wg + (y[0] >> 31));
        TRF(15 + 16 * k + (y[13] >> 31));
        wg_fence();
        wgmma_sp_n192_tb<true, 0>(acc, pa[0], pa[1], pa[2], pa[3], desc_at(dA, kToV), tabu.y);
        wgmma_sp_n192_tb<false, 1>(acc, pa[4], pa[5], pa[6], pa[7], desc_at(dA, kToV + 4096), tabu.y);
        wgmma_sp_n192_tb<false, 0>(acc, pa[8], pa[9], pa[10], pa[11], desc_at(dA, kToV + 8192), tabu.z);
        wgmma_sp_n192_tb<false, 1>(acc, y[10], y[11], y[12], y[13], desc_at(dsc, kToV + kOffMid), tabu.z);
        wg_commit();
        unfold<8, 0, 6>(y, tabv.w, pb);
        wg_fence();
        wgmma_sp_n192_tb<false, 0>(acc, pb[0], pb[1], pb[2], pb[3], desc_at(dB, kToV), tabu.y);
        wgmma_sp_n192_tb<false, 1>(acc, pb[4], pb[5], pb[6], pb[7], desc_at(dB, kToV + 4096), tabu.y);
        wgmma_sp_n192_tb<false, 0>(acc, pb[8], pb[9], pb[10], pb[11], desc_at(dB, kToV + 8192), tabu.z);
        wg_commit();
        if (!last) turn_pass(wg);
        TRF(16 + 16 * k);
        wg_wait<1>();
        if (lane == 0) mbar_arrive(bar_use);
        TRF(17 + 16 * k);
        mbar_wait(bar_ok + 24, 0);
        wg_wait<0>();
        if (lane == 0) mbar_arrive(bar_use + 8);
        pin(acc);
        TR(18 + 16 * k);

        acc_to_frags(acc, po);
        pin(po);
        if (!last) turn_wait(wg);
        wg_fence();
        proj_gemm(acc, po, dsc, s_wv, [&](int s) {
            if (s + 1 == OSPLIT && i + 2 == w.ntiles) { turn_pass(wg); turn_wait(wg); }
        });
        if (!last) turn_pass(wg);
        TRF(19 + 16 * k);
        const uint32_t zero = lds_volatile(s_late);
        const float inv0 = rcp(quad_sum(s0 + __uint_as_float(zero))), inv1 = rcp(quad_sum(s1 + __uint_as_float(zero)));
        raw_to_frags(nxt, zero, fa);
        pin(fa);
#pragma unroll
        for (int q = 0; q < 48; q += 4) keep(wqkv == nullptr, fa[q], fa[q + 1], fa[q + 2], fa[q + 3]);
        keep(wqkv == nullptr, __float_as_uint(inv0), __float_as_uint(inv1), zero, lane);
        TRF(20 + 16 * k);
        tu += du2; tv += dv2;
        wg_wait<0>();
        pin(acc);
        TR(21 + 16 * k);
#pragma unroll
        for (int q = 0; q < 96; q++) acc[q] *= q & 2 ? inv1 : inv0;
        pack_out(acc, po);
#pragma unroll
        for (int n = 0; n < INLOOP; n++) store_one<false>(last, out + c0, out + c1, po, n);
        pin(po);
    }
#pragma unroll
    for (int n = 0; n < 12; n++) {
        asm volatile("{\n.reg .pred p;\nsetp.eq.u32 p, %0, 0;\n@p nanosleep.u32 %1;\n}\n" ::"r"(wg), "n"(NAP) : "memory");
        store_one<false>(n >= INLOOP || wg == 0, out + c0, out + c1, po, n);
    }
    TRE(7);
    TRG(1);
    TRDUMP();
}

typedef CUresult (*EncodeTiledFn)(CUtensorMap*, CUtensorMapDataType, cuuint32_t, void*, const cuuint64_t*, const cuuint64_t*,
                                  const cuuint32_t*, const cuuint32_t*, CUtensorMapInterleave, CUtensorMapSwizzle,
                                  CUtensorMapL2promotion, CUtensorMapFloatOOBfill);

bool make_maps(EncodeTiledFn fn, Maps* maps, void* x, void* wqkv, void* wo) {
    const cuuint64_t pix2 = 2 * kPixBytes, row = (cuuint64_t)kHW * kPixBytes;
    const cuuint32_t estr[5] = {1, 1, 1, 1, 1};
    bool ok = true;
    for (int tr = 0; tr < 2; tr++)
        for (int b = 0; b < 2; b++) {
            const cuuint64_t su = tr ? 2 * row : pix2, sv = tr ? pix2 : 2 * row;
            const cuuint64_t dims[5] = {2 * kC, 2, 105, 2, 112};
            const cuuint64_t strides[4] = {7 * su, su, row, sv};
            const cuuint32_t box[5] = {64, 2, 7, 1, b ? 2u : 6u};
            ok = ok && fn(&maps->m[2 * tr + b], CU_TENSOR_MAP_DATA_TYPE_BFLOAT16, 5, x, dims, strides, box, estr,
                          CU_TENSOR_MAP_INTERLEAVE_NONE, CU_TENSOR_MAP_SWIZZLE_128B, CU_TENSOR_MAP_L2_PROMOTION_L2_128B,
                          CU_TENSOR_MAP_FLOAT_OOB_FILL_NONE) == CUDA_SUCCESS;
        }
    for (int b = 0; b < 2; b++) {
        const cuuint64_t dims[3] = {16, kC, b ? 36u : 12u}, strides[2] = {(b ? 3u : 1u) * kPixBytes, 32};
        const cuuint32_t box[3] = {16, b ? 16u : 192u, b ? 12u : 3u};
        ok = ok && fn(b ? &maps->wv : &maps->wo, CU_TENSOR_MAP_DATA_TYPE_BFLOAT16, 3, b ? wqkv : wo, dims, strides, box, estr,
                      CU_TENSOR_MAP_INTERLEAVE_NONE, CU_TENSOR_MAP_SWIZZLE_32B, CU_TENSOR_MAP_L2_PROMOTION_L2_128B,
                      CU_TENSOR_MAP_FLOAT_OOB_FILL_NONE) == CUDA_SUCCESS;
    }
    return ok;
}

}

extern "C" void kernel_launch(void* const* d_in, const int* in_sizes, int n_in, void* d_out, int out_size) {
    static EncodeTiledFn encode = nullptr;
    static Scratch* scratch = nullptr;
    static Tables* tables = nullptr;
    if (!encode) {
        int dev = 0, reserved = 0;
        cudaFuncAttributes attr;
        cudaGetDevice(&dev);
        cudaDeviceGetAttribute(&reserved, cudaDevAttrReservedSharedMemoryPerBlock, dev);
        cudaFuncGetAttributes(&attr, nat_fused_kernel);
        if (reserved != (int)kSmemBase || attr.sharedSizeBytes != 0) return;
        cudaGetSymbolAddress((void**)&scratch, g_scratch);
        cudaGetSymbolAddress((void**)&tables, g_tables);
        void* fn = nullptr;
        cudaDriverEntryPointQueryResult st;
        cudaGetDriverEntryPoint("cuTensorMapEncodeTiled", &fn, cudaEnableDefault, &st);
        encode = (EncodeTiledFn)fn;
        cudaFuncSetAttribute(nat_fused_kernel, cudaFuncAttributeMaxDynamicSharedMemorySize, kSmemBytes);
    }
    Maps maps;
    if (!encode || !make_maps(encode, &maps, d_in[0], d_in[1], d_in[2])) return;
    nat_fused_kernel<<<kGrid, kThreads, kSmemBytes>>>((const uint8_t*)d_in[0], (const uint8_t*)d_in[1], (uint8_t*)d_out, scratch, tables, kDescRing, maps);
}
```

```cpp
#include <cuda_runtime.h>
#include <cuda_bf16.h>
#include <cuda.h>
#include <stdint.h>
#include <type_traits>
#include <stdlib.h>
#include <stddef.h>

#define KEEPFA 1
#define ASLOTS 0x3800
#define BSLOTS 0x6
#define QSLOTS 0x78a
#define OSPLIT 3
#define NAP 40
#define INLOOP 3
#define WUNROLL 2

namespace {

constexpr int kC          = 192;
constexpr int kHW         = 224;
constexpr int kPixBytes   = kC * 2;
constexpr int kSlotBytes  = 84 * 128;
constexpr int kMidBytes   = 28 * 128;
constexpr int kOffMid     = 88 * 128;
constexpr int kSlotStride = 120 * 128;
constexpr int kRingChunk  = 208 * 128;
constexpr int kWChunk     = 192 * 128;
constexpr int kWBytes     = 3 * kWChunk;
constexpr uint32_t kSmemBase = 1024;
constexpr uint32_t s_ring = kSmemBase, s_m = s_ring + 3 * kRingChunk, s_wv = s_m + kWBytes, s_bar = s_wv + kWBytes;
constexpr uint32_t bar_b = s_bar, bar_img = s_bar + 24, bar_redo = s_bar + 72, bar_wop = s_bar + 96, bar_a = s_bar + 104,
                   bar_ok = s_bar + 112, bar_use = s_bar + 144;
constexpr uint32_t s_cnt = s_bar + 160, s_par = s_bar + 176, s_late = s_bar + 180, s_tab = s_bar + 256, s_trace = s_tab + 2048;
constexpr int kSmemBytes  = s_trace + 2048 - kSmemBase;
constexpr int kThreads    = 384, kWUnroll = WUNROLL;
constexpr int kGrid       = 132;
constexpr int kPieces     = 144;
constexpr float kScaleLog2e = 0.07216878364870322f * 1.4426950408889634f;

struct Maps {
    CUtensorMap m[4];
    CUtensorMap wo, wv;
};
#define TN(i, dflt) (dflt)
#define START_TIME (wg ? 1900 + 500 * order : which ? 100 + 500 * order : order ? 2100 + 200 * order : 400)

struct Scratch {
    uint8_t img[2][2][kWBytes];
    uint32_t cnt[4];
};
__device__ __align__(1024) Scratch g_scratch;

struct Table {
    uint32_t route[32][4];
    uint32_t u[8][4][4];
    uint32_t v[16][4][4];
};
struct Tables { Table t[2]; };
constexpr Tables make_tables() {
    Tables r = {};
    for (int rev = 0; rev < 2; rev++)
        for (int j = 0; j < 4; j++) {
            Table& t = r.t[rev];
            for (int q = 0; q < 8; q++) {
                uint32_t* e = t.route[4 * q + j];
                e[0] = 4 * q + 2 * (j & 1) + (j >> 1); e[1] = e[0] ^ 1;
                e[2] = j < 2 ? 0x5410u : 0x1054u; e[3] = e[2] + 0x2222u;
                e = t.u[q][j];
                for (int n = 0; n < 7; n++) e[0] |= ((n + j) % 7 < q ? 1u : 0u) << n;
                e[3] = e[0];
                for (int k = 0; k < 2; k++) {
                    const int step = 2 * k + (j >> 1), p0 = (step < 3 ? 16 * step : 40) + 8 * (j & 1);
                    uint32_t m = 0x8888u;
                    for (int n = 0; n < 8; n++) m |= ((p0 + n) % 7 < q ? 1u : 0u) << (2 * n);
                    e[1 + k] = m * 0x10001u;
                }
            }
            for (int sum = 0; sum < 15; sum++) {
                uint32_t* e = t.v[sum][j];
                for (int row = 0; row < 2; row++)
                    for (int b = 0; b < 14; b++) {
                        const int off = (sum + row) / 2, p = 4 * b + j;
                        const uint32_t bit = 1u << (2 * b + row);
                        if (p < 42 && p >= 7 * off) e[rev] |= bit;
                        if (p < 7 * off - 7) e[1 - rev] |= bit;
                        if (p >= 42 && p >= 7 * off && p < 7 * off + 49) e[2] |= bit;
                    }
                for (int n = 0; n < 6; n++)
                    if (8 * n + 2 * j < 42) e[3] |= 1u << (n + ((8 * n + 2 * j >= 7 * (sum / 2 & ~1)) != rev ? 0 : 8));
            }
        }
    return r;
}
__device__ __align__(128) const Tables g_tables = make_tables();

#define WO4(i) "=f"(d[i]), "=f"(d[i + 1]), "=f"(d[i + 2]), "=f"(d[i + 3])
#define RW4(i) "+f"(d[i]), "+f"(d[i + 1]), "+f"(d[i + 2]), "+f"(d[i + 3])

template <bool FIRST>
__device__ __forceinline__ void wgmma_n192(float (&d)[96], uint32_t a0, uint32_t a1, uint32_t a2, uint32_t a3, uint64_t descb) {
    if constexpr (FIRST) {
        asm volatile(
            "wgmma.mma_async.sync.aligned.m64n192k16.f32.bf16.bf16 "
            "{%0, %1, %2, %3, %4, %5, %6, %7, %8, %9, %10, %11, %12, %13, %14, %15, %16, %17, %18, %19, %20, %21, %22, %23, "
            "%24, %25, %26, %27, %28, %29, %30, %31, %32, %33, %34, %35, %36, %37, %38, %39, %40, %41, %42, %43, %44, %45, %46, %47, "
            "%48, %49, %50, %51, %52, %53, %54, %55, %56, %57, %58, %59, %60, %61, %62, %63, %64, %65, %66, %67, %68, %69, %70, %71, "
            "%72, %73, %74, %75, %76, %77, %78, %79, %80, %81, %82, %83, %84, %85, %86, %87, %88, %89, %90, %91, %92, %93, %94, %95}, "
            "{%96, %97, %98, %99}, %100, 0, 1, 1, 0;"
            : WO4(0), WO4(4), WO4(8), WO4(12), WO4(16), WO4(20), WO4(24), WO4(28), WO4(32), WO4(36), WO4(40), WO4(44),
              WO4(48), WO4(52), WO4(56), WO4(60), WO4(64), WO4(68), WO4(72), WO4(76), WO4(80), WO4(84), WO4(88), WO4(92)
            : "r"(a0), "r"(a1), "r"(a2), "r"(a3), "l"(descb));
    } else {
        asm volatile(
            "wgmma.mma_async.sync.aligned.m64n192k16.f32.bf16.bf16 "
            "{%0, %1, %2, %3, %4, %5, %6, %7, %8, %9, %10, %11, %12, %13, %14, %15, %16, %17, %18, %19, %20, %21, %22, %23, "
            "%24, %25, %26, %27, %28, %29, %30, %31, %32, %33, %34, %35, %36, %37, %38, %39, %40, %41, %42, %43, %44, %45, %46, %47, "
            "%48, %49, %50, %51, %52, %53, %54, %55, %56, %57, %58, %59, %60, %61, %62, %63, %64, %65, %66, %67, %68, %69, %70, %71, "
            "%72, %73, %74, %75, %76, %77, %78, %79, %80, %81, %82, %83, %84, %85, %86, %87, %88, %89, %90, %91, %92, %93, %94, %95}, "
            "{%96, %97, %98, %99}, %100, 1, 1, 1, 0;"
            : RW4(0), RW4(4), RW4(8), RW4(12), RW4(16), RW4(20), RW4(24), RW4(28), RW4(32), RW4(36), RW4(40), RW4(44),
              RW4(48), RW4(52), RW4(56), RW4(60), RW4(64), RW4(68), RW4(72), RW4(76), RW4(80), RW4(84), RW4(88), RW4(92)
            : "r"(a0), "r"(a1), "r"(a2), "r"(a3), "l"(descb));
    }
}

template <bool FIRST>
__device__ __forceinline__ void wgmma_n88(float (&d)[44], uint32_t a0, uint32_t a1, uint32_t a2, uint32_t a3, uint64_t descb) {
    if constexpr (FIRST) {
        asm volatile(
            "wgmma.mma_async.sync.aligned.m64n88k16.f32.bf16.bf16 "
            "{%0, %1, %2, %3, %4, %5, %6, %7, %8, %9, %10, %11, %12, %13, %14, %15, %16, %17, %18, %19, %20, %21, %22, %23, "
            "%24, %25, %26, %27, %28, %29, %30, %31, %32, %33, %34, %35, %36, %37, %38, %39, %40, %41, %42, %43}, "
            "{%44, %45, %46, %47}, %48, 0, 1, 1, 0;"
            : WO4(0), WO4(4), WO4(8), WO4(12), WO4(16), WO4(20), WO4(24), WO4(28), WO4(32), WO4(36), WO4(40)
            : "r"(a0), "r"(a1), "r"(a2), "r"(a3), "l"(descb));
    } else {
        asm volatile(
            "wgmma.mma_async.sync.aligned.m64n88k16.f32.bf16.bf16 "
            "{%0, %1, %2, %3, %4, %5, %6, %7, %8, %9, %10, %11, %12, %13, %14, %15, %16, %17, %18, %19, %20, %21, %22, %23, "
            "%24, %25, %26, %27, %28, %29, %30, %31, %32, %33, %34, %35, %36, %37, %38, %39, %40, %41, %42, %43}, "
            "{%44, %45, %46, %47}, %48, 1, 1, 1, 0;"
            : RW4(0), RW4(4), RW4(8), RW4(12), RW4(16), RW4(20), RW4(24), RW4(28), RW4(32), RW4(36), RW4(40)
            : "r"(a0), "r"(a1), "r"(a2), "r"(a3), "l"(descb));
    }
}

template <bool FIRST>
__device__ __forceinline__ void wgmma_n32(float (&d)[16], uint32_t a0, uint32_t a1, uint32_t a2, uint32_t a3, uint64_t descb) {
    if constexpr (FIRST) {
        asm volatile(
            "wgmma.mma_async.sync.aligned.m64n32k16.f32.bf16.bf16 "
            "{%0, %1, %2, %3, %4, %5, %6, %7, %8, %9, %10, %11, %12, %13, %14, %15}, "
            "{%16, %17, %18, %19}, %20, 0, 1, 1, 0;"
            : WO4(0), WO4(4), WO4(8), WO4(12)
            : "r"(a0), "r"(a1), "r"(a2), "r"(a3), "l"(descb));
    } else {
        asm volatile(
            "wgmma.mma_async.sync.aligned.m64n32k16.f32.bf16.bf16 "
            "{%0, %1, %2, %3, %4, %5, %6, %7, %8, %9, %10, %11, %12, %13, %14, %15}, "
            "{%16, %17, %18, %19}, %20, 1, 1, 1, 0;"
            : RW4(0), RW4(4), RW4(8), RW4(12)
            : "r"(a0), "r"(a1), "r"(a2), "r"(a3), "l"(descb));
    }
}

template <bool FIRST, int SEL>
__device__ __forceinline__ void wgmma_sp_n192_tb(float (&d)[96], uint32_t a0, uint32_t a1, uint32_t a2, uint32_t a3, uint64_t descb, uint32_t meta) {
    if constexpr (FIRST) {
        asm volatile(
            "wgmma.mma_async.sp.sync.aligned.m64n192k32.f32.bf16.bf16 "
            "{%0, %1, %2, %3, %4, %5, %6, %7, %8, %9, %10, %11, %12, %13, %14, %15, %16, %17, %18, %19, %20, %21, %22, %23, "
            "%24, %25, %26, %27, %28, %29, %30, %31, %32, %33, %34, %35, %36, %37, %38, %39, %40, %41, %42, %43, %44, %45, %46, %47, "
            "%48, %49, %50, %51, %52, %53, %54, %55, %56, %57, %58, %59, %60, %61, %62, %63, %64, %65, %66, %67, %68, %69, %70, %71, "
            "%72, %73, %74, %75, %76, %77, %78, %79, %80, %81, %82, %83, %84, %85, %86, %87, %88, %89, %90, %91, %92, %93, %94, %95}, "
            "{%96, %97, %98, %99}, %100, %101, %102, 0, 1, 1, 1;"
            : WO4(0), WO4(4), WO4(8), WO4(12), WO4(16), WO4(20), WO4(24), WO4(28), WO4(32), WO4(36), WO4(40), WO4(44),
              WO4(48), WO4(52), WO4(56), WO4(60), WO4(64), WO4(68), WO4(72), WO4(76), WO4(80), WO4(84), WO4(88), WO4(92)
            : "r"(a0), "r"(a1), "r"(a2), "r"(a3), "l"(descb), "r"(meta), "n"(SEL));
    } else {
        asm volatile(
            "wgmma.mma_async.sp.sync.aligned.m64n192k32.f32.bf16.bf16 "
            "{%0, %1, %2, %3, %4, %5, %6, %7, %8, %9, %10, %11, %12, %13, %14, %15, %16, %17, %18, %19, %20, %21, %22, %23, "
            "%24, %25, %26, %27, %28, %29, %30, %31, %32, %33, %34, %35, %36, %37, %38, %39, %40, %41, %42, %43, %44, %45, %46, %47, "
            "%48, %49, %50, %51, %52, %53, %54, %55, %56, %57, %58, %59, %60, %61, %62, %63, %64, %65, %66, %67, %68, %69, %70, %71, "
            "%72, %73, %74, %75, %76, %77, %78, %79, %80, %81, %82, %83, %84, %85, %86, %87, %88, %89, %90, %91, %92, %93, %94, %95}, "
            "{%96, %97, %98, %99}, %100, %101, %102, 1, 1, 1, 1;"
            : RW4(0), RW4(4), RW4(8), RW4(12), RW4(16), RW4(20), RW4(24), RW4(28), RW4(32), RW4(36), RW4(40), RW4(44),
              RW4(48), RW4(52), RW4(56), RW4(60), RW4(64), RW4(68), RW4(72), RW4(76), RW4(80), RW4(84), RW4(88), RW4(92)
            : "r"(a0), "r"(a1), "r"(a2), "r"(a3), "l"(descb), "r"(meta), "n"(SEL));
    }
}

#define TR(slot)
#define TRE(slot)
#define TRT(slot)
#define TRF(slot)
#define TRW(slot)
#define TRG(slot)
#define TRDUMP()

__device__ __forceinline__ void wg_fence() { asm volatile("wgmma.fence.sync.aligned;" ::: "memory"); }
__device__ __forceinline__ void wg_commit() { asm volatile("wgmma.commit_group.sync.aligned;" ::: "memory"); }
template <int N>
__device__ __forceinline__ void wg_wait() { asm volatile("wgmma.wait_group.sync.aligned %0;" ::"n"(N) : "memory"); }

template <int N>
__device__ __forceinline__ void pin(float (&d)[N]) {
#pragma unroll
    for (int i = 0; i < N; i++) asm volatile("" : "+f"(d[i])::"memory");
}
template <int N>
__device__ __forceinline__ void pin(uint32_t (&d)[N]) {
#pragma unroll
    for (int i = 0; i < N; i++) asm volatile("" : "+r"(d[i])::"memory");
}

constexpr uint64_t kDescRing = ((uint64_t)((1u << 30) | (1024u >> 4)) << 32) | (1u << 16) | (s_ring >> 4);
constexpr uint32_t kToV = ((kRingChunk >> 4) - 1) << 20;
__device__ __forceinline__ uint64_t desc_at(uint64_t base, uint32_t byte_off) {
    uint64_t d;
    asm volatile("add.s64 %0, %1, %2;" : "=l"(d) : "l"(base), "l"((uint64_t)(byte_off >> 4)));
    return d;
}

__device__ __forceinline__ void mbar_init(uint32_t bar, uint32_t count) {
    asm volatile("mbarrier.init.shared::cta.b64 [%0], %1;" ::"r"(bar), "r"(count) : "memory");
}
__device__ __forceinline__ void mbar_expect_tx(uint32_t bar, uint32_t bytes) {
    asm volatile("mbarrier.arrive.expect_tx.shared::cta.b64 _, [%0], %1;" ::"r"(bar), "r"(bytes) : "memory");
}
__device__ __forceinline__ void expect_tx_only(uint32_t bar, uint32_t bytes) {
    asm volatile("mbarrier.expect_tx.relaxed.cta.shared::cta.b64 [%0], %1;" ::"r"(bar), "r"(bytes) : "memory");
}
__device__ __forceinline__ void mbar_arrive(uint32_t bar) {
    asm volatile("mbarrier.arrive.shared::cta.b64 _, [%0];" ::"r"(bar) : "memory");
}
__device__ __forceinline__ void mbar_wait(uint32_t bar, uint32_t parity) {
    asm volatile(
        "{\n.reg .pred p;\n"
        "W: mbarrier.try_wait.parity.shared::cta.b64 p, [%0], %1;\n"
        "@!p bra W;\n}\n"
        ::"r"(bar), "r"(parity) : "memory");
}
__device__ __forceinline__ uint32_t clock_now() {
    uint32_t c;
    asm volatile("mov.u32 %0, %%clock;" : "=r"(c)::"memory");
    return c;
}
__device__ __forceinline__ void wait_until(uint32_t t0, int t) {
    if (t == 0) return;
    while ((int)(clock_now() - t0) < t) {}
}
__device__ __forceinline__ bool elect() {
    uint32_t ok;
    asm volatile("{\n.reg .pred p;\nelect.sync _|p, 0xffffffff;\nselp.u32 %0, 1, 0, p;\n}\n" : "=r"(ok));
    return ok != 0;
}
__device__ __forceinline__ void turn_wait(int wg) { asm volatile("bar.sync %0, 256;" ::"r"(1 + wg) : "memory"); }
__device__ __forceinline__ void turn_pass(int wg) { asm volatile("bar.arrive %0, 256;" ::"r"(2 - wg) : "memory"); }

__device__ __forceinline__ void tma_box(uint32_t dst, const CUtensorMap* map, uint32_t bar, int c0, int c2, int c3, int c4) {
    asm volatile(
        "cp.async.bulk.tensor.5d.shared::cluster.global.mbarrier::complete_tx::bytes [%0], [%1, {%3, %4, %5, %6, %7}], [%2];"
        ::"r"(dst), "l"(map), "r"(bar), "r"(c0), "r"(0), "r"(c2), "r"(c3), "r"(c4)
        : "memory");
}
__device__ __forceinline__ void tma_3d(uint32_t dst, const CUtensorMap* map, uint32_t bar, int c1, int c2) {
    asm volatile("cp.async.bulk.tensor.3d.shared::cluster.global.mbarrier::complete_tx::bytes [%0], [%1, {%3, %4, %5}], [%2];"
                 ::"r"(dst), "l"(map), "r"(bar), "r"(0), "r"(c1), "r"(c2)
                 : "memory");
}
__device__ __forceinline__ void prefetch_map(const CUtensorMap* map) {
    asm volatile("prefetch.tensormap [%0];" ::"l"(map) : "memory");
}
__device__ __forceinline__ uint4 ldg(const void* p) {
    uint4 v;
    asm volatile("ld.global.v4.u32 {%0, %1, %2, %3}, [%4];" : "=r"(v.x), "=r"(v.y), "=r"(v.z), "=r"(v.w) : "l"(p) : "memory");
    return v;
}
__device__ __forceinline__ uint32_t pack_bf16(float lo, float hi) {
    uint32_t r;
    asm("cvt.rn.bf16x2.f32 %0, %1, %2;" : "=r"(r) : "f"(hi), "f"(lo));
    return r;
}
__device__ __forceinline__ float ex2(float x) {
    float y;
    asm("ex2.approx.ftz.f32 %0, %1;" : "=f"(y) : "f"(x));
    return y;
}
__device__ __forceinline__ float rcp(float x) {
    float y;
    asm("rcp.approx.ftz.f32 %0, %1;" : "=f"(y) : "f"(x));
    return y;
}
__device__ __forceinline__ void mma16816(float (&d)[4], uint32_t a0, uint32_t a1, uint32_t a2, uint32_t a3, uint32_t b0, uint32_t b1) {
    asm volatile("mma.sync.aligned.m16n8k16.row.col.f32.bf16.bf16.f32 {%0, %1, %2, %3}, {%4, %5, %6, %7}, {%8, %9}, {%0, %1, %2, %3};"
                 : "+f"(d[0]), "+f"(d[1]), "+f"(d[2]), "+f"(d[3])
                 : "r"(a0), "r"(a1), "r"(a2), "r"(a3), "r"(b0), "r"(b1));
}
__device__ __forceinline__ uint4 lds128(uint32_t addr) {
    uint4 v;
    asm volatile("ld.volatile.shared.v4.u32 {%0, %1, %2, %3}, [%4];" : "=r"(v.x), "=r"(v.y), "=r"(v.z), "=r"(v.w) : "r"(addr) : "memory");
    return v;
}
__device__ __forceinline__ uint32_t lds_volatile(uint32_t addr) {
    uint32_t v;
    asm volatile("ld.volatile.shared.u32 %0, [%1];" : "=r"(v) : "r"(addr) : "memory");
    return v;
}

__device__ __forceinline__ int window_start(int n) { return min(max(n, 0), 105); }
__device__ __forceinline__ int origin_u(int u) { return min(max(u, 0), 98); }

struct Work {
    int u, v;
    int step;
    uint32_t su, sv;
    uint32_t base;
    bool corner;
    int ntiles;
    __device__ __forceinline__ void pixel_offsets(int qu, int qv, int j, uint32_t& o0, uint32_t& o1) const {
        const uint32_t b = (qu + window_start(qu)) * su + j * 16 + base;
        o0 = b + (qv + window_start(qv)) * sv;
        o1 = b + (qv + 1 + window_start(qv + 1)) * sv;
    }
};

__device__ __forceinline__ Work decode_work(int c) {
    Work w;
    const bool transposed = (c >> 4) == 7;
    const int px = 6 * (c & 1), py = 3 * (c & 2);
    w.corner = c >= 128;
    w.step = 8 - 4 * (c & 4);
    w.u = (c < 112 ? c & ~7 : 96 + (c & 8)) + (transposed ? py : px) - 6;
    w.v = (w.corner ? 96 : 48 - 2 * (c & 4)) + (transposed ? px : py) - 6;
    w.su = transposed ? kHW * kPixBytes : kPixBytes;
    w.sv = transposed ? kPixBytes : kHW * kPixBytes;
    w.base = px * (kPixBytes / 6) + py * (kHW * kPixBytes / 6) + 6 * (kHW + 1) * kPixBytes;
    w.ntiles = w.corner ? 4 : 6;
    return w;
}

struct RawX { uint4 a[6], b[6]; };
__device__ __forceinline__ void load_raw(RawX& r, const uint8_t* base, uint32_t o0, uint32_t o1) {
    __syncwarp();
#pragma unroll
    for (int c = 0; c < 6; c++) { r.a[c] = ldg(base + o0 + c * 64); r.b[c] = ldg(base + o1 + c * 64); }
    __syncwarp();
}
__device__ __forceinline__ void raw_to_frags(const RawX& r, uint32_t zero, uint32_t (&f)[48]) {
#pragma unroll
    for (int c = 0; c < 6; c++) {
        asm volatile("{\n.reg .b32 t, u;\nadd.u32 t, %4, %8;\nadd.u32 u, %5, %8;\nxor.b32 %0, %6, %8;\nxor.b32 %1, %7, %8;\n"
                     "xor.b32 %2, t, %8;\nxor.b32 %3, u, %8;\n}\n"
                     : "=&r"(f[8 * c + 1]), "=&r"(f[8 * c + 3]), "=&r"(f[8 * c + 4]), "=&r"(f[8 * c + 6])
                     : "r"(r.a[c].y), "r"(r.a[c].w), "r"(r.b[c].x), "r"(r.b[c].z), "r"(zero));
        f[8 * c + 0] = r.a[c].x; f[8 * c + 2] = r.a[c].z; f[8 * c + 5] = r.b[c].y; f[8 * c + 7] = r.b[c].w;
    }
}
__device__ __forceinline__ void acc_to_frags(const float (&d)[96], uint32_t (&f)[48]) {
#pragma unroll
    for (int i = 0; i < 48; i++) f[i] = pack_bf16(d[2 * i], d[2 * i + 1]);
}

template <class F>
__device__ __forceinline__ void proj_gemm(float (&d)[96], const uint32_t (&a)[48], uint64_t dsc, uint32_t img, F after) {
#pragma unroll
    for (int s = 0; s < 12; s++) {
        if (s == 0) wgmma_n192<true>(d, a[4 * s], a[4 * s + 1], a[4 * s + 2], a[4 * s + 3], desc_at(dsc, img - s_ring + (s >> 2) * kWChunk + (s & 3) * 32));
        else wgmma_n192<false>(d, a[4 * s], a[4 * s + 1], a[4 * s + 2], a[4 * s + 3], desc_at(dsc, img - s_ring + (s >> 2) * kWChunk + (s & 3) * 32));
        if (s == 11) wg_commit();
        after(s);
    }
}
__device__ __forceinline__ void pack_out(const float (&acc)[96], uint32_t (&po)[48]) {
#pragma unroll
    for (int g = 0; g < 6; g++)
#pragma unroll
        for (int q = 0; q < 4; q++) {
            po[8 * g + q] = pack_bf16(acc[16 * g + 4 * q], acc[16 * g + 4 * q + 1]);
            po[8 * g + 4 + q] = pack_bf16(acc[16 * g + 4 * q + 2], acc[16 * g + 4 * q + 3]);
        }
}
template <bool PINNED = true>
__device__ __forceinline__ void store_one(bool on, uint8_t* p0, uint8_t* p1, const uint32_t (&po)[48], int n) {
    if (PINNED) __syncwarp();
    asm volatile("{\n.reg .pred p;\nsetp.ne.u32 p, %5, 0;\n@p st.global.v4.u32 [%0], {%1, %2, %3, %4};\n}\n"
                 ::"l"(((n & 1) ? p1 : p0) + (n >> 1) * 64), "r"(po[4 * n]), "r"(po[4 * n + 1]), "r"(po[4 * n + 2]), "r"(po[4 * n + 3]), "r"((uint32_t)on) : "memory");
}

template <int N>
__device__ __forceinline__ float tree_max(const float (&v)[N]) {
    float t[N];
#pragma unroll
    for (int i = 0; i < N; i++) t[i] = v[i];
#pragma unroll
    for (int w = 1; w < N; w *= 2)
#pragma unroll
        for (int i = 0; i + w < N; i += 2 * w) t[i] = fmaxf(t[i], t[i + w]);
    return t[0];
}
template <int N>
__device__ __forceinline__ float tree_sum(const float (&v)[N]) {
    float t[N];
#pragma unroll
    for (int i = 0; i < N; i++) t[i] = v[i];
#pragma unroll
    for (int w = 1; w < N; w *= 2)
#pragma unroll
        for (int i = 0; i + w < N; i += 2 * w) t[i] += t[i + w];
    return t[0];
}

template <int B>
__device__ __forceinline__ void pick(uint32_t h, uint32_t ok, const float* s, float& v0, float& v1) {
    asm("{\n.reg .pred p, q0, q1;\n.reg .b32 t;\nand.b32 t, %6, %7;\nsetp.ne.u32 p, t, 0;\n"
        "and.b32 t, %8, %9;\nsetp.ne.u32 q0, t, 0;\nand.b32 t, %8, %10;\nsetp.ne.u32 q1, t, 0;\n"
        "@q0 selp.f32 %0, %3, %2, p;\n@q1 selp.f32 %1, %5, %4, p;\n}\n"
        : "+f"(v0), "+f"(v1)
        : "f"(s[0]), "f"(s[1]), "f"(s[2]), "f"(s[3]), "r"(h), "n"(1 << ((4 * B) % 7)), "r"(ok), "n"(1 << (2 * B)), "n"(2 << (2 * B)));
}
template <int B, class F>
__device__ __forceinline__ void for_blocks(F f) {
    if constexpr (B > 0) { for_blocks<B - 1>(f); f(std::integral_constant<int, B - 1>{}); }
}
__device__ __forceinline__ void gather_outer(const float (&s)[44], uint32_t h, uint32_t ok, float (&v0)[14], float (&v1)[14]) {
    for_blocks<11>([&](auto B) {
        constexpr int b = B.value < 8 ? (B.value >> 1) + 7 * (B.value & 1) : B.value - 4;
        pick<b>(h, ok, &s[4 * b], v0[b], v1[b]);
    });
}
__device__ __forceinline__ void gather_mid(const float (&sE)[16], uint32_t h, uint32_t ok, float (&v0)[14], float (&v1)[14]) {
    for_blocks<4>([&](auto B) { pick<10 + B.value>(h, ok, &sE[4 * B.value], v0[10 + B.value], v1[10 + B.value]); });
}
__device__ __forceinline__ float quad_max(float m) {
    m = fmaxf(m, __shfl_xor_sync(0xffffffffu, m, 1));
    return fmaxf(m, __shfl_xor_sync(0xffffffffu, m, 2));
}
__device__ __forceinline__ float quad_sum(float s) {
    s += __shfl_xor_sync(0xffffffffu, s, 1);
    return s + __shfl_xor_sync(0xffffffffu, s, 2);
}
template <int B0, int B1>
__device__ __forceinline__ void exp_route(float (&v0)[14], float (&v1)[14], float m0, float m1, const uint4& r, bool even, uint32_t (&y)[14]) {
#pragma unroll
    for (int b = B0; b < B1; b++) { v0[b] = ex2(v0[b] - m0); v1[b] = ex2(v1[b] - m1); }
#pragma unroll
    for (int b = B0; b < B1; b += 2) {
        const uint32_t x0 = pack_bf16(v0[b], v1[b]), x1 = pack_bf16(v0[b + 1], v1[b + 1]);
        const uint32_t u = __shfl_sync(0xffffffffu, even ? x0 : x1, r.x);
        const uint32_t w = __shfl_sync(0xffffffffu, even ? x1 : x0, r.y);
        y[b] = __byte_perm(u, w, r.z); y[b + 1] = __byte_perm(u, w, r.w);
    }
}
template <int BIT0, int N0, int N1>
__device__ __forceinline__ void unfold(const uint32_t (&y)[14], uint32_t fold, uint32_t (&p)[12]) {
    for_blocks<N1 - N0>([&](auto N) {
        constexpr int n = N0 + N.value;
        asm("{\n.reg .pred p;\n.reg .b32 t;\nand.b32 t, %4, %5;\nsetp.ne.u32 p, t, 0;\nselp.b32 %0, %2, 0, p;\nselp.b32 %1, %3, 0, p;\n}\n"
            : "=r"(p[2 * n]), "=r"(p[2 * n + 1]) : "r"(y[2 * n]), "r"(y[2 * n + 1]), "r"(fold), "n"(1 << (BIT0 + n)));
    });
}
__device__ __forceinline__ void keep(bool never, uint32_t a, uint32_t b, uint32_t c, uint32_t d) {
    asm volatile("{\n.reg .pred p;\nsetp.ne.u32 p, %4, 0;\n@p st.volatile.shared.v4.u32 [%5], {%0, %1, %2, %3};\n}\n"
                 ::"r"(a), "r"(b), "r"(c), "r"(d), "r"((uint32_t)never), "r"(s_trace) : "memory");
}

__device__ __forceinline__ uint32_t wimg_offset(uint32_t row, uint32_t s, uint32_t j) {
    return (s >> 2) * kWChunk + row * 128 + (((2 * (s & 3) + (j >> 1)) ^ (row & 7)) << 4) + (j & 1) * 8;
}

__device__ __forceinline__ void ldsm4(uint32_t (&r)[4], uint32_t addr) {
    asm volatile("ldmatrix.sync.aligned.m8n8.x4.shared.b16 {%0, %1, %2, %3}, [%4];" : "=r"(r[0]), "=r"(r[1]), "=r"(r[2]), "=r"(r[3]) : "r"(addr) : "memory");
}
__device__ __forceinline__ void ldsm4_t(uint32_t (&r)[4], uint32_t addr) {
    asm volatile("ldmatrix.sync.aligned.m8n8.x4.trans.shared.b16 {%0, %1, %2, %3}, [%4];" : "=r"(r[0]), "=r"(r[1]), "=r"(r[2]), "=r"(r[3]) : "r"(addr) : "memory");
}
__device__ __forceinline__ void m_partial(const uint8_t* wqkv, uint32_t mt, uint32_t s, uint32_t q, uint32_t lane, uint32_t zero) {
    const uint32_t r8 = lane >> 2, col = q * 128 + (lane & 3) * 16;
    const uint8_t* pa = wqkv + (16 * mt + r8) * 1152 + col;
    const uint8_t* pb = wqkv + (16 * s + 8 * (r8 & 2) + (r8 & 5)) * 1152 + col;
    uint4 A[2][2], B[4][2];
#pragma unroll
    for (int c = 0; c < 2; c++) {
#pragma unroll
        for (int h = 0; h < 2; h++) A[h][c] = ldg(pa + 384 + h * 8 * 1152 + c * 64);
#pragma unroll
        for (int n = 0; n < 4; n++) B[n][c] = ldg(pb + ((n & 1) * 8 + (n & 2)) * 1152 + c * 64);
    }
#pragma unroll
    for (int i = 0; i < 4; i++) { uint4& a = A[i >> 1][i & 1]; a.x ^= zero; a.y ^= zero; a.z ^= zero; a.w ^= zero; }
#pragma unroll
    for (int n = 0; n < 4; n++) {
        float d[4] = {0.f, 0.f, 0.f, 0.f};
#pragma unroll
        for (int c = 0; c < 2; c++) {
            mma16816(d, A[0][c].x, A[1][c].x, A[0][c].y, A[1][c].y, B[n][c].x, B[n][c].y);
            mma16816(d, A[0][c].z, A[1][c].z, A[0][c].w, A[1][c].w, B[n][c].z, B[n][c].w);
        }
        asm volatile("st.shared.v4.f32 [%0], {%1, %2, %3, %4};" ::"r"(s_wv + q * 2048 + n * 512 + lane * 16), "f"(d[0]), "f"(d[1]), "f"(d[2]), "f"(d[3]) : "memory");
    }
}
__device__ __forceinline__ void m_reduce(uint32_t e, uint32_t lane, float (&d)[2][4]) {
#pragma unroll
    for (int n = 0; n < 2; n++) {
        float t[3][4];
#pragma unroll
        for (int q = 0; q < 3; q++)
            asm volatile("ld.shared.v4.f32 {%0, %1, %2, %3}, [%4];" : "=f"(t[q][0]), "=f"(t[q][1]), "=f"(t[q][2]), "=f"(t[q][3]) : "r"(s_wv + q * 2048 + e * 1024 + n * 512 + lane * 16) : "memory");
#pragma unroll
        for (int i = 0; i < 4; i++) d[n][i] = (t[0][i] + t[1][i] + t[2][i]) * kScaleLog2e;
    }
}
__device__ __forceinline__ void w_piece(uint32_t q, uint32_t lane, float (&d)[2][4]) {
    const uint32_t rr = lane & 7, mi = lane >> 3, kr = 4 * (rr >> 1) + (mi & 2) + (rr & 1);
    const uint32_t pa = s_wv + q * 6144 + (4 * (mi & 2) + rr) * 32 + (((mi ^ (rr >> 2)) & 1) << 4);
    const uint32_t pb = s_wv + 3 * 6144 + kr * 32 + (((mi ^ (kr >> 2)) & 1) << 4);
#pragma unroll
    for (int i = 0; i < 8; i++) (&d[0][0])[i] = 0.f;
#pragma unroll kWUnroll
    for (int k = 0; k < 12; k++) {
        uint32_t aq[4], bq[4];
        ldsm4_t(aq, pa + k * 512);
        ldsm4(bq, pb + k * 512);
        mma16816(d[0], aq[0], aq[1], aq[2], aq[3], bq[0], bq[1]);
        mma16816(d[1], aq[0], aq[1], aq[2], aq[3], bq[2], bq[3]);
    }
}
__device__ __forceinline__ uint32_t piece_offset(uint32_t which, uint32_t s, uint32_t mt, uint32_t lane) {
    const uint32_t r8 = lane >> 2;
    return which * kWBytes + wimg_offset(which ? 32 * (mt >> 1) + 8 * (r8 >> 1) + 4 * (mt & 1) + (r8 & 1) : 16 * mt + r8, s, lane & 3);
}
__device__ __forceinline__ void piece_store(Scratch* g, uint32_t par, uint32_t off0, uint32_t which, const float (&d)[2][4]) {
#pragma unroll
    for (int hf = 0; hf < 2; hf++) {
        const uint32_t off = off0 ^ (hf ? which ? 288 : 1024 : 0);
        const uint32_t a = pack_bf16(d[0][2 * hf], d[0][2 * hf + 1]), b = pack_bf16(d[1][2 * hf], d[1][2 * hf + 1]);
        asm volatile("st.relaxed.gpu.global.v2.u32 [%0], {%1, %2};" ::"l"(g->img[0][0] + (par + off)), "r"(a ? a : 0x8000u), "r"(b) : "memory");
    }
}
__device__ __forceinline__ void piece_clear(Scratch* g, uint32_t par, uint32_t off0, uint32_t which) {
#pragma unroll
    for (int hf = 0; hf < 2; hf++)
        asm volatile("st.relaxed.gpu.global.v2.u32 [%0], {%1, %1};" ::"l"(g->img[0][0] + (par + (off0 ^ (hf ? which ? 288 : 1024 : 0)))), "r"(0) : "memory");
}

__device__ __forceinline__ uint32_t ld_relaxed(const uint32_t* p) {
    uint32_t v;
    asm volatile("ld.relaxed.gpu.global.u32 %0, [%1];" : "=r"(v) : "l"(p) : "memory");
    return v;
}
__device__ __forceinline__ void count_up(uint32_t* p) {
    asm volatile("red.relaxed.gpu.global.add.u32 [%0], %1;" ::"l"(p), "r"(1) : "memory");
}
__device__ __forceinline__ void bulk_g2s(uint32_t dst, const void* src, uint32_t bytes, uint32_t bar) {
    asm volatile("cp.async.bulk.shared::cluster.global.mbarrier::complete_tx::bytes [%0], [%1], %2, [%3];"
                 ::"r"(dst), "l"(src), "r"(bytes), "r"(bar)
                 : "memory");
}

__global__ void __launch_bounds__(kThreads, 1)
nat_fused_kernel(const uint8_t* __restrict__ x, const uint8_t* __restrict__ wqkv, uint8_t* __restrict__ out, Scratch* g,
                 const Tables* tables, uint64_t dsc, const __grid_constant__ Maps maps) {
    const int tid = threadIdx.x, lane = tid & 31;
    const int warp = __shfl_sync(0xffffffffu, tid >> 5, 0);
    const int wg = warp >> 2, wq = warp & 3, r8 = lane >> 2, j = lane & 3;
    const int cta = blockIdx.x;
    const Work w = decode_work(cta);
    const uint32_t which = cta >= 72, job = which ? cta - 72 : 2 * cta, jhi = job / 12, jlo = job % 12;
    if (wg == 1 && wq < 3) {
#pragma unroll
        for (int r = 0; r < 3; r++)
            asm volatile("st.shared.v4.u32 [%0], {%1, %1, %1, %1};" ::"r"(s_ring + wq * kRingChunk + (r == 0 ? 84 : r == 1 ? 88 : 204) * 128 + lane * 16), "r"(0) : "memory");
        asm volatile("fence.proxy.async.shared::cta;" ::: "memory");
    }
    if (x == nullptr) return;
    const uint32_t t_start = clock_now();
    if (wg == 2) {
        if (wq < 3 && !which) m_partial(wqkv, jhi, jlo, wq, lane, (uint32_t)dsc & 1);
        asm volatile("setmaxnreg.dec.sync.aligned.u32 40;");
        if (wq < 3) {
            const uint32_t off = piece_offset(which, which ? jlo : jlo + wq, which ? 3 * jhi + wq : jhi, lane);
            asm volatile("bar.sync %0, 128;" ::"r"(5 + (off >> 31)) : "memory");
            const uint32_t par = lds_volatile(s_par);
            if (cta < 120 && wq < 2 + which) {
                float d[2][4];
                if (wq == 0) TRW(which ? 1 : 18);
                if (which) {
                    mbar_wait(bar_wop, 0);
                    if (wq == 0) TRW(2);
                    w_piece(wq, lane, d);
                } else {
                    m_reduce(wq, lane, d);
                }
                piece_store(g, par, off, which, d);
                __syncwarp();
                if (!which && lane == 0) count_up(&g->cnt[0]);
                __syncwarp();
                piece_clear(g, 2 * kWBytes - par, off, which);
                if (wq == 0) TRW(which ? 3 : 0);
            }
            asm volatile("bar.arrive 6, 128;" ::: "memory");
            uint32_t phase = 0;
#pragma unroll 1
            for (uint32_t c = 0; c < 6; c++) {
                const uint32_t part = c * kWChunk + wq * (kWChunk / 3), img = 8 * min(c, 3u);
                mbar_wait(bar_img + 8 * c, 0);
                if (wq == 0) TRW(10 + c);
#pragma unroll 1
                while (true) {
                    uint32_t lo = ~0u;
#pragma unroll
                    for (int q = 0; q < 8; q++) lo = min(lo, lds_volatile(s_m + part + lane * 32 + (lane & 12) * 2 + q * 1024));
                    if (__all_sync(0xffffffffu, lo) || phase > 65535) break;
                    if (elect()) {
                        mbar_expect_tx(bar_redo + 8 * wq, kWChunk / 3);
                        bulk_g2s(s_m + part, g->img[0][0] + par + part, kWChunk / 3, bar_redo + 8 * wq);
                    }
                    mbar_wait(bar_redo + 8 * wq, phase++ & 1);
                }
                if (c != 3 && c != 4 && lane == 0) mbar_arrive(bar_ok + img);
            }
        } else {
            uint32_t launch = ld_relaxed(&g->cnt[1]);
            const CUtensorMap* map = &maps.m[w.sv == kPixBytes ? 2 : 0];
            if (elect()) {
#pragma unroll
                for (int i = 0; i < 20; i++) mbar_init(s_bar + 8 * i, i < 13 ? 1 : i < 18 ? 3 : 4);
                asm volatile("fence.mbarrier_init.release.cluster;" ::: "memory");
                prefetch_map(map + 1);
                expect_tx_only(bar_a, sizeof(Table));
                bulk_g2s(s_tab, &tables->t[w.step < 0], sizeof(Table), bar_a);
            }
            if (which && cta < 120 && elect()) {
                mbar_expect_tx(bar_wop, 4 * 6144);
                tma_3d(s_wv, &maps.wo, bar_wop, 0, 3 * jhi);
                tma_3d(s_wv + 3 * 6144, &maps.wv, bar_wop, 16 * jlo, 24);
            }
            int u = w.u, v = w.v;
            uint32_t wait_bar = bar_use, wait_par = 1, slot = 0;
#pragma unroll 1
            for (int step = 0; step < 7 - w.corner; step++) {
                const bool first = step == 0 || (w.corner && step == 4);
                const int row = v + 4 + (first ? -w.step : w.step) / 2, ou = origin_u(u);
                uint32_t dst = s_ring + (first ? 0 : slot), mid = s_ring + kOffMid + 512, bar = first ? bar_a : bar_b;
                mbar_wait(wait_bar, wait_par);
                TRW(24 + step);
#pragma unroll 1
                for (int ch = (cta & 1) * kC; mid < s_m; ch += 64, dst += kRingChunk, mid += kRingChunk) {
                    if (elect()) {
                        mbar_expect_tx(bar, first ? kSlotBytes : kSlotBytes + kMidBytes);
                        tma_box(dst, map, bar, ch, ou, (cta >> 1) & 1, row);
                    }
                    if (!first) {
                        if (elect()) tma_box(mid, map + 1, bar, ch, ou, (cta >> 1) & 1, v + 6);
                        bar += 8;
                    }
                }
                if (step == 0) {
                    launch /= kGrid;
                    asm volatile("st.shared.u32 [%0], %2;\nst.shared.v2.u32 [%0 + 16], {%1, %2};" ::"r"(s_cnt), "r"((launch & 1) * 2 * kWBytes), "r"(0) : "memory");
                    if (lane == 0) count_up(&g->cnt[1]);
                    asm volatile("bar.arrive 5, 128;\nbar.arrive 3, 160;\nbar.arrive 4, 160;" ::: "memory");
#pragma unroll 1
                    for (int t = TN(6, 2800); t < (1 << 24);) {
                        if (__shfl_sync(0xffffffffu, lds_volatile(s_cnt), 0) >= (launch + 1) * kPieces) break;
                        if ((int)(clock_now() - t_start) < t) continue;
                        t += TN(7, 120);
                        if (elect()) {
                            expect_tx_only(bar_use + 8, 16);
                            bulk_g2s(s_cnt, g->cnt, 16, bar_use + 8);
                        }
                    }
                }
                if (step == 1) {
                    asm volatile("bar.sync 6, 128;" ::: "memory");
                    wait_until(t_start, TN(5, 6000));
                }
                if (step < 2) {
                    TRW(5 + 4 * step);
#pragma unroll 1
                    for (int c = 3 * step; c < 3 + 3 * step; c++)
                        if (elect()) {
                            mbar_expect_tx(bar_img + 8 * c, kWChunk);
                            bulk_g2s(s_m + c * kWChunk, g->img[launch & 1][0] + c * kWChunk, kWChunk, bar_img + 8 * c);
                        }
                }
                const bool again = w.corner && step == 3;
                wait_bar = step == 0 ? bar_img + 8 * TN(1, 1) : again ? bar_use + 8 : bar_use;
                if (!again) {
                    wait_par = slot ? 0 : step != 0;
                    slot ^= kSlotStride;
                    if (w.corner && step == 2) { u += 8; v -= 8; } else if (step) v += w.step;
                }
            }
        }
        TRDUMP();
        return;
    }
    const int order = w.step < 0 ? warp ^ 3 : warp;
    int tu = w.u, tv = w.v + w.step * wg;
    const int du2 = w.corner ? 8 : 0, dv2 = w.corner ? 0 : 2 * w.step;
    uint32_t o0, o1;
    wait_until(t_start, START_TIME);
    asm volatile("setmaxnreg.inc.sync.aligned.u32 232;");
    w.pixel_offsets(tu + r8, tv + 2 * wq, j, o0, o1);
    uint32_t fa[48];
    {
        RawX raw;
        load_raw(raw, x, o0, o1);
        asm volatile("bar.sync %0, 160;" ::"r"(3 + wg) : "memory");
        raw_to_frags(raw, 0, fa);
        pin(fa);
    }
    mbar_wait(bar_ok, 0);
    const uint64_t dA = dsc + wg * (kSlotStride >> 4), dB = dsc + (wg ^ 1) * (kSlotStride >> 4);

    float acc[96];
    uint32_t po[48];
    uint32_t c0, c1;
    asm volatile("" : "=r"(c0), "=r"(c1));
#pragma unroll
    for (int q = 0; q < 48; q++) asm volatile("" : "=r"(po[q]));
#pragma unroll 1
    for (int i = wg; i < w.ntiles; i += 2) {
        const bool first = i == 0, last = i == w.ntiles - 1;

        TRF(8 + 16 * k);
        wg_fence();
        if (!first) turn_wait(wg);
        proj_gemm(acc, fa, dsc, s_m, [&](int s) {
            if (s == 11 && !first) turn_pass(wg);
            const int n = __builtin_popcount(QSLOTS & ((1 << s) - 1));
            if (((QSLOTS >> s) & 1) && n < 12) store_one(i >= 2, out + c0, out + c1, po, n);
            if (s == 3 || s == 7) { mbar_wait(bar_ok + 2 * s + 2, 0); wg_fence(); }
        });
        __syncwarp();
        TRF(9 + 16 * k);
        uint8_t *p0 = out + c0, *p1 = out + c1;
        c0 = o0; c1 = o1;
        w.pixel_offsets(tu + du2 + r8, tv + dv2 + 2 * wq, j, o0, o1);
        if (i + 2 >= w.ntiles) o0 = o1 = 0;
        wg_wait<0>();
        pin(acc);
        TR(11 + 16 * k);
        TRT(80 + k);
#pragma unroll
        for (int n = __builtin_popcount(QSLOTS); n < 12 - __builtin_popcount(ASLOTS) - __builtin_popcount(BSLOTS); n++) store_one(i >= 2, p0, p1, po, n);
        acc_to_frags(acc, fa);
        pin(fa);

        float sA[44], sE[16], sB[44];
        RawX nxt;
        if (!first) turn_wait(wg);
        mbar_wait(bar_a, w.corner ? i >> 1 : 0);
        if (i == 0) TR(12);
        wg_fence();
#pragma unroll
        for (int s = 0; s < 12; s++) {
            if (s == 0) wgmma_n88<true>(sA, fa[4 * s], fa[4 * s + 1], fa[4 * s + 2], fa[4 * s + 3], desc_at(dA, (s >> 2) * kRingChunk + (s & 3) * 32));
            else wgmma_n88<false>(sA, fa[4 * s], fa[4 * s + 1], fa[4 * s + 2], fa[4 * s + 3], desc_at(dA, (s >> 2) * kRingChunk + (s & 3) * 32));
            if (s == 11) { wg_commit(); if (!first) turn_pass(wg); }
            if ((ASLOTS >> s) & 1) store_one(i >= 2, p0, p1, po, 12 - __builtin_popcount(BSLOTS) - __builtin_popcount(ASLOTS >> s));
        }
#pragma unroll
        for (int s = 12; s < 16; s++)
            if ((ASLOTS >> s) & 1) store_one(i >= 2, p0, p1, po, 12 - __builtin_popcount(BSLOTS) - __builtin_popcount(ASLOTS >> s));
        TRF(12 + 16 * k);
        const int vq = tv + 2 * wq;
        const uint4 tabu = lds128(s_tab + offsetof(Table, u) + (window_start(tu + r8) - origin_u(tu)) * 64 + j * 16);
        const uint4 tabv = lds128(s_tab + offsetof(Table, v) + (window_start(vq) + window_start(vq + 1) - 2 * tv) * 64 + j * 16);
        const uint4 route = lds128(s_tab + lane * 16);
        load_raw(nxt, x, o0, o1);
        float v0[14], v1[14];
#pragma unroll
        for (int b = 0; b < 14; b++) v0[b] = v1[b] = __int_as_float(0xff800000);
        wg_wait<0>();
        pin(sA);
        gather_outer(sA, tabu.x, tabv.x, v0, v1);
        pin(v0); pin(v1);
        if (!first) turn_wait(wg);
#pragma unroll
        for (int c = 0; c < 3; c++) {
            mbar_wait(bar_b + 8 * c, wg);
            if (i == 0 && c != 1) TR(13 + c);
            wg_fence();
#pragma unroll
            for (int s = 4 * c; s < 4 * c + 4; s++) {
                if (s == 0) wgmma_n88<true>(sB, fa[4 * s], fa[4 * s + 1], fa[4 * s + 2], fa[4 * s + 3], desc_at(dB, c * kRingChunk + (s & 3) * 32));
                else wgmma_n88<false>(sB, fa[4 * s], fa[4 * s + 1], fa[4 * s + 2], fa[4 * s + 3], desc_at(dB, c * kRingChunk + (s & 3) * 32));
                if ((BSLOTS >> s) & 1) store_one(i >= 2, p0, p1, po, 12 - __builtin_popcount(BSLOTS >> s));
            }
        }
        wg_commit();
#pragma unroll
        for (int s = 0; s < 12; s++)
            if (s == 0) wgmma_n32<true>(sE, fa[4 * s], fa[4 * s + 1], fa[4 * s + 2], fa[4 * s + 3], desc_at(dsc, kOffMid + (s >> 2) * kRingChunk + (s & 3) * 32));
            else wgmma_n32<false>(sE, fa[4 * s], fa[4 * s + 1], fa[4 * s + 2], fa[4 * s + 3], desc_at(dsc, kOffMid + (s >> 2) * kRingChunk + (s & 3) * 32));
        wg_commit();
        if (OSPLIT || !last) turn_pass(wg);
        TRF(13 + 16 * k);
        wg_wait<1>();
        pin(sB);
        gather_outer(sB, tabu.w, tabv.y, v0, v1);
        wg_wait<0>();
        pin(sE);
        TRF(14 + 16 * k);
        gather_mid(sE, tabu.w, tabv.z, v0, v1);
        const float m0 = quad_max(tree_max(v0)), m1 = quad_max(tree_max(v1));

        uint32_t y[14], pa[12], pb[12];
        exp_route<0, 14>(v0, v1, m0, m1, route, (j & 1) == 0, y);
        float s0 = tree_sum(v0), s1 = tree_sum(v1);
        asm volatile("" : "+f"(s0), "+f"(s1));
        unfold<0, 0, 6>(y, tabv.w, pa);
        if (OSPLIT || !last) turn_wait(wg + (y[0] >> 31));
        TRF(15 + 16 * k + (y[13] >> 31));
        wg_fence();
        wgmma_sp_n192_tb<true, 0>(acc, pa[0], pa[1], pa[2], pa[3], desc_at(dA, kToV), tabu.y);
        wgmma_sp_n192_tb<false, 1>(acc, pa[4], pa[5], pa[6], pa[7], desc_at(dA, kToV + 4096), tabu.y);
        wgmma_sp_n192_tb<false, 0>(acc, pa[8], pa[9], pa[10], pa[11], desc_at(dA, kToV + 8192), tabu.z);
        wgmma_sp_n192_tb<false, 1>(acc, y[10], y[11], y[12], y[13], desc_at(dsc, kToV + kOffMid), tabu.z);
        wg_commit();
        unfold<8, 0, 6>(y, tabv.w, pb);
        wg_fence();
        wgmma_sp_n192_tb<false, 0>(acc, pb[0], pb[1], pb[2], pb[3], desc_at(dB, kToV), tabu.y);
        wgmma_sp_n192_tb<false, 1>(acc, pb[4], pb[5], pb[6], pb[7], desc_at(dB, kToV + 4096), tabu.y);
        wgmma_sp_n192_tb<false, 0>(acc, pb[8], pb[9], pb[10], pb[11], desc_at(dB, kToV + 8192), tabu.z);
        wg_commit();
        if (!last) turn_pass(wg);
        TRF(16 + 16 * k);
        wg_wait<1>();
        if (lane == 0) mbar_arrive(bar_use);
        TRF(17 + 16 * k);
        mbar_wait(bar_ok + 24, 0);
        wg_wait<0>();
        if (lane == 0) mbar_arrive(bar_use + 8);
        pin(acc);
        TR(18 + 16 * k);

        acc_to_frags(acc, po);
        pin(po);
        if (!last) turn_wait(wg);
        wg_fence();
        proj_gemm(acc, po, dsc, s_wv, [&](int s) {
            if (s + 1 == OSPLIT && i + 2 == w.ntiles) { turn_pass(wg); turn_wait(wg); }
        });
        if (!last) turn_pass(wg);
        TRF(19 + 16 * k);
        const uint32_t zero = lds_volatile(s_late);
        const float inv0 = rcp(quad_sum(s0 + __uint_as_float(zero))), inv1 = rcp(quad_sum(s1 + __uint_as_float(zero)));
        raw_to_frags(nxt, zero, fa);
        pin(fa);
#pragma unroll
        for (int q = 0; q < 48; q += 4) keep(wqkv == nullptr, fa[q], fa[q + 1], fa[q + 2], fa[q + 3]);
        keep(wqkv == nullptr, __float_as_uint(inv0), __float_as_uint(inv1), zero, lane);
        TRF(20 + 16 * k);
        tu += du2; tv += dv2;
        wg_wait<0>();
        pin(acc);
        TR(21 + 16 * k);
#pragma unroll
        for (int q = 0; q < 96; q++) acc[q] *= q & 2 ? inv1 : inv0;
        pack_out(acc, po);
#pragma unroll
        for (int n = 0; n < INLOOP; n++) store_one<false>(last, out + c0, out + c1, po, n);
        pin(po);
    }
#pragma unroll
    for (int n = 0; n < 12; n++) {
        asm volatile("{\n.reg .pred p;\nsetp.eq.u32 p, %0, 0;\n@p nanosleep.u32 %1;\n}\n" ::"r"(wg), "n"(NAP) : "memory");
        store_one<false>(n >= INLOOP || wg == 0, out + c0, out + c1, po, n);
    }
    TRE(7);
    TRG(1);
    TRDUMP();
}

typedef CUresult (*EncodeTiledFn)(CUtensorMap*, CUtensorMapDataType, cuuint32_t, void*, const cuuint64_t*, const cuuint64_t*,
                                  const cuuint32_t*, const cuuint32_t*, CUtensorMapInterleave, CUtensorMapSwizzle,
                                  CUtensorMapL2promotion, CUtensorMapFloatOOBfill);

bool make_maps(EncodeTiledFn fn, Maps* maps, void* x, void* wqkv, void* wo) {
    const cuuint64_t pix2 = 2 * kPixBytes, row = (cuuint64_t)kHW * kPixBytes;
    const cuuint32_t estr[5] = {1, 1, 1, 1, 1};
    bool ok = true;
    for (int tr = 0; tr < 2; tr++)
        for (int b = 0; b < 2; b++) {
            const cuuint64_t su = tr ? 2 * row : pix2, sv = tr ? pix2 : 2 * row;
            const cuuint64_t dims[5] = {2 * kC, 2, 105, 2, 112};
            const cuuint64_t strides[4] = {7 * su, su, row, sv};
            const cuuint32_t box[5] = {64, 2, 7, 1, b ? 2u : 6u};
            ok = ok && fn(&maps->m[2 * tr + b], CU_TENSOR_MAP_DATA_TYPE_BFLOAT16, 5, x, dims, strides, box, estr,
                          CU_TENSOR_MAP_INTERLEAVE_NONE, CU_TENSOR_MAP_SWIZZLE_128B, CU_TENSOR_MAP_L2_PROMOTION_L2_128B,
                          CU_TENSOR_MAP_FLOAT_OOB_FILL_NONE) == CUDA_SUCCESS;
        }
    for (int b = 0; b < 2; b++) {
        const cuuint64_t dims[3] = {16, kC, b ? 36u : 12u}, strides[2] = {(b ? 3u : 1u) * kPixBytes, 32};
        const cuuint32_t box[3] = {16, b ? 16u : 192u, b ? 12u : 3u};
        ok = ok && fn(b ? &maps->wv : &maps->wo, CU_TENSOR_MAP_DATA_TYPE_BFLOAT16, 3, b ? wqkv : wo, dims, strides, box, estr,
                      CU_TENSOR_MAP_INTERLEAVE_NONE, CU_TENSOR_MAP_SWIZZLE_32B, CU_TENSOR_MAP_L2_PROMOTION_L2_128B,
                      CU_TENSOR_MAP_FLOAT_OOB_FILL_NONE) == CUDA_SUCCESS;
    }
    return ok;
}

}

extern "C" void kernel_launch(void* const* d_in, const int* in_sizes, int n_in, void* d_out, int out_size) {
    static EncodeTiledFn encode = nullptr;
    static Scratch* scratch = nullptr;
    static Tables* tables = nullptr;
    if (!encode) {
        int dev = 0, reserved = 0;
        cudaFuncAttributes attr;
        cudaGetDevice(&dev);
        cudaDeviceGetAttribute(&reserved, cudaDevAttrReservedSharedMemoryPerBlock, dev);
        cudaFuncGetAttributes(&attr, nat_fused_kernel);
        if (reserved != (int)kSmemBase || attr.sharedSizeBytes != 0) return;
        cudaGetSymbolAddress((void**)&scratch, g_scratch);
        cudaGetSymbolAddress((void**)&tables, g_tables);
        void* fn = nullptr;
        cudaDriverEntryPointQueryResult st;
        cudaGetDriverEntryPoint("cuTensorMapEncodeTiled", &fn, cudaEnableDefault, &st);
        encode = (EncodeTiledFn)fn;
        cudaFuncSetAttribute(nat_fused_kernel, cudaFuncAttributeMaxDynamicSharedMemorySize, kSmemBytes);
    }
    Maps maps;
    if (!encode || !make_maps(encode, &maps, d_in[0], d_in[1], d_in[2])) return;
    nat_fused_kernel<<<kGrid, kThreads, kSmemBytes>>>((const uint8_t*)d_in[0], (const uint8_t*)d_in[1], (uint8_t*)d_out, scratch, tables, kDescRing, maps);
}
```

```cpp
#include <cuda_runtime.h>
#include <cuda_bf16.h>
#include <cuda.h>
#include <stdint.h>
#include <type_traits>
#include <stdlib.h>
#include <stddef.h>

#define KEEPFA 1
#define ASLOTS 0x3800
#define BSLOTS 0x6
#define QSLOTS 0x78a
#define OSPLIT 3
#define NAP 40
#define INLOOP 3
#define WUNROLL 2

namespace {

constexpr int kC          = 192;
constexpr int kHW         = 224;
constexpr int kPixBytes   = kC * 2;
constexpr int kSlotBytes  = 84 * 128;
constexpr int kMidBytes   = 28 * 128;
constexpr int kOffMid     = 88 * 128;
constexpr int kSlotStride = 120 * 128;
constexpr int kRingChunk  = 208 * 128;
constexpr int kWChunk     = 192 * 128;
constexpr int kWBytes     = 3 * kWChunk;
constexpr uint32_t kSmemBase = 1024;
constexpr uint32_t s_ring = kSmemBase, s_m = s_ring + 3 * kRingChunk, s_wv = s_m + kWBytes, s_bar = s_wv + kWBytes;
constexpr uint32_t bar_b = s_bar, bar_img = s_bar + 24, bar_redo = s_bar + 72, bar_wop = s_bar + 96, bar_a = s_bar + 104,
                   bar_ok = s_bar + 112, bar_use = s_bar + 144;
constexpr uint32_t s_par = s_bar + 160, s_late = s_bar + 164, s_tab = s_bar + 256, s_trace = s_tab + 2048;
constexpr int kSmemBytes  = s_trace + 2048 - kSmemBase;
constexpr int kThreads    = 384, kWUnroll = WUNROLL;
constexpr int kGrid       = 132;
constexpr int kTimeM = 2750, kTimeW = 5400;
constexpr float kScaleLog2e = 0.07216878364870322f * 1.4426950408889634f;

struct Maps {
    CUtensorMap m[4];
    CUtensorMap wo, wv;
};
#define TN(i, dflt) (dflt)
#define START_TIME (wg ? 1100 + 500 * order : 250 + 700 * order)

struct Scratch {
    uint8_t img[2][2][kWBytes];
    uint32_t launches;
};
__device__ __align__(1024) Scratch g_scratch;

struct Table {
    uint32_t route[32][4];
    uint32_t u[8][4][4];
    uint32_t v[16][4][4];
};
struct Tables { Table t[2]; };
constexpr Tables make_tables() {
    Tables r = {};
    for (int rev = 0; rev < 2; rev++)
        for (int j = 0; j < 4; j++) {
            Table& t = r.t[rev];
            for (int q = 0; q < 8; q++) {
                uint32_t* e = t.route[4 * q + j];
                e[0] = 4 * q + 2 * (j & 1) + (j >> 1); e[1] = e[0] ^ 1;
                e[2] = j < 2 ? 0x5410u : 0x1054u; e[3] = e[2] + 0x2222u;
                e = t.u[q][j];
                for (int n = 0; n < 7; n++) e[0] |= ((n + j) % 7 < q ? 1u : 0u) << n;
                e[3] = e[0];
                for (int k = 0; k < 2; k++) {
                    const int step = 2 * k + (j >> 1), p0 = (step < 3 ? 16 * step : 40) + 8 * (j & 1);
                    uint32_t m = 0x8888u;
                    for (int n = 0; n < 8; n++) m |= ((p0 + n) % 7 < q ? 1u : 0u) << (2 * n);
                    e[1 + k] = m * 0x10001u;
                }
            }
            for (int sum = 0; sum < 15; sum++) {
                uint32_t* e = t.v[sum][j];
                for (int row = 0; row < 2; row++)
                    for (int b = 0; b < 14; b++) {
                        const int off = (sum + row) / 2, p = 4 * b + j;
                        const uint32_t bit = 1u << (2 * b + row);
                        if (p < 42 && p >= 7 * off) e[rev] |= bit;
                        if (p < 7 * off - 7) e[1 - rev] |= bit;
                        if (p >= 42 && p >= 7 * off && p < 7 * off + 49) e[2] |= bit;
                    }
                for (int n = 0; n < 6; n++)
                    if (8 * n + 2 * j < 42) e[3] |= 1u << (n + ((8 * n + 2 * j >= 7 * (sum / 2 & ~1)) != rev ? 0 : 8));
            }
        }
    return r;
}
__device__ __align__(128) const Tables g_tables = make_tables();

#define WO4(i) "=f"(d[i]), "=f"(d[i + 1]), "=f"(d[i + 2]), "=f"(d[i + 3])
#define RW4(i) "+f"(d[i]), "+f"(d[i + 1]), "+f"(d[i + 2]), "+f"(d[i + 3])

template <bool FIRST>
__device__ __forceinline__ void wgmma_n192(float (&d)[96], uint32_t a0, uint32_t a1, uint32_t a2, uint32_t a3, uint64_t descb) {
    if constexpr (FIRST) {
        asm volatile(
            "wgmma.mma_async.sync.aligned.m64n192k16.f32.bf16.bf16 "
            "{%0, %1, %2, %3, %4, %5, %6, %7, %8, %9, %10, %11, %12, %13, %14, %15, %16, %17, %18, %19, %20, %21, %22, %23, "
            "%24, %25, %26, %27, %28, %29, %30, %31, %32, %33, %34, %35, %36, %37, %38, %39, %40, %41, %42, %43, %44, %45, %46, %47, "
            "%48, %49, %50, %51, %52, %53, %54, %55, %56, %57, %58, %59, %60, %61, %62, %63, %64, %65, %66, %67, %68, %69, %70, %71, "
            "%72, %73, %74, %75, %76, %77, %78, %79, %80, %81, %82, %83, %84, %85, %86, %87, %88, %89, %90, %91, %92, %93, %94, %95}, "
            "{%96, %97, %98, %99}, %100, 0, 1, 1, 0;"
            : WO4(0), WO4(4), WO4(8), WO4(12), WO4(16), WO4(20), WO4(24), WO4(28), WO4(32), WO4(36), WO4(40), WO4(44),
              WO4(48), WO4(52), WO4(56), WO4(60), WO4(64), WO4(68), WO4(72), WO4(76), WO4(80), WO4(84), WO4(88), WO4(92)
            : "r"(a0), "r"(a1), "r"(a2), "r"(a3), "l"(descb));
    } else {
        asm volatile(
            "wgmma.mma_async.sync.aligned.m64n192k16.f32.bf16.bf16 "
            "{%0, %1, %2, %3, %4, %5, %6, %7, %8, %9, %10, %11, %12, %13, %14, %15, %16, %17, %18, %19, %20, %21, %22, %23, "
            "%24, %25, %26, %27, %28, %29, %30, %31, %32, %33, %34, %35, %36, %37, %38, %39, %40, %41, %42, %43, %44, %45, %46, %47, "
            "%48, %49, %50, %51, %52, %53, %54, %55, %56, %57, %58, %59, %60, %61, %62, %63, %64, %65, %66, %67, %68, %69, %70, %71, "
            "%72, %73, %74, %75, %76, %77, %78, %79, %80, %81, %82, %83, %84, %85, %86, %87, %88, %89, %90, %91, %92, %93, %94, %95}, "
            "{%96, %97, %98, %99}, %100, 1, 1, 1, 0;"
            : RW4(0), RW4(4), RW4(8), RW4(12), RW4(16), RW4(20), RW4(24), RW4(28), RW4(32), RW4(36), RW4(40), RW4(44),
              RW4(48), RW4(52), RW4(56), RW4(60), RW4(64), RW4(68), RW4(72), RW4(76), RW4(80), RW4(84), RW4(88), RW4(92)
            : "r"(a0), "r"(a1), "r"(a2), "r"(a3), "l"(descb));
    }
}

template <bool FIRST>
__device__ __forceinline__ void wgmma_n88(float (&d)[44], uint32_t a0, uint32_t a1, uint32_t a2, uint32_t a3, uint64_t descb) {
    if constexpr (FIRST) {
        asm volatile(
            "wgmma.mma_async.sync.aligned.m64n88k16.f32.bf16.bf16 "
            "{%0, %1, %2, %3, %4, %5, %6, %7, %8, %9, %10, %11, %12, %13, %14, %15, %16, %17, %18, %19, %20, %21, %22, %23, "
            "%24, %25, %26, %27, %28, %29, %30, %31, %32, %33, %34, %35, %36, %37, %38, %39, %40, %41, %42, %43}, "
            "{%44, %45, %46, %47}, %48, 0, 1, 1, 0;"
            : WO4(0), WO4(4), WO4(8), WO4(12), WO4(16), WO4(20), WO4(24), WO4(28), WO4(32), WO4(36), WO4(40)
            : "r"(a0), "r"(a1), "r"(a2), "r"(a3), "l"(descb));
    } else {
        asm volatile(
            "wgmma.mma_async.sync.aligned.m64n88k16.f32.bf16.bf16 "
            "{%0, %1, %2, %3, %4, %5, %6, %7, %8, %9, %10, %11, %12, %13, %14, %15, %16, %17, %18, %19, %20, %21, %22, %23, "
            "%24, %25, %26, %27, %28, %29, %30, %31, %32, %33, %34, %35, %36, %37, %38, %39, %40, %41, %42, %43}, "
            "{%44, %45, %46, %47}, %48, 1, 1, 1, 0;"
            : RW4(0), RW4(4), RW4(8), RW4(12), RW4(16), RW4(20), RW4(24), RW4(28), RW4(32), RW4(36), RW4(40)
            : "r"(a0), "r"(a1), "r"(a2), "r"(a3), "l"(descb));
    }
}

template <bool FIRST>
__device__ __forceinline__ void wgmma_n32(float (&d)[16], uint32_t a0, uint32_t a1, uint32_t a2, uint32_t a3, uint64_t descb) {
    if constexpr (FIRST) {
        asm volatile(
            "wgmma.mma_async.sync.aligned.m64n32k16.f32.bf16.bf16 "
            "{%0, %1, %2, %3, %4, %5, %6, %7, %8, %9, %10, %11, %12, %13, %14, %15}, "
            "{%16, %17, %18, %19}, %20, 0, 1, 1, 0;"
            : WO4(0), WO4(4), WO4(8), WO4(12)
            : "r"(a0), "r"(a1), "r"(a2), "r"(a3), "l"(descb));
    } else {
        asm volatile(
            "wgmma.mma_async.sync.aligned.m64n32k16.f32.bf16.bf16 "
            "{%0, %1, %2, %3, %4, %5, %6, %7, %8, %9, %10, %11, %12, %13, %14, %15}, "
            "{%16, %17, %18, %19}, %20, 1, 1, 1, 0;"
            : RW4(0), RW4(4), RW4(8), RW4(12)
            : "r"(a0), "r"(a1), "r"(a2), "r"(a3), "l"(descb));
    }
}

template <bool FIRST, int SEL>
__device__ __forceinline__ void wgmma_sp_n192_tb(float (&d)[96], uint32_t a0, uint32_t a1, uint32_t a2, uint32_t a3, uint64_t descb, uint32_t meta) {
    if constexpr (FIRST) {
        asm volatile(
            "wgmma.mma_async.sp.sync.aligned.m64n192k32.f32.bf16.bf16 "
            "{%0, %1, %2, %3, %4, %5, %6, %7, %8, %9, %10, %11, %12, %13, %14, %15, %16, %17, %18, %19, %20, %21, %22, %23, "
            "%24, %25, %26, %27, %28, %29, %30, %31, %32, %33, %34, %35, %36, %37, %38, %39, %40, %41, %42, %43, %44, %45, %46, %47, "
            "%48, %49, %50, %51, %52, %53, %54, %55, %56, %57, %58, %59, %60, %61, %62, %63, %64, %65, %66, %67, %68, %69, %70, %71, "
            "%72, %73, %74, %75, %76, %77, %78, %79, %80, %81, %82, %83, %84, %85, %86, %87, %88, %89, %90, %91, %92, %93, %94, %95}, "
            "{%96, %97, %98, %99}, %100, %101, %102, 0, 1, 1, 1;"
            : WO4(0), WO4(4), WO4(8), WO4(12), WO4(16), WO4(20), WO4(24), WO4(28), WO4(32), WO4(36), WO4(40), WO4(44),
              WO4(48), WO4(52), WO4(56), WO4(60), WO4(64), WO4(68), WO4(72), WO4(76), WO4(80), WO4(84), WO4(88), WO4(92)
            : "r"(a0), "r"(a1), "r"(a2), "r"(a3), "l"(descb), "r"(meta), "n"(SEL));
    } else {
        asm volatile(
            "wgmma.mma_async.sp.sync.aligned.m64n192k32.f32.bf16.bf16 "
            "{%0, %1, %2, %3, %4, %5, %6, %7, %8, %9, %10, %11, %12, %13, %14, %15, %16, %17, %18, %19, %20, %21, %22, %23, "
            "%24, %25, %26, %27, %28, %29, %30, %31, %32, %33, %34, %35, %36, %37, %38, %39, %40, %41, %42, %43, %44, %45, %46, %47, "
            "%48, %49, %50, %51, %52, %53, %54, %55, %56, %57, %58, %59, %60, %61, %62, %63, %64, %65, %66, %67, %68, %69, %70, %71, "
            "%72, %73, %74, %75, %76, %77, %78, %79, %80, %81, %82, %83, %84, %85, %86, %87, %88, %89, %90, %91, %92, %93, %94, %95}, "
            "{%96, %97, %98, %99}, %100, %101, %102, 1, 1, 1, 1;"
            : RW4(0), RW4(4), RW4(8), RW4(12), RW4(16), RW4(20), RW4(24), RW4(28), RW4(32), RW4(36), RW4(40), RW4(44),
              RW4(48), RW4(52), RW4(56), RW4(60), RW4(64), RW4(68), RW4(72), RW4(76), RW4(80), RW4(84), RW4(88), RW4(92)
            : "r"(a0), "r"(a1), "r"(a2), "r"(a3), "l"(descb), "r"(meta), "n"(SEL));
    }
}

#define TR(slot)
#define TRE(slot)
#define TRT(slot)
#define TRF(slot)
#define TRW(slot)
#define TRG(slot)
#define TRDUMP()

__device__ __forceinline__ void wg_fence() { asm volatile("wgmma.fence.sync.aligned;" ::: "memory"); }
__device__ __forceinline__ void wg_commit() { asm volatile("wgmma.commit_group.sync.aligned;" ::: "memory"); }
template <int N>
__device__ __forceinline__ void wg_wait() { asm volatile("wgmma.wait_group.sync.aligned %0;" ::"n"(N) : "memory"); }

template <int N>
__device__ __forceinline__ void pin(float (&d)[N]) {
#pragma unroll
    for (int i = 0; i < N; i++) asm volatile("" : "+f"(d[i])::"memory");
}
template <int N>
__device__ __forceinline__ void pin(uint32_t (&d)[N]) {
#pragma unroll
    for (int i = 0; i < N; i++) asm volatile("" : "+r"(d[i])::"memory");
}

constexpr uint64_t kDescRing = ((uint64_t)((1u << 30) | (1024u >> 4)) << 32) | (1u << 16) | (s_ring >> 4);
constexpr uint32_t kToV = ((kRingChunk >> 4) - 1) << 20;
__device__ __forceinline__ uint64_t desc_at(uint64_t base, uint32_t byte_off) {
    uint64_t d;
    asm volatile("add.s64 %0, %1, %2;" : "=l"(d) : "l"(base), "l"((uint64_t)(byte_off >> 4)));
    return d;
}

__device__ __forceinline__ void mbar_init(uint32_t bar, uint32_t count) {
    asm volatile("mbarrier.init.shared::cta.b64 [%0], %1;" ::"r"(bar), "r"(count) : "memory");
}
__device__ __forceinline__ void mbar_expect_tx(uint32_t bar, uint32_t bytes) {
    asm volatile("mbarrier.arrive.expect_tx.shared::cta.b64 _, [%0], %1;" ::"r"(bar), "r"(bytes) : "memory");
}
__device__ __forceinline__ void expect_tx_only(uint32_t bar, uint32_t bytes) {
    asm volatile("mbarrier.expect_tx.relaxed.cta.shared::cta.b64 [%0], %1;" ::"r"(bar), "r"(bytes) : "memory");
}
__device__ __forceinline__ void mbar_arrive(uint32_t bar) {
    asm volatile("mbarrier.arrive.shared::cta.b64 _, [%0];" ::"r"(bar) : "memory");
}
__device__ __forceinline__ void mbar_wait(uint32_t bar, uint32_t parity) {
    asm volatile(
        "{\n.reg .pred p;\n"
        "W: mbarrier.try_wait.parity.shared::cta.b64 p, [%0], %1;\n"
        "@!p bra W;\n}\n"
        ::"r"(bar), "r"(parity) : "memory");
}
__device__ __forceinline__ uint32_t clock_now() {
    uint32_t c;
    asm volatile("mov.u32 %0, %%clock;" : "=r"(c)::"memory");
    return c;
}
__device__ __forceinline__ void wait_until(uint32_t t0, int t) {
    if (t == 0) return;
    while ((int)(clock_now() - t0) < t) {}
}
__device__ __forceinline__ bool elect() {
    uint32_t ok;
    asm volatile("{\n.reg .pred p;\nelect.sync _|p, 0xffffffff;\nselp.u32 %0, 1, 0, p;\n}\n" : "=r"(ok));
    return ok != 0;
}
__device__ __forceinline__ void turn_wait(int wg) { asm volatile("bar.sync %0, 256;" ::"r"(1 + wg) : "memory"); }
__device__ __forceinline__ void turn_pass(int wg) { asm volatile("bar.arrive %0, 256;" ::"r"(2 - wg) : "memory"); }

__device__ __forceinline__ void tma_box(uint32_t dst, const CUtensorMap* map, uint32_t bar, int c0, int c2, int c3, int c4) {
    asm volatile(
        "cp.async.bulk.tensor.5d.shared::cluster.global.mbarrier::complete_tx::bytes [%0], [%1, {%3, %4, %5, %6, %7}], [%2];"
        ::"r"(dst), "l"(map), "r"(bar), "r"(c0), "r"(0), "r"(c2), "r"(c3), "r"(c4)
        : "memory");
}
__device__ __forceinline__ void tma_3d(uint32_t dst, const CUtensorMap* map, uint32_t bar, int c1, int c2) {
    asm volatile("cp.async.bulk.tensor.3d.shared::cluster.global.mbarrier::complete_tx::bytes [%0], [%1, {%3, %4, %5}], [%2];"
                 ::"r"(dst), "l"(map), "r"(bar), "r"(0), "r"(c1), "r"(c2)
                 : "memory");
}
__device__ __forceinline__ void prefetch_map(const CUtensorMap* map) {
    asm volatile("prefetch.tensormap [%0];" ::"l"(map) : "memory");
}
__device__ __forceinline__ uint4 ldg(const void* p) {
    uint4 v;
    asm volatile("ld.global.v4.u32 {%0, %1, %2, %3}, [%4];" : "=r"(v.x), "=r"(v.y), "=r"(v.z), "=r"(v.w) : "l"(p) : "memory");
    return v;
}
__device__ __forceinline__ uint32_t pack_bf16(float lo, float hi) {
    uint32_t r;
    asm("cvt.rn.bf16x2.f32 %0, %1, %2;" : "=r"(r) : "f"(hi), "f"(lo));
    return r;
}
__device__ __forceinline__ float ex2(float x) {
    float y;
    asm("ex2.approx.ftz.f32 %0, %1;" : "=f"(y) : "f"(x));
    return y;
}
__device__ __forceinline__ float rcp(float x) {
    float y;
    asm("rcp.approx.ftz.f32 %0, %1;" : "=f"(y) : "f"(x));
    return y;
}
__device__ __forceinline__ void mma16816(float (&d)[4], uint32_t a0, uint32_t a1, uint32_t a2, uint32_t a3, uint32_t b0, uint32_t b1) {
    asm volatile("mma.sync.aligned.m16n8k16.row.col.f32.bf16.bf16.f32 {%0, %1, %2, %3}, {%4, %5, %6, %7}, {%8, %9}, {%0, %1, %2, %3};"
                 : "+f"(d[0]), "+f"(d[1]), "+f"(d[2]), "+f"(d[3])
                 : "r"(a0), "r"(a1), "r"(a2), "r"(a3), "r"(b0), "r"(b1));
}
__device__ __forceinline__ uint4 lds128(uint32_t addr) {
    uint4 v;
    asm volatile("ld.volatile.shared.v4.u32 {%0, %1, %2, %3}, [%4];" : "=r"(v.x), "=r"(v.y), "=r"(v.z), "=r"(v.w) : "r"(addr) : "memory");
    return v;
}
__device__ __forceinline__ uint32_t lds_volatile(uint32_t addr) {
    uint32_t v;
    asm volatile("ld.volatile.shared.u32 %0, [%1];" : "=r"(v) : "r"(addr) : "memory");
    return v;
}

__device__ __forceinline__ int window_start(int n) { return min(max(n, 0), 105); }
__device__ __forceinline__ int origin_u(int u) { return min(max(u, 0), 98); }

struct Work {
    int u, v;
    int step;
    uint32_t su, sv;
    uint32_t base;
    bool corner;
    int ntiles;
    __device__ __forceinline__ void pixel_offsets(int qu, int qv, int j, uint32_t& o0, uint32_t& o1) const {
        const uint32_t b = (qu + window_start(qu)) * su + j * 16 + base;
        o0 = b + (qv + window_start(qv)) * sv;
        o1 = b + (qv + 1 + window_start(qv + 1)) * sv;
    }
};

__device__ __forceinline__ Work decode_work(int c) {
    Work w;
    const bool transposed = (c >> 4) == 7;
    const int px = 6 * (c & 1), py = 3 * (c & 2);
    w.corner = c >= 128;
    w.step = 8 - 4 * (c & 4);
    w.u = (c < 112 ? c & ~7 : 96 + (c & 8)) + (transposed ? py : px) - 6;
    w.v = (w.corner ? 96 : 48 - 2 * (c & 4)) + (transposed ? px : py) - 6;
    w.su = transposed ? kHW * kPixBytes : kPixBytes;
    w.sv = transposed ? kPixBytes : kHW * kPixBytes;
    w.base = px * (kPixBytes / 6) + py * (kHW * kPixBytes / 6) + 6 * (kHW + 1) * kPixBytes;
    w.ntiles = w.corner ? 4 : 6;
    return w;
}

struct RawX { uint4 a[6], b[6]; };
__device__ __forceinline__ void load_raw(RawX& r, const uint8_t* base, uint32_t o0, uint32_t o1) {
    __syncwarp();
#pragma unroll
    for (int c = 0; c < 6; c++) { r.a[c] = ldg(base + o0 + c * 64); r.b[c] = ldg(base + o1 + c * 64); }
    __syncwarp();
}
__device__ __forceinline__ void raw_to_frags(const RawX& r, uint32_t zero, uint32_t (&f)[48]) {
#pragma unroll
    for (int c = 0; c < 6; c++) {
        asm volatile("{\n.reg .b32 t, u;\nadd.u32 t, %4, %8;\nadd.u32 u, %5, %8;\nxor.b32 %0, %6, %8;\nxor.b32 %1, %7, %8;\n"
                     "xor.b32 %2, t, %8;\nxor.b32 %3, u, %8;\n}\n"
                     : "=&r"(f[8 * c + 1]), "=&r"(f[8 * c + 3]), "=&r"(f[8 * c + 4]), "=&r"(f[8 * c + 6])
                     : "r"(r.a[c].y), "r"(r.a[c].w), "r"(r.b[c].x), "r"(r.b[c].z), "r"(zero));
        f[8 * c + 0] = r.a[c].x; f[8 * c + 2] = r.a[c].z; f[8 * c + 5] = r.b[c].y; f[8 * c + 7] = r.b[c].w;
    }
}
__device__ __forceinline__ void acc_to_frags(const float (&d)[96], uint32_t (&f)[48]) {
#pragma unroll
    for (int i = 0; i < 48; i++) f[i] = pack_bf16(d[2 * i], d[2 * i + 1]);
}

template <class F>
__device__ __forceinline__ void proj_gemm(float (&d)[96], const uint32_t (&a)[48], uint64_t dsc, uint32_t img, F after) {
#pragma unroll
    for (int s = 0; s < 12; s++) {
        if (s == 0) wgmma_n192<true>(d, a[4 * s], a[4 * s + 1], a[4 * s + 2], a[4 * s + 3], desc_at(dsc, img - s_ring + (s >> 2) * kWChunk + (s & 3) * 32));
        else wgmma_n192<false>(d, a[4 * s], a[4 * s + 1], a[4 * s + 2], a[4 * s + 3], desc_at(dsc, img - s_ring + (s >> 2) * kWChunk + (s & 3) * 32));
        if (s == 11) wg_commit();
        after(s);
    }
}
__device__ __forceinline__ void pack_out(const float (&acc)[96], uint32_t (&po)[48]) {
#pragma unroll
    for (int g = 0; g < 6; g++)
#pragma unroll
        for (int q = 0; q < 4; q++) {
            po[8 * g + q] = pack_bf16(acc[16 * g + 4 * q], acc[16 * g + 4 * q + 1]);
            po[8 * g + 4 + q] = pack_bf16(acc[16 * g + 4 * q + 2], acc[16 * g + 4 * q + 3]);
        }
}
template <bool PINNED = true>
__device__ __forceinline__ void store_one(bool on, uint8_t* p0, uint8_t* p1, const uint32_t (&po)[48], int n) {
    if (PINNED) __syncwarp();
    asm volatile("{\n.reg .pred p;\nsetp.ne.u32 p, %5, 0;\n@p st.global.v4.u32 [%0], {%1, %2, %3, %4};\n}\n"
                 ::"l"(((n & 1) ? p1 : p0) + (n >> 1) * 64), "r"(po[4 * n]), "r"(po[4 * n + 1]), "r"(po[4 * n + 2]), "r"(po[4 * n + 3]), "r"((uint32_t)on) : "memory");
}

template <int N>
__device__ __forceinline__ float tree_max(const float (&v)[N]) {
    float t[N];
#pragma unroll
    for (int i = 0; i < N; i++) t[i] = v[i];
#pragma unroll
    for (int w = 1; w < N; w *= 2)
#pragma unroll
        for (int i = 0; i + w < N; i += 2 * w) t[i] = fmaxf(t[i], t[i + w]);
    return t[0];
}
template <int N>
__device__ __forceinline__ float tree_sum(const float (&v)[N]) {
    float t[N];
#pragma unroll
    for (int i = 0; i < N; i++) t[i] = v[i];
#pragma unroll
    for (int w = 1; w < N; w *= 2)
#pragma unroll
        for (int i = 0; i + w < N; i += 2 * w) t[i] += t[i + w];
    return t[0];
}

template <int B>
__device__ __forceinline__ void pick(uint32_t h, uint32_t ok, const float* s, float& v0, float& v1) {
    asm("{\n.reg .pred p, q0, q1;\n.reg .b32 t;\nand.b32 t, %6, %7;\nsetp.ne.u32 p, t, 0;\n"
        "and.b32 t, %8, %9;\nsetp.ne.u32 q0, t, 0;\nand.b32 t, %8, %10;\nsetp.ne.u32 q1, t, 0;\n"
        "@q0 selp.f32 %0, %3, %2, p;\n@q1 selp.f32 %1, %5, %4, p;\n}\n"
        : "+f"(v0), "+f"(v1)
        : "f"(s[0]), "f"(s[1]), "f"(s[2]), "f"(s[3]), "r"(h), "n"(1 << ((4 * B) % 7)), "r"(ok), "n"(1 << (2 * B)), "n"(2 << (2 * B)));
}
template <int B, class F>
__device__ __forceinline__ void for_blocks(F f) {
    if constexpr (B > 0) { for_blocks<B - 1>(f); f(std::integral_constant<int, B - 1>{}); }
}
__device__ __forceinline__ void gather_outer(const float (&s)[44], uint32_t h, uint32_t ok, float (&v0)[14], float (&v1)[14]) {
    for_blocks<11>([&](auto B) {
        constexpr int b = B.value < 8 ? (B.value >> 1) + 7 * (B.value & 1) : B.value - 4;
        pick<b>(h, ok, &s[4 * b], v0[b], v1[b]);
    });
}
__device__ __forceinline__ void gather_mid(const float (&sE)[16], uint32_t h, uint32_t ok, float (&v0)[14], float (&v1)[14]) {
    for_blocks<4>([&](auto B) { pick<10 + B.value>(h, ok, &sE[4 * B.value], v0[10 + B.value], v1[10 + B.value]); });
}
__device__ __forceinline__ float quad_max(float m) {
    m = fmaxf(m, __shfl_xor_sync(0xffffffffu, m, 1));
    return fmaxf(m, __shfl_xor_sync(0xffffffffu, m, 2));
}
__device__ __forceinline__ float quad_sum(float s) {
    s += __shfl_xor_sync(0xffffffffu, s, 1);
    return s + __shfl_xor_sync(0xffffffffu, s, 2);
}
template <int B0, int B1>
__device__ __forceinline__ void exp_route(float (&v0)[14], float (&v1)[14], float m0, float m1, const uint4& r, bool even, uint32_t (&y)[14]) {
#pragma unroll
    for (int b = B0; b < B1; b++) { v0[b] = ex2(v0[b] - m0); v1[b] = ex2(v1[b] - m1); }
#pragma unroll
    for (int b = B0; b < B1; b += 2) {
        const uint32_t x0 = pack_bf16(v0[b], v1[b]), x1 = pack_bf16(v0[b + 1], v1[b + 1]);
        const uint32_t u = __shfl_sync(0xffffffffu, even ? x0 : x1, r.x);
        const uint32_t w = __shfl_sync(0xffffffffu, even ? x1 : x0, r.y);
        y[b] = __byte_perm(u, w, r.z); y[b + 1] = __byte_perm(u, w, r.w);
    }
}
template <int BIT0, int N0, int N1>
__device__ __forceinline__ void unfold(const uint32_t (&y)[14], uint32_t fold, uint32_t (&p)[12]) {
    for_blocks<N1 - N0>([&](auto N) {
        constexpr int n = N0 + N.value;
        asm("{\n.reg .pred p;\n.reg .b32 t;\nand.b32 t, %4, %5;\nsetp.ne.u32 p, t, 0;\nselp.b32 %0, %2, 0, p;\nselp.b32 %1, %3, 0, p;\n}\n"
            : "=r"(p[2 * n]), "=r"(p[2 * n + 1]) : "r"(y[2 * n]), "r"(y[2 * n + 1]), "r"(fold), "n"(1 << (BIT0 + n)));
    });
}
__device__ __forceinline__ void keep(bool never, uint32_t a, uint32_t b, uint32_t c, uint32_t d) {
    asm volatile("{\n.reg .pred p;\nsetp.ne.u32 p, %4, 0;\n@p st.volatile.shared.v4.u32 [%5], {%0, %1, %2, %3};\n}\n"
                 ::"r"(a), "r"(b), "r"(c), "r"(d), "r"((uint32_t)never), "r"(s_trace) : "memory");
}

__device__ __forceinline__ uint32_t wimg_offset(uint32_t row, uint32_t s, uint32_t j) {
    return (s >> 2) * kWChunk + row * 128 + (((2 * (s & 3) + (j >> 1)) ^ (row & 7)) << 4) + (j & 1) * 8;
}

__device__ __forceinline__ void ldsm4(uint32_t (&r)[4], uint32_t addr) {
    asm volatile("ldmatrix.sync.aligned.m8n8.x4.shared.b16 {%0, %1, %2, %3}, [%4];" : "=r"(r[0]), "=r"(r[1]), "=r"(r[2]), "=r"(r[3]) : "r"(addr) : "memory");
}
__device__ __forceinline__ void ldsm4_t(uint32_t (&r)[4], uint32_t addr) {
    asm volatile("ldmatrix.sync.aligned.m8n8.x4.trans.shared.b16 {%0, %1, %2, %3}, [%4];" : "=r"(r[0]), "=r"(r[1]), "=r"(r[2]), "=r"(r[3]) : "r"(addr) : "memory");
}
__device__ __forceinline__ void m_partial(const uint8_t* wqkv, uint32_t mt, uint32_t s, uint32_t q, uint32_t lane, uint32_t zero) {
    const uint32_t r8 = lane >> 2, col = q * 128 + (lane & 3) * 16;
    const uint8_t* pa = wqkv + (16 * mt + r8) * 1152 + col;
    const uint8_t* pb = wqkv + (16 * s + 8 * (r8 & 2) + (r8 & 5)) * 1152 + col;
    uint4 A[2][2], B[4][2];
#pragma unroll
    for (int c = 0; c < 2; c++) {
#pragma unroll
        for (int h = 0; h < 2; h++) A[h][c] = ldg(pa + 384 + h * 8 * 1152 + c * 64);
#pragma unroll
        for (int n = 0; n < 4; n++) B[n][c] = ldg(pb + ((n & 1) * 8 + (n & 2)) * 1152 + c * 64);
    }
#pragma unroll
    for (int i = 0; i < 4; i++) { uint4& a = A[i >> 1][i & 1]; a.x ^= zero; a.y ^= zero; a.z ^= zero; a.w ^= zero; }
#pragma unroll
    for (int n = 0; n < 4; n++) {
        float d[4] = {0.f, 0.f, 0.f, 0.f};
#pragma unroll
        for (int c = 0; c < 2; c++) {
            mma16816(d, A[0][c].x, A[1][c].x, A[0][c].y, A[1][c].y, B[n][c].x, B[n][c].y);
            mma16816(d, A[0][c].z, A[1][c].z, A[0][c].w, A[1][c].w, B[n][c].z, B[n][c].w);
        }
        asm volatile("st.shared.v4.f32 [%0], {%1, %2, %3, %4};" ::"r"(s_wv + q * 2048 + n * 512 + lane * 16), "f"(d[0]), "f"(d[1]), "f"(d[2]), "f"(d[3]) : "memory");
    }
}
__device__ __forceinline__ void m_reduce(uint32_t e, uint32_t lane, float (&d)[2][4]) {
#pragma unroll
    for (int n = 0; n < 2; n++) {
        float t[3][4];
#pragma unroll
        for (int q = 0; q < 3; q++)
            asm volatile("ld.shared.v4.f32 {%0, %1, %2, %3}, [%4];" : "=f"(t[q][0]), "=f"(t[q][1]), "=f"(t[q][2]), "=f"(t[q][3]) : "r"(s_wv + q * 2048 + e * 1024 + n * 512 + lane * 16) : "memory");
#pragma unroll
        for (int i = 0; i < 4; i++) d[n][i] = (t[0][i] + t[1][i] + t[2][i]) * kScaleLog2e;
    }
}
__device__ __forceinline__ void w_piece(uint32_t q, uint32_t lane, float (&d)[2][4]) {
    const uint32_t rr = lane & 7, mi = lane >> 3, kr = 4 * (rr >> 1) + (mi & 2) + (rr & 1);
    const uint32_t pa = s_wv + q * 6144 + (4 * (mi & 2) + rr) * 32 + (((mi ^ (rr >> 2)) & 1) << 4);
    const uint32_t pb = s_wv + 3 * 6144 + kr * 32 + (((mi ^ (kr >> 2)) & 1) << 4);
#pragma unroll
    for (int i = 0; i < 8; i++) (&d[0][0])[i] = 0.f;
#pragma unroll kWUnroll
    for (int k = 0; k < 12; k++) {
        uint32_t aq[4], bq[4];
        ldsm4_t(aq, pa + k * 512);
        ldsm4(bq, pb + k * 512);
        mma16816(d[0], aq[0], aq[1], aq[2], aq[3], bq[0], bq[1]);
        mma16816(d[1], aq[0], aq[1], aq[2], aq[3], bq[2], bq[3]);
    }
}
__device__ __forceinline__ uint32_t piece_offset(uint32_t which, uint32_t s, uint32_t mt, uint32_t lane) {
    const uint32_t r8 = lane >> 2;
    return which * kWBytes + wimg_offset(which ? 32 * (mt >> 1) + 8 * (r8 >> 1) + 4 * (mt & 1) + (r8 & 1) : 16 * mt + r8, s, lane & 3);
}
__device__ __forceinline__ void piece_store(Scratch* g, uint32_t par, uint32_t off0, uint32_t which, const float (&d)[2][4]) {
#pragma unroll
    for (int hf = 0; hf < 2; hf++) {
        const uint32_t off = off0 ^ (hf ? which ? 288 : 1024 : 0);
        const uint32_t a = pack_bf16(d[0][2 * hf], d[0][2 * hf + 1]), b = pack_bf16(d[1][2 * hf], d[1][2 * hf + 1]);
        asm volatile("st.relaxed.gpu.global.v2.u32 [%0], {%1, %2};" ::"l"(g->img[0][0] + (par + off)), "r"(a ? a : 0x8000u), "r"(b) : "memory");
    }
}
__device__ __forceinline__ void piece_clear(Scratch* g, uint32_t par, uint32_t off0, uint32_t which) {
#pragma unroll
    for (int hf = 0; hf < 2; hf++)
        asm volatile("st.relaxed.gpu.global.v2.u32 [%0], {%1, %1};" ::"l"(g->img[0][0] + (par + (off0 ^ (hf ? which ? 288 : 1024 : 0)))), "r"(0) : "memory");
}

__device__ __forceinline__ uint32_t ld_relaxed(const uint32_t* p) {
    uint32_t v;
    asm volatile("ld.relaxed.gpu.global.u32 %0, [%1];" : "=r"(v) : "l"(p) : "memory");
    return v;
}
__device__ __forceinline__ void count_up(uint32_t* p) {
    asm volatile("red.relaxed.gpu.global.add.u32 [%0], %1;" ::"l"(p), "r"(1) : "memory");
}
__device__ __forceinline__ void bulk_g2s(uint32_t dst, const void* src, uint32_t bytes, uint32_t bar) {
    asm volatile("cp.async.bulk.shared::cluster.global.mbarrier::complete_tx::bytes [%0], [%1], %2, [%3];"
                 ::"r"(dst), "l"(src), "r"(bytes), "r"(bar)
                 : "memory");
}

__global__ void __launch_bounds__(kThreads, 1)
nat_fused_kernel(const uint8_t* __restrict__ x, const uint8_t* __restrict__ wqkv, uint8_t* __restrict__ out, Scratch* g,
                 const Tables* tables, uint64_t dsc, const __grid_constant__ Maps maps) {
    const int tid = threadIdx.x, lane = tid & 31;
    const int warp = __shfl_sync(0xffffffffu, tid >> 5, 0);
    const int wg = warp >> 2, wq = warp & 3, r8 = lane >> 2, j = lane & 3;
    const int cta = blockIdx.x;
    const Work w = decode_work(cta);
    const uint32_t which = cta >= 72, job = which ? cta - 72 : 2 * cta, jhi = job / 12, jlo = job % 12;
    if (wg == 1 && wq < 3) {
#pragma unroll
        for (int r = 0; r < 3; r++)
            asm volatile("st.shared.v4.u32 [%0], {%1, %1, %1, %1};" ::"r"(s_ring + wq * kRingChunk + (r == 0 ? 84 : r == 1 ? 88 : 204) * 128 + lane * 16), "r"(0) : "memory");
        asm volatile("fence.proxy.async.shared::cta;" ::: "memory");
    }
    if (x == nullptr) return;
    const uint32_t t_start = clock_now();
    if (wg == 2) {
        if (wq < 3 && !which) m_partial(wqkv, jhi, jlo, wq, lane, (uint32_t)dsc & 1);
        asm volatile("setmaxnreg.dec.sync.aligned.u32 40;");
        if (wq < 3) {
            const uint32_t off = piece_offset(which, which ? jlo : jlo + wq, which ? 3 * jhi + wq : jhi, lane);
            asm volatile("bar.sync %0, 128;" ::"r"(5 + (off >> 31)) : "memory");
            const uint32_t par = lds_volatile(s_par);
            if (cta < 120 && wq < 2 + which) {
                float d[2][4];
                if (wq == 0) TRW(which ? 1 : 18);
                if (which) {
                    mbar_wait(bar_wop, 0);
                    if (wq == 0) TRW(2);
                    w_piece(wq, lane, d);
                } else {
                    m_reduce(wq, lane, d);
                }
                piece_store(g, par, off, which, d);
                __syncwarp();
                piece_clear(g, 2 * kWBytes - par, off, which);
                if (wq == 0) TRW(which ? 3 : 0);
            }
            asm volatile("bar.arrive 6, 128;" ::: "memory");
            uint32_t phase = 0;
#pragma unroll 1
            for (uint32_t c = 0; c < 6; c++) {
                const uint32_t part = c * kWChunk + wq * (kWChunk / 3), img = 8 * min(c, 3u);
                mbar_wait(bar_img + 8 * c, 0);
                if (wq == 0) TRW(10 + c);
#pragma unroll 1
                while (true) {
                    uint32_t lo = ~0u;
#pragma unroll
                    for (int q = 0; q < 8; q++) lo = min(lo, lds_volatile(s_m + part + lane * 32 + (lane & 12) * 2 + q * 1024));
                    if (__all_sync(0xffffffffu, lo) || phase > 65535) break;
                    if (elect()) {
                        mbar_expect_tx(bar_redo + 8 * wq, kWChunk / 3);
                        bulk_g2s(s_m + part, g->img[0][0] + par + part, kWChunk / 3, bar_redo + 8 * wq);
                    }
                    mbar_wait(bar_redo + 8 * wq, phase++ & 1);
                }
                if (c != 3 && c != 4 && lane == 0) mbar_arrive(bar_ok + img);
            }
        } else {
            uint32_t launch = ld_relaxed(&g->launches);
            const CUtensorMap* map = &maps.m[w.sv == kPixBytes ? 2 : 0];
            if (elect()) {
#pragma unroll
                for (int i = 0; i < 20; i++) mbar_init(s_bar + 8 * i, i < 13 ? 1 : i < 18 ? 3 : 4);
                asm volatile("fence.mbarrier_init.release.cluster;" ::: "memory");
                prefetch_map(map + 1);
                expect_tx_only(bar_a, sizeof(Table));
                bulk_g2s(s_tab, &tables->t[w.step < 0], sizeof(Table), bar_a);
            }
            if (which && cta < 120 && elect()) {
                mbar_expect_tx(bar_wop, 4 * 6144);
                tma_3d(s_wv, &maps.wo, bar_wop, 0, 3 * jhi);
                tma_3d(s_wv + 3 * 6144, &maps.wv, bar_wop, 16 * jlo, 24);
            }
            int u = w.u, v = w.v;
            uint32_t wait_bar = bar_use, wait_par = 1, slot = 0;
#pragma unroll 1
            for (int step = 0; step < 7 - w.corner; step++) {
                const bool first = step == 0 || (w.corner && step == 4);
                const int row = v + 4 + (first ? -w.step : w.step) / 2, ou = origin_u(u);
                uint32_t dst = s_ring + (first ? 0 : slot), mid = s_ring + kOffMid + 512, bar = first ? bar_a : bar_b;
                mbar_wait(wait_bar, wait_par);
                TRW(24 + step);
#pragma unroll 1
                for (int ch = (cta & 1) * kC; mid < s_m; ch += 64, dst += kRingChunk, mid += kRingChunk) {
                    if (elect()) {
                        mbar_expect_tx(bar, first ? kSlotBytes : kSlotBytes + kMidBytes);
                        tma_box(dst, map, bar, ch, ou, (cta >> 1) & 1, row);
                    }
                    if (!first) {
                        if (elect()) tma_box(mid, map + 1, bar, ch, ou, (cta >> 1) & 1, v + 6);
                        bar += 8;
                    }
                }
                if (step == 0) {
                    launch /= kGrid;
                    asm volatile("st.shared.v2.u32 [%0], {%1, %2};" ::"r"(s_par), "r"((launch & 1) * 2 * kWBytes), "r"(0) : "memory");
                    asm volatile("bar.arrive 5, 128;\nbar.arrive 3, 160;\nbar.arrive 4, 160;" ::: "memory");
                }
                if (step < 2) {
                    if (step) {
                        if (lane == 0) count_up(&g->launches);
                        asm volatile("bar.sync 6, 128;" ::: "memory");
                    }
                    wait_until(t_start, step ? TN(5, kTimeW) : TN(6, kTimeM));
                    TRW(5 + 4 * step);
#pragma unroll 1
                    for (int c = 3 * step; c < 3 + 3 * step; c++)
                        if (elect()) {
                            mbar_expect_tx(bar_img + 8 * c, kWChunk);
                            bulk_g2s(s_m + c * kWChunk, g->img[launch & 1][0] + c * kWChunk, kWChunk, bar_img + 8 * c);
                        }
                }
                const bool again = w.corner && step == 3;
                wait_bar = step == 0 ? bar_img + 8 * TN(1, 1) : again ? bar_use + 8 : bar_use;
                if (!again) {
                    wait_par = slot ? 0 : step != 0;
                    slot ^= kSlotStride;
                    if (w.corner && step == 2) { u += 8; v -= 8; } else if (step) v += w.step;
                }
            }
        }
        TRDUMP();
        return;
    }
    const int order = w.step < 0 ? warp ^ 3 : warp;
    int tu = w.u, tv = w.v + w.step * wg;
    const int du2 = w.corner ? 8 : 0, dv2 = w.corner ? 0 : 2 * w.step;
    uint32_t o0, o1;
    wait_until(t_start, START_TIME);
    asm volatile("setmaxnreg.inc.sync.aligned.u32 232;");
    w.pixel_offsets(tu + r8, tv + 2 * wq, j, o0, o1);
    uint32_t fa[48];
    {
        RawX raw;
        load_raw(raw, x, o0, o1);
        asm volatile("bar.sync %0, 160;" ::"r"(3 + wg) : "memory");
        raw_to_frags(raw, 0, fa);
        pin(fa);
    }
    mbar_wait(bar_ok, 0);
    const uint64_t dA = dsc + wg * (kSlotStride >> 4), dB = dsc + (wg ^ 1) * (kSlotStride >> 4);

    float acc[96];
    uint32_t po[48];
    uint32_t c0, c1;
    asm volatile("" : "=r"(c0), "=r"(c1));
#pragma unroll
    for (int q = 0; q < 48; q++) asm volatile("" : "=r"(po[q]));
#pragma unroll 1
    for (int i = wg; i < w.ntiles; i += 2) {
        const bool first = i == 0, last = i == w.ntiles - 1;

        TRF(8 + 16 * k);
        wg_fence();
        if (!first) turn_wait(wg);
        proj_gemm(acc, fa, dsc, s_m, [&](int s) {
            if (s == 11 && !first) turn_pass(wg);
            const int n = __builtin_popcount(QSLOTS & ((1 << s) - 1));
            if (((QSLOTS >> s) & 1) && n < 12) store_one(i >= 2, out + c0, out + c1, po, n);
            if (s == 3 || s == 7) { mbar_wait(bar_ok + 2 * s + 2, 0); wg_fence(); }
        });
        __syncwarp();
        TRF(9 + 16 * k);
        uint8_t *p0 = out + c0, *p1 = out + c1;
        c0 = o0; c1 = o1;
        w.pixel_offsets(tu + du2 + r8, tv + dv2 + 2 * wq, j, o0, o1);
        if (i + 2 >= w.ntiles) o0 = o1 = 0;
        wg_wait<0>();
        pin(acc);
        TR(11 + 16 * k);
        TRT(80 + k);
#pragma unroll
        for (int n = __builtin_popcount(QSLOTS); n < 12 - __builtin_popcount(ASLOTS) - __builtin_popcount(BSLOTS); n++) store_one(i >= 2, p0, p1, po, n);
        acc_to_frags(acc, fa);
        pin(fa);

        float sA[44], sE[16], sB[44];
        RawX nxt;
        if (!first) turn_wait(wg);
        mbar_wait(bar_a, w.corner ? i >> 1 : 0);
        if (i == 0) TR(12);
        wg_fence();
#pragma unroll
        for (int s = 0; s < 12; s++) {
            if (s == 0) wgmma_n88<true>(sA, fa[4 * s], fa[4 * s + 1], fa[4 * s + 2], fa[4 * s + 3], desc_at(dA, (s >> 2) * kRingChunk + (s & 3) * 32));
            else wgmma_n88<false>(sA, fa[4 * s], fa[4 * s + 1], fa[4 * s + 2], fa[4 * s + 3], desc_at(dA, (s >> 2) * kRingChunk + (s & 3) * 32));
            if (s == 11) { wg_commit(); if (!first) turn_pass(wg); }
            if ((ASLOTS >> s) & 1) store_one(i >= 2, p0, p1, po, 12 - __builtin_popcount(BSLOTS) - __builtin_popcount(ASLOTS >> s));
        }
#pragma unroll
        for (int s = 12; s < 16; s++)
            if ((ASLOTS >> s) & 1) store_one(i >= 2, p0, p1, po, 12 - __builtin_popcount(BSLOTS) - __builtin_popcount(ASLOTS >> s));
        TRF(12 + 16 * k);
        const int vq = tv + 2 * wq;
        const uint4 tabu = lds128(s_tab + offsetof(Table, u) + (window_start(tu + r8) - origin_u(tu)) * 64 + j * 16);
        const uint4 tabv = lds128(s_tab + offsetof(Table, v) + (window_start(vq) + window_start(vq + 1) - 2 * tv) * 64 + j * 16);
        const uint4 route = lds128(s_tab + lane * 16);
        load_raw(nxt, x, o0, o1);
        float v0[14], v1[14];
#pragma unroll
        for (int b = 0; b < 14; b++) v0[b] = v1[b] = __int_as_float(0xff800000);
        wg_wait<0>();
        pin(sA);
        gather_outer(sA, tabu.x, tabv.x, v0, v1);
        pin(v0); pin(v1);
        if (!first) turn_wait(wg);
#pragma unroll
        for (int c = 0; c < 3; c++) {
            mbar_wait(bar_b + 8 * c, wg);
            if (i == 0 && c != 1) TR(13 + c);
            wg_fence();
#pragma unroll
            for (int s = 4 * c; s < 4 * c + 4; s++) {
                if (s == 0) wgmma_n88<true>(sB, fa[4 * s], fa[4 * s + 1], fa[4 * s + 2], fa[4 * s + 3], desc_at(dB, c * kRingChunk + (s & 3) * 32));
                else wgmma_n88<false>(sB, fa[4 * s], fa[4 * s + 1], fa[4 * s + 2], fa[4 * s + 3], desc_at(dB, c * kRingChunk + (s & 3) * 32));
                if ((BSLOTS >> s) & 1) store_one(i >= 2, p0, p1, po, 12 - __builtin_popcount(BSLOTS >> s));
            }
        }
        wg_commit();
#pragma unroll
        for (int s = 0; s < 12; s++)
            if (s == 0) wgmma_n32<true>(sE, fa[4 * s], fa[4 * s + 1], fa[4 * s + 2], fa[4 * s + 3], desc_at(dsc, kOffMid + (s >> 2) * kRingChunk + (s & 3) * 32));
            else wgmma_n32<false>(sE, fa[4 * s], fa[4 * s + 1], fa[4 * s + 2], fa[4 * s + 3], desc_at(dsc, kOffMid + (s >> 2) * kRingChunk + (s & 3) * 32));
        wg_commit();
        if (OSPLIT || !last) turn_pass(wg);
        TRF(13 + 16 * k);
        wg_wait<1>();
        pin(sB);
        gather_outer(sB, tabu.w, tabv.y, v0, v1);
        wg_wait<0>();
        pin(sE);
        TRF(14 + 16 * k);
        gather_mid(sE, tabu.w, tabv.z, v0, v1);
        const float m0 = quad_max(tree_max(v0)), m1 = quad_max(tree_max(v1));

        uint32_t y[14], pa[12], pb[12];
        exp_route<0, 14>(v0, v1, m0, m1, route, (j & 1) == 0, y);
        float s0 = tree_sum(v0), s1 = tree_sum(v1);
        asm volatile("" : "+f"(s0), "+f"(s1));
        unfold<0, 0, 6>(y, tabv.w, pa);
        if (OSPLIT || !last) turn_wait(wg + (y[0] >> 31));
        TRF(15 + 16 * k + (y[13] >> 31));
        wg_fence();
        wgmma_sp_n192_tb<true, 0>(acc, pa[0], pa[1], pa[2], pa[3], desc_at(dA, kToV), tabu.y);
        wgmma_sp_n192_tb<false, 1>(acc, pa[4], pa[5], pa[6], pa[7], desc_at(dA, kToV + 4096), tabu.y);
        wgmma_sp_n192_tb<false, 0>(acc, pa[8], pa[9], pa[10], pa[11], desc_at(dA, kToV + 8192), tabu.z);
        wgmma_sp_n192_tb<false, 1>(acc, y[10], y[11], y[12], y[13], desc_at(dsc, kToV + kOffMid), tabu.z);
        wg_commit();
        unfold<8, 0, 6>(y, tabv.w, pb);
        wg_fence();
        wgmma_sp_n192_tb<false, 0>(acc, pb[0], pb[1], pb[2], pb[3], desc_at(dB, kToV), tabu.y);
        wgmma_sp_n192_tb<false, 1>(acc, pb[4], pb[5], pb[6], pb[7], desc_at(dB, kToV + 4096), tabu.y);
        wgmma_sp_n192_tb<false, 0>(acc, pb[8], pb[9], pb[10], pb[11], desc_at(dB, kToV + 8192), tabu.z);
        wg_commit();
        if (!last) turn_pass(wg);
        TRF(16 + 16 * k);
        wg_wait<1>();
        if (lane == 0) mbar_arrive(bar_use);
        TRF(17 + 16 * k);
        mbar_wait(bar_ok + 24, 0);
        wg_wait<0>();
        if (lane == 0) mbar_arrive(bar_use + 8);
        pin(acc);
        TR(18 + 16 * k);

        acc_to_frags(acc, po);
        pin(po);
        if (!last) turn_wait(wg);
        wg_fence();
        proj_gemm(acc, po, dsc, s_wv, [&](int s) {
            if (s + 1 == OSPLIT && i + 2 == w.ntiles) { turn_pass(wg); turn_wait(wg); }
        });
        if (!last) turn_pass(wg);
        TRF(19 + 16 * k);
        const uint32_t zero = lds_volatile(s_late);
        const float inv0 = rcp(quad_sum(s0 + __uint_as_float(zero))), inv1 = rcp(quad_sum(s1 + __uint_as_float(zero)));
        raw_to_frags(nxt, zero, fa);
        pin(fa);
#pragma unroll
        for (int q = 0; q < 48; q += 4) keep(wqkv == nullptr, fa[q], fa[q + 1], fa[q + 2], fa[q + 3]);
        keep(wqkv == nullptr, __float_as_uint(inv0), __float_as_uint(inv1), zero, lane);
        TRF(20 + 16 * k);
        tu += du2; tv += dv2;
        wg_wait<0>();
        pin(acc);
        TR(21 + 16 * k);
#pragma unroll
        for (int q = 0; q < 96; q++) acc[q] *= q & 2 ? inv1 : inv0;
        pack_out(acc, po);
#pragma unroll
        for (int n = 0; n < INLOOP; n++) store_one<false>(last, out + c0, out + c1, po, n);
        pin(po);
    }
#pragma unroll
    for (int n = 0; n < 12; n++) {
        asm volatile("{\n.reg .pred p;\nsetp.eq.u32 p, %0, 0;\n@p nanosleep.u32 %1;\n}\n" ::"r"(wg), "n"(NAP) : "memory");
        store_one<false>(n >= INLOOP || wg == 0, out + c0, out + c1, po, n);
    }
    TRE(7);
    TRG(1);
    TRDUMP();
}

typedef CUresult (*EncodeTiledFn)(CUtensorMap*, CUtensorMapDataType, cuuint32_t, void*, const cuuint64_t*, const cuuint64_t*,
                                  const cuuint32_t*, const cuuint32_t*, CUtensorMapInterleave, CUtensorMapSwizzle,
                                  CUtensorMapL2promotion, CUtensorMapFloatOOBfill);

bool make_maps(EncodeTiledFn fn, Maps* maps, void* x, void* wqkv, void* wo) {
    const cuuint64_t pix2 = 2 * kPixBytes, row = (cuuint64_t)kHW * kPixBytes;
    const cuuint32_t estr[5] = {1, 1, 1, 1, 1};
    bool ok = true;
    for (int tr = 0; tr < 2; tr++)
        for (int b = 0; b < 2; b++) {
            const cuuint64_t su = tr ? 2 * row : pix2, sv = tr ? pix2 : 2 * row;
            const cuuint64_t dims[5] = {2 * kC, 2, 105, 2, 112};
            const cuuint64_t strides[4] = {7 * su, su, row, sv};
            const cuuint32_t box[5] = {64, 2, 7, 1, b ? 2u : 6u};
            ok = ok && fn(&maps->m[2 * tr + b], CU_TENSOR_MAP_DATA_TYPE_BFLOAT16, 5, x, dims, strides, box, estr,
                          CU_TENSOR_MAP_INTERLEAVE_NONE, CU_TENSOR_MAP_SWIZZLE_128B, CU_TENSOR_MAP_L2_PROMOTION_L2_128B,
                          CU_TENSOR_MAP_FLOAT_OOB_FILL_NONE) == CUDA_SUCCESS;
        }
    for (int b = 0; b < 2; b++) {
        const cuuint64_t dims[3] = {16, kC, b ? 36u : 12u}, strides[2] = {(b ? 3u : 1u) * kPixBytes, 32};
        const cuuint32_t box[3] = {16, b ? 16u : 192u, b ? 12u : 3u};
        ok = ok && fn(b ? &maps->wv : &maps->wo, CU_TENSOR_MAP_DATA_TYPE_BFLOAT16, 3, b ? wqkv : wo, dims, strides, box, estr,
                      CU_TENSOR_MAP_INTERLEAVE_NONE, CU_TENSOR_MAP_SWIZZLE_32B, CU_TENSOR_MAP_L2_PROMOTION_L2_128B,
                      CU_TENSOR_MAP_FLOAT_OOB_FILL_NONE) == CUDA_SUCCESS;
    }
    return ok;
}

}

extern "C" void kernel_launch(void* const* d_in, const int* in_sizes, int n_in, void* d_out, int out_size) {
    static EncodeTiledFn encode = nullptr;
    static Scratch* scratch = nullptr;
    static Tables* tables = nullptr;
    if (!encode) {
        int dev = 0, reserved = 0;
        cudaFuncAttributes attr;
        cudaGetDevice(&dev);
        cudaDeviceGetAttribute(&reserved, cudaDevAttrReservedSharedMemoryPerBlock, dev);
        cudaFuncGetAttributes(&attr, nat_fused_kernel);
        if (reserved != (int)kSmemBase || attr.sharedSizeBytes != 0) return;
        cudaGetSymbolAddress((void**)&scratch, g_scratch);
        cudaGetSymbolAddress((void**)&tables, g_tables);
        void* fn = nullptr;
        cudaDriverEntryPointQueryResult st;
        cudaGetDriverEntryPoint("cuTensorMapEncodeTiled", &fn, cudaEnableDefault, &st);
        encode = (EncodeTiledFn)fn;
        cudaFuncSetAttribute(nat_fused_kernel, cudaFuncAttributeMaxDynamicSharedMemorySize, kSmemBytes);
    }
    Maps maps;
    if (!encode || !make_maps(encode, &maps, d_in[0], d_in[1], d_in[2])) return;
    nat_fused_kernel<<<kGrid, kThreads, kSmemBytes>>>((const uint8_t*)d_in[0], (const uint8_t*)d_in[1], (uint8_t*)d_out, scratch, tables, kDescRing, maps);
}
```

```cpp
#include <cuda_runtime.h>
#include <cuda_bf16.h>
#include <cuda.h>
#include <stdint.h>
#include <type_traits>
#include <stdlib.h>
#include <stddef.h>

#define KEEPFA 1
#define ASLOTS 0x3800
#define BSLOTS 0x6
#define QSLOTS 0x78a
#define OSPLIT 3
#define NAP 40
#define INLOOP 3

namespace {

constexpr int kC          = 192;
constexpr int kHW         = 224;
constexpr int kPixBytes   = kC * 2;
constexpr int kSlotBytes  = 84 * 128;
constexpr int kMidBytes   = 28 * 128;
constexpr int kOffMid     = 88 * 128;
constexpr int kSlotStride = 120 * 128;
constexpr int kRingChunk  = 208 * 128;
constexpr int kWChunk     = 192 * 128;
constexpr int kWBytes     = 3 * kWChunk;
constexpr uint32_t kSmemBase = 1024;
constexpr uint32_t s_ring = kSmemBase, s_m = s_ring + 3 * kRingChunk, s_wv = s_m + kWBytes, s_bar = s_wv + kWBytes;
constexpr uint32_t bar_b = s_bar, bar_img = s_bar + 24, bar_redo = s_bar + 72, bar_wop = s_bar + 96, bar_a = s_bar + 104,
                   bar_ok = s_bar + 112, bar_use = s_bar + 144;
constexpr uint32_t s_par = s_bar + 160, s_late = s_bar + 164, s_tab = s_bar + 256, s_trace = s_tab + 2048;
constexpr int kSmemBytes  = s_trace + 2048 - kSmemBase;
constexpr int kThreads    = 384;
constexpr int kGrid       = 132;
constexpr int kTimeM = 2600, kTimeW = 5100;
constexpr float kScaleLog2e = 0.07216878364870322f * 1.4426950408889634f;

struct Maps {
    CUtensorMap m[4];
    CUtensorMap wo, wv;
    const struct Tables* tables;
};
#define TN(i, dflt) (dflt)
#define START_TIME (wg ? 850 + 500 * order : which ? 650 * order : 550 + 450 * order)

struct Scratch {
    uint8_t img[2][2][kWBytes];
    uint32_t launches;
};
__device__ __align__(1024) Scratch g_scratch;

struct Table {
    uint32_t route[32][4];
    uint32_t u[8][4][4];
    uint32_t v[16][4][4];
};
struct Tables { Table t[2]; };
constexpr Tables make_tables() {
    Tables r = {};
    for (int rev = 0; rev < 2; rev++)
        for (int j = 0; j < 4; j++) {
            Table& t = r.t[rev];
            for (int q = 0; q < 8; q++) {
                uint32_t* e = t.route[4 * q + j];
                e[0] = 4 * q + 2 * (j & 1) + (j >> 1); e[1] = e[0] ^ 1;
                e[2] = j < 2 ? 0x5410u : 0x1054u; e[3] = e[2] + 0x2222u;
                e = t.u[q][j];
                for (int n = 0; n < 7; n++) e[0] |= ((n + j) % 7 < q ? 1u : 0u) << n;
                e[3] = e[0];
                for (int k = 0; k < 2; k++) {
                    const int step = 2 * k + (j >> 1), p0 = (step < 3 ? 16 * step : 40) + 8 * (j & 1);
                    uint32_t m = 0x8888u;
                    for (int n = 0; n < 8; n++) m |= ((p0 + n) % 7 < q ? 1u : 0u) << (2 * n);
                    e[1 + k] = m * 0x10001u;
                }
            }
            for (int sum = 0; sum < 15; sum++) {
                uint32_t* e = t.v[sum][j];
                for (int row = 0; row < 2; row++)
                    for (int b = 0; b < 14; b++) {
                        const int off = (sum + row) / 2, p = 4 * b + j;
                        const uint32_t bit = 1u << (2 * b + row);
                        if (p < 42 && p >= 7 * off) e[rev] |= bit;
                        if (p < 7 * off - 7) e[1 - rev] |= bit;
                        if (p >= 42 && p >= 7 * off && p < 7 * off + 49) e[2] |= bit;
                    }
                for (int n = 0; n < 6; n++)
                    if (8 * n + 2 * j < 42) e[3] |= 1u << (n + ((8 * n + 2 * j >= 7 * (sum / 2 & ~1)) != rev ? 0 : 8));
            }
        }
    return r;
}
__device__ __align__(128) const Tables g_tables = make_tables();

#define WO4(i) "=f"(d[i]), "=f"(d[i + 1]), "=f"(d[i + 2]), "=f"(d[i + 3])
#define RW4(i) "+f"(d[i]), "+f"(d[i + 1]), "+f"(d[i + 2]), "+f"(d[i + 3])

template <bool FIRST>
__device__ __forceinline__ void wgmma_n192(float (&d)[96], uint32_t a0, uint32_t a1, uint32_t a2, uint32_t a3, uint64_t descb) {
    if constexpr (FIRST) {
        asm volatile(
            "wgmma.mma_async.sync.aligned.m64n192k16.f32.bf16.bf16 "
            "{%0, %1, %2, %3, %4, %5, %6, %7, %8, %9, %10, %11, %12, %13, %14, %15, %16, %17, %18, %19, %20, %21, %22, %23, "
            "%24, %25, %26, %27, %28, %29, %30, %31, %32, %33, %34, %35, %36, %37, %38, %39, %40, %41, %42, %43, %44, %45, %46, %47, "
            "%48, %49, %50, %51, %52, %53, %54, %55, %56, %57, %58, %59, %60, %61, %62, %63, %64, %65, %66, %67, %68, %69, %70, %71, "
            "%72, %73, %74, %75, %76, %77, %78, %79, %80, %81, %82, %83, %84, %85, %86, %87, %88, %89, %90, %91, %92, %93, %94, %95}, "
            "{%96, %97, %98, %99}, %100, 0, 1, 1, 0;"
            : WO4(0), WO4(4), WO4(8), WO4(12), WO4(16), WO4(20), WO4(24), WO4(28), WO4(32), WO4(36), WO4(40), WO4(44),
              WO4(48), WO4(52), WO4(56), WO4(60), WO4(64), WO4(68), WO4(72), WO4(76), WO4(80), WO4(84), WO4(88), WO4(92)
            : "r"(a0), "r"(a1), "r"(a2), "r"(a3), "l"(descb));
    } else {
        asm volatile(
            "wgmma.mma_async.sync.aligned.m64n192k16.f32.bf16.bf16 "
            "{%0, %1, %2, %3, %4, %5, %6, %7, %8, %9, %10, %11, %12, %13, %14, %15, %16, %17, %18, %19, %20, %21, %22, %23, "
            "%24, %25, %26, %27, %28, %29, %30, %31, %32, %33, %34, %35, %36, %37, %38, %39, %40, %41, %42, %43, %44, %45, %46, %47, "
            "%48, %49, %50, %51, %52, %53, %54, %55, %56, %57, %58, %59, %60, %61, %62, %63, %64, %65, %66, %67, %68, %69, %70, %71, "
            "%72, %73, %74, %75, %76, %77, %78, %79, %80, %81, %82, %83, %84, %85, %86, %87, %88, %89, %90, %91, %92, %93, %94, %95}, "
            "{%96, %97, %98, %99}, %100, 1, 1, 1, 0;"
            : RW4(0), RW4(4), RW4(8), RW4(12), RW4(16), RW4(20), RW4(24), RW4(28), RW4(32), RW4(36), RW4(40), RW4(44),
              RW4(48), RW4(52), RW4(56), RW4(60), RW4(64), RW4(68), RW4(72), RW4(76), RW4(80), RW4(84), RW4(88), RW4(92)
            : "r"(a0), "r"(a1), "r"(a2), "r"(a3), "l"(descb));
    }
}

template <bool FIRST>
__device__ __forceinline__ void wgmma_n88(float (&d)[44], uint32_t a0, uint32_t a1, uint32_t a2, uint32_t a3, uint64_t descb) {
    if constexpr (FIRST) {
        asm volatile(
            "wgmma.mma_async.sync.aligned.m64n88k16.f32.bf16.bf16 "
            "{%0, %1, %2, %3, %4, %5, %6, %7, %8, %9, %10, %11, %12, %13, %14, %15, %16, %17, %18, %19, %20, %21, %22, %23, "
            "%24, %25, %26, %27, %28, %29, %30, %31, %32, %33, %34, %35, %36, %37, %38, %39, %40, %41, %42, %43}, "
            "{%44, %45, %46, %47}, %48, 0, 1, 1, 0;"
            : WO4(0), WO4(4), WO4(8), WO4(12), WO4(16), WO4(20), WO4(24), WO4(28), WO4(32), WO4(36), WO4(40)
            : "r"(a0), "r"(a1), "r"(a2), "r"(a3), "l"(descb));
    } else {
        asm volatile(
            "wgmma.mma_async.sync.aligned.m64n88k16.f32.bf16.bf16 "
            "{%0, %1, %2, %3, %4, %5, %6, %7, %8, %9, %10, %11, %12, %13, %14, %15, %16, %17, %18, %19, %20, %21, %22, %23, "
            "%24, %25, %26, %27, %28, %29, %30, %31, %32, %33, %34, %35, %36, %37, %38, %39, %40, %41, %42, %43}, "
            "{%44, %45, %46, %47}, %48, 1, 1, 1, 0;"
            : RW4(0), RW4(4), RW4(8), RW4(12), RW4(16), RW4(20), RW4(24), RW4(28), RW4(32), RW4(36), RW4(40)
            : "r"(a0), "r"(a1), "r"(a2), "r"(a3), "l"(descb));
    }
}

template <bool FIRST>
__device__ __forceinline__ void wgmma_n32(float (&d)[16], uint32_t a0, uint32_t a1, uint32_t a2, uint32_t a3, uint64_t descb) {
    if constexpr (FIRST) {
        asm volatile(
            "wgmma.mma_async.sync.aligned.m64n32k16.f32.bf16.bf16 "
            "{%0, %1, %2, %3, %4, %5, %6, %7, %8, %9, %10, %11, %12, %13, %14, %15}, "
            "{%16, %17, %18, %19}, %20, 0, 1, 1, 0;"
            : WO4(0), WO4(4), WO4(8), WO4(12)
            : "r"(a0), "r"(a1), "r"(a2), "r"(a3), "l"(descb));
    } else {
        asm volatile(
            "wgmma.mma_async.sync.aligned.m64n32k16.f32.bf16.bf16 "
            "{%0, %1, %2, %3, %4, %5, %6, %7, %8, %9, %10, %11, %12, %13, %14, %15}, "
            "{%16, %17, %18, %19}, %20, 1, 1, 1, 0;"
            : RW4(0), RW4(4), RW4(8), RW4(12)
            : "r"(a0), "r"(a1), "r"(a2), "r"(a3), "l"(descb));
    }
}

template <bool FIRST, int SEL>
__device__ __forceinline__ void wgmma_sp_n192_tb(float (&d)[96], uint32_t a0, uint32_t a1, uint32_t a2, uint32_t a3, uint64_t descb, uint32_t meta) {
    if constexpr (FIRST) {
        asm volatile(
            "wgmma.mma_async.sp.sync.aligned.m64n192k32.f32.bf16.bf16 "
            "{%0, %1, %2, %3, %4, %5, %6, %7, %8, %9, %10, %11, %12, %13, %14, %15, %16, %17, %18, %19, %20, %21, %22, %23, "
            "%24, %25, %26, %27, %28, %29, %30, %31, %32, %33, %34, %35, %36, %37, %38, %39, %40, %41, %42, %43, %44, %45, %46, %47, "
            "%48, %49, %50, %51, %52, %53, %54, %55, %56, %57, %58, %59, %60, %61, %62, %63, %64, %65, %66, %67, %68, %69, %70, %71, "
            "%72, %73, %74, %75, %76, %77, %78, %79, %80, %81, %82, %83, %84, %85, %86, %87, %88, %89, %90, %91, %92, %93, %94, %95}, "
            "{%96, %97, %98, %99}, %100, %101, %102, 0, 1, 1, 1;"
            : WO4(0), WO4(4), WO4(8), WO4(12), WO4(16), WO4(20), WO4(24), WO4(28), WO4(32), WO4(36), WO4(40), WO4(44),
              WO4(48), WO4(52), WO4(56), WO4(60), WO4(64), WO4(68), WO4(72), WO4(76), WO4(80), WO4(84), WO4(88), WO4(92)
            : "r"(a0), "r"(a1), "r"(a2), "r"(a3), "l"(descb), "r"(meta), "n"(SEL));
    } else {
        asm volatile(
            "wgmma.mma_async.sp.sync.aligned.m64n192k32.f32.bf16.bf16 "
            "{%0, %1, %2, %3, %4, %5, %6, %7, %8, %9, %10, %11, %12, %13, %14, %15, %16, %17, %18, %19, %20, %21, %22, %23, "
            "%24, %25, %26, %27, %28, %29, %30, %31, %32, %33, %34, %35, %36, %37, %38, %39, %40, %41, %42, %43, %44, %45, %46, %47, "
            "%48, %49, %50, %51, %52, %53, %54, %55, %56, %57, %58, %59, %60, %61, %62, %63, %64, %65, %66, %67, %68, %69, %70, %71, "
            "%72, %73, %74, %75, %76, %77, %78, %79, %80, %81, %82, %83, %84, %85, %86, %87, %88, %89, %90, %91, %92, %93, %94, %95}, "
            "{%96, %97, %98, %99}, %100, %101, %102, 1, 1, 1, 1;"
            : RW4(0), RW4(4), RW4(8), RW4(12), RW4(16), RW4(20), RW4(24), RW4(28), RW4(32), RW4(36), RW4(40), RW4(44),
              RW4(48), RW4(52), RW4(56), RW4(60), RW4(64), RW4(68), RW4(72), RW4(76), RW4(80), RW4(84), RW4(88), RW4(92)
            : "r"(a0), "r"(a1), "r"(a2), "r"(a3), "l"(descb), "r"(meta), "n"(SEL));
    }
}

#define TR(slot)
#define TRX(slot)
#define TRE(slot)
#define TRT(slot)
#define TRF(slot)
#define TRW(slot)
#define TRG(slot)
#define TRDUMP()

__device__ __forceinline__ void wg_fence() { asm volatile("wgmma.fence.sync.aligned;" ::: "memory"); }
__device__ __forceinline__ void wg_commit() { asm volatile("wgmma.commit_group.sync.aligned;" ::: "memory"); }
template <int N>
__device__ __forceinline__ void wg_wait() { asm volatile("wgmma.wait_group.sync.aligned %0;" ::"n"(N) : "memory"); }

template <int N>
__device__ __forceinline__ void pin(float (&d)[N]) {
#pragma unroll
    for (int i = 0; i < N; i++) asm volatile("" : "+f"(d[i])::"memory");
}
template <int N>
__device__ __forceinline__ void pin(uint32_t (&d)[N]) {
#pragma unroll
    for (int i = 0; i < N; i++) asm volatile("" : "+r"(d[i])::"memory");
}

constexpr uint64_t kDescRing = ((uint64_t)((1u << 30) | (1024u >> 4)) << 32) | (1u << 16) | (s_ring >> 4);
constexpr uint32_t kToV = ((kRingChunk >> 4) - 1) << 20;
__device__ __forceinline__ uint64_t desc_at(uint64_t base, uint32_t byte_off) {
    uint64_t d;
    asm volatile("add.s64 %0, %1, %2;" : "=l"(d) : "l"(base), "l"((uint64_t)(byte_off >> 4)));
    return d;
}

__device__ __forceinline__ void mbar_init(uint32_t bar, uint32_t count) {
    asm volatile("mbarrier.init.shared::cta.b64 [%0], %1;" ::"r"(bar), "r"(count) : "memory");
}
__device__ __forceinline__ void mbar_expect_tx(uint32_t bar, uint32_t bytes) {
    asm volatile("mbarrier.arrive.expect_tx.shared::cta.b64 _, [%0], %1;" ::"r"(bar), "r"(bytes) : "memory");
}
__device__ __forceinline__ void expect_tx_only(uint32_t bar, uint32_t bytes) {
    asm volatile("mbarrier.expect_tx.relaxed.cta.shared::cta.b64 [%0], %1;" ::"r"(bar), "r"(bytes) : "memory");
}
__device__ __forceinline__ void mbar_arrive(uint32_t bar) {
    asm volatile("mbarrier.arrive.shared::cta.b64 _, [%0];" ::"r"(bar) : "memory");
}
__device__ __forceinline__ void mbar_wait(uint32_t bar, uint32_t parity) {
    asm volatile(
        "{\n.reg .pred p;\n"
        "W: mbarrier.try_wait.parity.shared::cta.b64 p, [%0], %1;\n"
        "@!p bra W;\n}\n"
        ::"r"(bar), "r"(parity) : "memory");
}
__device__ __forceinline__ uint32_t clock_now() {
    uint32_t c;
    asm volatile("mov.u32 %0, %%clock;" : "=r"(c)::"memory");
    return c;
}
__device__ __forceinline__ void wait_until(uint32_t t0, int t) {
    if (t == 0) return;
    while ((int)(clock_now() - t0) < t) {}
}
__device__ __forceinline__ bool elect() {
    uint32_t ok;
    asm volatile("{\n.reg .pred p;\nelect.sync _|p, 0xffffffff;\nselp.u32 %0, 1, 0, p;\n}\n" : "=r"(ok));
    return ok != 0;
}
__device__ __forceinline__ void turn_wait(int wg) { asm volatile("bar.sync %0, 256;" ::"r"(1 + wg) : "memory"); }
__device__ __forceinline__ void turn_pass(int wg) { asm volatile("bar.arrive %0, 256;" ::"r"(2 - wg) : "memory"); }

__device__ __forceinline__ void tma_box(uint32_t dst, const CUtensorMap* map, uint32_t bar, int c0, int c2, int c3, int c4) {
    asm volatile(
        "cp.async.bulk.tensor.5d.shared::cluster.global.mbarrier::complete_tx::bytes [%0], [%1, {%3, %4, %5, %6, %7}], [%2];"
        ::"r"(dst), "l"(map), "r"(bar), "r"(c0), "r"(0), "r"(c2), "r"(c3), "r"(c4)
        : "memory");
}
__device__ __forceinline__ void tma_3d(uint32_t dst, const CUtensorMap* map, uint32_t bar, int c1, int c2) {
    asm volatile("cp.async.bulk.tensor.3d.shared::cluster.global.mbarrier::complete_tx::bytes [%0], [%1, {%3, %4, %5}], [%2];"
                 ::"r"(dst), "l"(map), "r"(bar), "r"(0), "r"(c1), "r"(c2)
                 : "memory");
}
__device__ __forceinline__ void tma_prefetch(const CUtensorMap* map, int c0, int c2, int c3, int c4) {
    asm volatile("cp.async.bulk.prefetch.tensor.5d.L2.global [%0, {%1, %2, %3, %4, %5}];"
                 ::"l"(map), "r"(c0), "r"(0), "r"(c2), "r"(c3), "r"(c4)
                 : "memory");
}
__device__ __forceinline__ void prefetch_map(const CUtensorMap* map) {
    asm volatile("prefetch.tensormap [%0];" ::"l"(map) : "memory");
}
__device__ __forceinline__ uint4 ldg(const void* p) {
    uint4 v;
    asm volatile("ld.global.v4.u32 {%0, %1, %2, %3}, [%4];" : "=r"(v.x), "=r"(v.y), "=r"(v.z), "=r"(v.w) : "l"(p) : "memory");
    return v;
}
__device__ __forceinline__ uint32_t pack_bf16(float lo, float hi) {
    uint32_t r;
    asm("cvt.rn.bf16x2.f32 %0, %1, %2;" : "=r"(r) : "f"(hi), "f"(lo));
    return r;
}
__device__ __forceinline__ float ex2(float x) {
    float y;
    asm("ex2.approx.ftz.f32 %0, %1;" : "=f"(y) : "f"(x));
    return y;
}
__device__ __forceinline__ float rcp(float x) {
    float y;
    asm("rcp.approx.ftz.f32 %0, %1;" : "=f"(y) : "f"(x));
    return y;
}
__device__ __forceinline__ void mma16816(float (&d)[4], uint32_t a0, uint32_t a1, uint32_t a2, uint32_t a3, uint32_t b0, uint32_t b1) {
    asm volatile("mma.sync.aligned.m16n8k16.row.col.f32.bf16.bf16.f32 {%0, %1, %2, %3}, {%4, %5, %6, %7}, {%8, %9}, {%0, %1, %2, %3};"
                 : "+f"(d[0]), "+f"(d[1]), "+f"(d[2]), "+f"(d[3])
                 : "r"(a0), "r"(a1), "r"(a2), "r"(a3), "r"(b0), "r"(b1));
}
__device__ __forceinline__ uint4 lds128(uint32_t addr) {
    uint4 v;
    asm volatile("ld.volatile.shared.v4.u32 {%0, %1, %2, %3}, [%4];" : "=r"(v.x), "=r"(v.y), "=r"(v.z), "=r"(v.w) : "r"(addr) : "memory");
    return v;
}
__device__ __forceinline__ uint32_t lds_volatile(uint32_t addr) {
    uint32_t v;
    asm volatile("ld.volatile.shared.u32 %0, [%1];" : "=r"(v) : "r"(addr) : "memory");
    return v;
}

__device__ __forceinline__ int window_start(int n) { return min(max(n, 0), 105); }
__device__ __forceinline__ int origin_u(int u) { return min(max(u, 0), 98); }

struct Work {
    int u, v;
    int step;
    uint32_t su, sv;
    uint32_t base;
    bool corner;
    int ntiles;
    __device__ __forceinline__ void pixel_offsets(int qu, int qv, int j, uint32_t& o0, uint32_t& o1) const {
        const uint32_t b = (qu + window_start(qu)) * su + j * 16 + base;
        o0 = b + (qv + window_start(qv)) * sv;
        o1 = b + (qv + 1 + window_start(qv + 1)) * sv;
    }
};

__device__ __forceinline__ Work decode_work(int c) {
    Work w;
    const bool transposed = (c >> 4) == 7;
    const int px = 6 * (c & 1), py = 3 * (c & 2);
    w.corner = c >= 128;
    w.step = 8 - 4 * (c & 4);
    w.u = (c < 112 ? c & ~7 : 96 + (c & 8)) + (transposed ? py : px) - 6;
    w.v = (w.corner ? 96 : 48 - 2 * (c & 4)) + (transposed ? px : py) - 6;
    w.su = transposed ? kHW * kPixBytes : kPixBytes;
    w.sv = transposed ? kPixBytes : kHW * kPixBytes;
    w.base = px * (kPixBytes / 6) + py * (kHW * kPixBytes / 6) + 6 * (kHW + 1) * kPixBytes;
    w.ntiles = w.corner ? 4 : 6;
    return w;
}

struct RawX { uint4 a[6], b[6]; };
__device__ __forceinline__ void load_raw(RawX& r, const uint8_t* base, uint32_t o0, uint32_t o1) {
    __syncwarp();
#pragma unroll
    for (int c = 0; c < 6; c++) { r.a[c] = ldg(base + o0 + c * 64); r.b[c] = ldg(base + o1 + c * 64); }
    __syncwarp();
}
__device__ __forceinline__ void raw_to_frags(const RawX& r, uint32_t zero, uint32_t (&f)[48]) {
#pragma unroll
    for (int c = 0; c < 6; c++) {
        asm volatile("{\n.reg .b32 t, u;\nadd.u32 t, %4, %8;\nadd.u32 u, %5, %8;\nxor.b32 %0, %6, %8;\nxor.b32 %1, %7, %8;\n"
                     "xor.b32 %2, t, %8;\nxor.b32 %3, u, %8;\n}\n"
                     : "=&r"(f[8 * c + 1]), "=&r"(f[8 * c + 3]), "=&r"(f[8 * c + 4]), "=&r"(f[8 * c + 6])
                     : "r"(r.a[c].y), "r"(r.a[c].w), "r"(r.b[c].x), "r"(r.b[c].z), "r"(zero));
        f[8 * c + 0] = r.a[c].x; f[8 * c + 2] = r.a[c].z; f[8 * c + 5] = r.b[c].y; f[8 * c + 7] = r.b[c].w;
    }
}
__device__ __forceinline__ void acc_to_frags(const float (&d)[96], uint32_t (&f)[48]) {
#pragma unroll
    for (int i = 0; i < 48; i++) f[i] = pack_bf16(d[2 * i], d[2 * i + 1]);
}

template <class F>
__device__ __forceinline__ void proj_gemm(float (&d)[96], const uint32_t (&a)[48], uint64_t dsc, uint32_t img, F after) {
#pragma unroll
    for (int s = 0; s < 12; s++) {
        if (s == 0) wgmma_n192<true>(d, a[4 * s], a[4 * s + 1], a[4 * s + 2], a[4 * s + 3], desc_at(dsc, img - s_ring + (s >> 2) * kWChunk + (s & 3) * 32));
        else wgmma_n192<false>(d, a[4 * s], a[4 * s + 1], a[4 * s + 2], a[4 * s + 3], desc_at(dsc, img - s_ring + (s >> 2) * kWChunk + (s & 3) * 32));
        if (s == 11) wg_commit();
        after(s);
    }
}
__device__ __forceinline__ void pack_out(const float (&acc)[96], uint32_t (&po)[48]) {
#pragma unroll
    for (int g = 0; g < 6; g++)
#pragma unroll
        for (int q = 0; q < 4; q++) {
            po[8 * g + q] = pack_bf16(acc[16 * g + 4 * q], acc[16 * g + 4 * q + 1]);
            po[8 * g + 4 + q] = pack_bf16(acc[16 * g + 4 * q + 2], acc[16 * g + 4 * q + 3]);
        }
}
template <bool PINNED = true>
__device__ __forceinline__ void store_one(bool on, uint8_t* p0, uint8_t* p1, const uint32_t (&po)[48], int n) {
    if (PINNED) __syncwarp();
    asm volatile("{\n.reg .pred p;\nsetp.ne.u32 p, %5, 0;\n@p st.global.v4.u32 [%0], {%1, %2, %3, %4};\n}\n"
                 ::"l"(((n & 1) ? p1 : p0) + (n >> 1) * 64), "r"(po[4 * n]), "r"(po[4 * n + 1]), "r"(po[4 * n + 2]), "r"(po[4 * n + 3]), "r"((uint32_t)on) : "memory");
}

template <int N>
__device__ __forceinline__ float tree_max(const float (&v)[N]) {
    float t[N];
#pragma unroll
    for (int i = 0; i < N; i++) t[i] = v[i];
#pragma unroll
    for (int w = 1; w < N; w *= 2)
#pragma unroll
        for (int i = 0; i + w < N; i += 2 * w) t[i] = fmaxf(t[i], t[i + w]);
    return t[0];
}
template <int N>
__device__ __forceinline__ float tree_sum(const float (&v)[N]) {
    float t[N];
#pragma unroll
    for (int i = 0; i < N; i++) t[i] = v[i];
#pragma unroll
    for (int w = 1; w < N; w *= 2)
#pragma unroll
        for (int i = 0; i + w < N; i += 2 * w) t[i] += t[i + w];
    return t[0];
}

template <int B>
__device__ __forceinline__ void pick(uint32_t h, uint32_t ok, const float* s, float& v0, float& v1) {
    asm("{\n.reg .pred p, q0, q1;\n.reg .b32 t;\nand.b32 t, %6, %7;\nsetp.ne.u32 p, t, 0;\n"
        "and.b32 t, %8, %9;\nsetp.ne.u32 q0, t, 0;\nand.b32 t, %8, %10;\nsetp.ne.u32 q1, t, 0;\n"
        "@q0 selp.f32 %0, %3, %2, p;\n@q1 selp.f32 %1, %5, %4, p;\n}\n"
        : "+f"(v0), "+f"(v1)
        : "f"(s[0]), "f"(s[1]), "f"(s[2]), "f"(s[3]), "r"(h), "n"(1 << ((4 * B) % 7)), "r"(ok), "n"(1 << (2 * B)), "n"(2 << (2 * B)));
}
template <int B, class F>
__device__ __forceinline__ void for_blocks(F f) {
    if constexpr (B > 0) { for_blocks<B - 1>(f); f(std::integral_constant<int, B - 1>{}); }
}
__device__ __forceinline__ void gather_outer(const float (&s)[44], uint32_t h, uint32_t ok, float (&v0)[14], float (&v1)[14]) {
    for_blocks<11>([&](auto B) {
        constexpr int b = B.value < 8 ? (B.value >> 1) + 7 * (B.value & 1) : B.value - 4;
        pick<b>(h, ok, &s[4 * b], v0[b], v1[b]);
    });
}
__device__ __forceinline__ void gather_mid(const float (&sE)[16], uint32_t h, uint32_t ok, float (&v0)[14], float (&v1)[14]) {
    for_blocks<4>([&](auto B) { pick<10 + B.value>(h, ok, &sE[4 * B.value], v0[10 + B.value], v1[10 + B.value]); });
}
__device__ __forceinline__ float quad_max(float m) {
    m = fmaxf(m, __shfl_xor_sync(0xffffffffu, m, 1));
    return fmaxf(m, __shfl_xor_sync(0xffffffffu, m, 2));
}
__device__ __forceinline__ float quad_sum(float s) {
    s += __shfl_xor_sync(0xffffffffu, s, 1);
    return s + __shfl_xor_sync(0xffffffffu, s, 2);
}
template <int B0, int B1>
__device__ __forceinline__ void exp_route(float (&v0)[14], float (&v1)[14], float m0, float m1, const uint4& r, bool even, uint32_t (&y)[14]) {
#pragma unroll
    for (int b = B0; b < B1; b++) { v0[b] = ex2(v0[b] - m0); v1[b] = ex2(v1[b] - m1); }
#pragma unroll
    for (int b = B0; b < B1; b += 2) {
        const uint32_t x0 = pack_bf16(v0[b], v1[b]), x1 = pack_bf16(v0[b + 1], v1[b + 1]);
        const uint32_t u = __shfl_sync(0xffffffffu, even ? x0 : x1, r.x);
        const uint32_t w = __shfl_sync(0xffffffffu, even ? x1 : x0, r.y);
        y[b] = __byte_perm(u, w, r.z); y[b + 1] = __byte_perm(u, w, r.w);
    }
}
template <int BIT0, int N0, int N1>
__device__ __forceinline__ void unfold(const uint32_t (&y)[14], uint32_t fold, uint32_t (&p)[12]) {
    for_blocks<N1 - N0>([&](auto N) {
        constexpr int n = N0 + N.value;
        asm("{\n.reg .pred p;\n.reg .b32 t;\nand.b32 t, %4, %5;\nsetp.ne.u32 p, t, 0;\nselp.b32 %0, %2, 0, p;\nselp.b32 %1, %3, 0, p;\n}\n"
            : "=r"(p[2 * n]), "=r"(p[2 * n + 1]) : "r"(y[2 * n]), "r"(y[2 * n + 1]), "r"(fold), "n"(1 << (BIT0 + n)));
    });
}
__device__ __forceinline__ void keep(bool never, uint32_t a, uint32_t b, uint32_t c, uint32_t d) {
    asm volatile("{\n.reg .pred p;\nsetp.ne.u32 p, %4, 0;\n@p st.volatile.shared.v4.u32 [%5], {%0, %1, %2, %3};\n}\n"
                 ::"r"(a), "r"(b), "r"(c), "r"(d), "r"((uint32_t)never), "r"(s_trace) : "memory");
}

__device__ __forceinline__ uint32_t wimg_offset(uint32_t row, uint32_t s, uint32_t j) {
    return (s >> 2) * kWChunk + row * 128 + (((2 * (s & 3) + (j >> 1)) ^ (row & 7)) << 4) + (j & 1) * 8;
}

__device__ __forceinline__ void ldsm4(uint32_t (&r)[4], uint32_t addr) {
    asm volatile("ldmatrix.sync.aligned.m8n8.x4.shared.b16 {%0, %1, %2, %3}, [%4];" : "=r"(r[0]), "=r"(r[1]), "=r"(r[2]), "=r"(r[3]) : "r"(addr) : "memory");
}
__device__ __forceinline__ void ldsm4_t(uint32_t (&r)[4], uint32_t addr) {
    asm volatile("ldmatrix.sync.aligned.m8n8.x4.trans.shared.b16 {%0, %1, %2, %3}, [%4];" : "=r"(r[0]), "=r"(r[1]), "=r"(r[2]), "=r"(r[3]) : "r"(addr) : "memory");
}
__device__ __forceinline__ void m_partial(const uint8_t* wqkv, uint32_t mt, uint32_t s, uint32_t q, uint32_t lane, uint32_t zero) {
    const uint32_t r8 = lane >> 2, col = q * 128 + (lane & 3) * 16;
    const uint8_t* pa = wqkv + (16 * mt + r8) * 1152 + col;
    const uint8_t* pb = wqkv + (16 * s + 8 * (r8 & 2) + (r8 & 5)) * 1152 + col;
    uint4 A[2][2], B[4][2];
#pragma unroll
    for (int c = 0; c < 2; c++) {
#pragma unroll
        for (int h = 0; h < 2; h++) A[h][c] = ldg(pa + 384 + h * 8 * 1152 + c * 64);
#pragma unroll
        for (int n = 0; n < 4; n++) B[n][c] = ldg(pb + ((n & 1) * 8 + (n & 2)) * 1152 + c * 64);
    }
#pragma unroll
    for (int i = 0; i < 4; i++) { uint4& a = A[i >> 1][i & 1]; a.x ^= zero; a.y ^= zero; a.z ^= zero; a.w ^= zero; }
#pragma unroll
    for (int n = 0; n < 4; n++) {
        float d[4] = {0.f, 0.f, 0.f, 0.f};
#pragma unroll
        for (int c = 0; c < 2; c++) {
            mma16816(d, A[0][c].x, A[1][c].x, A[0][c].y, A[1][c].y, B[n][c].x, B[n][c].y);
            mma16816(d, A[0][c].z, A[1][c].z, A[0][c].w, A[1][c].w, B[n][c].z, B[n][c].w);
        }
        asm volatile("st.shared.v4.f32 [%0], {%1, %2, %3, %4};" ::"r"(s_wv + q * 2048 + n * 512 + lane * 16), "f"(d[0]), "f"(d[1]), "f"(d[2]), "f"(d[3]) : "memory");
    }
}
__device__ __forceinline__ void m_reduce(uint32_t e, uint32_t lane, float (&d)[2][4]) {
#pragma unroll
    for (int n = 0; n < 2; n++) {
        float t[3][4];
#pragma unroll
        for (int q = 0; q < 3; q++)
            asm volatile("ld.shared.v4.f32 {%0, %1, %2, %3}, [%4];" : "=f"(t[q][0]), "=f"(t[q][1]), "=f"(t[q][2]), "=f"(t[q][3]) : "r"(s_wv + q * 2048 + e * 1024 + n * 512 + lane * 16) : "memory");
#pragma unroll
        for (int i = 0; i < 4; i++) d[n][i] = (t[0][i] + t[1][i] + t[2][i]) * kScaleLog2e;
    }
}
__device__ __forceinline__ void w_piece(uint32_t q, uint32_t lane, float (&d)[2][4]) {
    const uint32_t rr = lane & 7, mi = lane >> 3, kr = 4 * (rr >> 1) + (mi & 2) + (rr & 1);
    const uint32_t pa = s_wv + q * 32 + (4 * (mi & 2) + rr) * 96 + ((mi & 1) << 4);
    const uint32_t pb = s_wv + 3 * 6144 + kr * 128 + (((mi & 1) ^ (kr & 7)) << 4);
    float e[2][4];
#pragma unroll
    for (int i = 0; i < 8; i++) (&d[0][0])[i] = (&e[0][0])[i] = 0.f;
#pragma unroll
    for (int k = 0; k < 12; k++) {
        uint32_t aq[4], bq[4];
        ldsm4_t(aq, pa + k * 1536);
        ldsm4(bq, (pb ^ ((k & 3) << 5)) + (k >> 2) * 2048);
        mma16816(k & 1 ? e[0] : d[0], aq[0], aq[1], aq[2], aq[3], bq[0], bq[1]);
        mma16816(k & 1 ? e[1] : d[1], aq[0], aq[1], aq[2], aq[3], bq[2], bq[3]);
    }
#pragma unroll
    for (int i = 0; i < 8; i++) (&d[0][0])[i] += (&e[0][0])[i];
}
__device__ __forceinline__ uint32_t piece_offset(uint32_t which, uint32_t s, uint32_t mt, uint32_t lane) {
    const uint32_t r8 = lane >> 2;
    return which * kWBytes + wimg_offset(which ? 32 * (mt >> 1) + 8 * (r8 >> 1) + 4 * (mt & 1) + (r8 & 1) : 16 * mt + r8, s, lane & 3);
}
__device__ __forceinline__ void piece_store(Scratch* g, uint32_t par, uint32_t off0, uint32_t which, const float (&d)[2][4]) {
#pragma unroll
    for (int hf = 0; hf < 2; hf++) {
        const uint32_t off = off0 ^ (hf ? which ? 288 : 1024 : 0);
        const uint32_t a = pack_bf16(d[0][2 * hf], d[0][2 * hf + 1]), b = pack_bf16(d[1][2 * hf], d[1][2 * hf + 1]);
        asm volatile("st.relaxed.gpu.global.v2.u32 [%0], {%1, %2};" ::"l"(g->img[0][0] + (par + off)), "r"(a ? a : 0x8000u), "r"(b) : "memory");
    }
}
__device__ __forceinline__ void piece_clear(Scratch* g, uint32_t par, uint32_t off0, uint32_t which) {
#pragma unroll
    for (int hf = 0; hf < 2; hf++)
        asm volatile("st.relaxed.gpu.global.v2.u32 [%0], {%1, %1};" ::"l"(g->img[0][0] + (par + (off0 ^ (hf ? which ? 288 : 1024 : 0)))), "r"(0) : "memory");
}

__device__ __forceinline__ uint32_t ld_relaxed(const uint32_t* p) {
    uint32_t v;
    asm volatile("ld.relaxed.gpu.global.u32 %0, [%1];" : "=r"(v) : "l"(p) : "memory");
    return v;
}
__device__ __forceinline__ void count_up(uint32_t* p) {
    asm volatile("red.relaxed.gpu.global.add.u32 [%0], %1;" ::"l"(p), "r"(1) : "memory");
}
__device__ __forceinline__ void bulk_g2s(uint32_t dst, const void* src, uint32_t bytes, uint32_t bar) {
    asm volatile("cp.async.bulk.shared::cluster.global.mbarrier::complete_tx::bytes [%0], [%1], %2, [%3];"
                 ::"r"(dst), "l"(src), "r"(bytes), "r"(bar)
                 : "memory");
}

__global__ void __launch_bounds__(kThreads, 1)
nat_fused_kernel(const uint8_t* __restrict__ x, const uint8_t* __restrict__ wqkv, uint8_t* __restrict__ out, Scratch* g,
                 const uint8_t* wo, uint64_t dsc, const __grid_constant__ Maps maps) {
    const int tid = threadIdx.x, lane = tid & 31;
    const int warp = __shfl_sync(0xffffffffu, tid >> 5, 0);
    const int wg = warp >> 2, wq = warp & 3, r8 = lane >> 2, j = lane & 3;
    const int cta = blockIdx.x;
    const Work w = decode_work(cta);
    const uint32_t jq = (cta < 124 ? cta + 8 : cta - 124) / 11u, jr = (cta < 124 ? cta + 8 : cta - 124) - 11 * jq;
    const uint32_t which = jr >= 6, jhi = which ? jr - 6 : jq, jlo = which ? jq : 2 * jr;
    const bool has_job = jr < 10;
    if (wg == 2 && wq < 3) {
#pragma unroll
        for (int r = 0; r < 3; r++)
            asm volatile("st.shared.v4.u32 [%0], {%1, %1, %1, %1};" ::"r"(s_ring + wq * kRingChunk + (r == 0 ? 84 : r == 1 ? 88 : 204) * 128 + lane * 16), "r"(0) : "memory");
        asm volatile("fence.proxy.async.shared::cta;" ::: "memory");
    }
    if (x == nullptr) return;
    const uint32_t t_start = clock_now();
    if (wg == 2) {
        asm volatile("setmaxnreg.dec.sync.aligned.u32 24;");
        if (wq < 3) {
            if (lane < 3 && cta < 128) {
                const uint32_t row = 3 * (cta >> 1) + wq;
                asm volatile("prefetch.global.L2 [%0];" ::"l"((cta & 1 ? wo + row * 384 : wqkv + row * 1152 + 768) + lane * 128));
            }
            asm volatile("bar.sync 7, 192;" ::: "memory");
            const uint32_t par = lds_volatile(s_par);
            uint32_t phase = 0;
#pragma unroll 1
            for (uint32_t c = 0; c < 6; c++) {
                const uint32_t part = c * kWChunk + wq * (kWChunk / 3), img = 8 * min(c, 3u);
                mbar_wait(bar_img + 8 * c, 0);
                if (wq == 0) TRW(10 + c);
#pragma unroll 1
                while (true) {
                    uint32_t lo = ~0u;
#pragma unroll
                    for (int q = 0; q < 8; q++) lo = min(lo, lds_volatile(s_m + part + lane * 32 + (lane & 12) * 2 + q * 1024));
                    if (__all_sync(0xffffffffu, lo) || phase > 65535) break;
                    if (elect()) {
                        mbar_expect_tx(bar_redo + 8 * wq, kWChunk / 3);
                        bulk_g2s(s_m + part, g->img[0][0] + par + part, kWChunk / 3, bar_redo + 8 * wq);
                    }
                    mbar_wait(bar_redo + 8 * wq, phase++ & 1);
                }
                if (c != 3 && c != 4 && lane == 0) mbar_arrive(bar_ok + img);
            }
        } else {
            uint32_t launch = ld_relaxed(&g->launches);
            const CUtensorMap* map = &maps.m[w.sv == kPixBytes ? 2 : 0];
            if (elect()) {
#pragma unroll
                for (int i = 0; i < 20; i++) mbar_init(s_bar + 8 * i, i < 13 ? 1 : i < 18 ? 3 : 4);
                asm volatile("fence.mbarrier_init.release.cluster;" ::: "memory");
                prefetch_map(map + 1);
                expect_tx_only(bar_a, sizeof(Table));
                bulk_g2s(s_tab, &maps.tables->t[w.step < 0], sizeof(Table), bar_a);
            }
            if (which && has_job && elect()) {
                mbar_expect_tx(bar_wop, 4 * 6144);
                tma_3d(s_wv, &maps.wo, bar_wop, 0, jhi);
                tma_3d(s_wv + 3 * 6144, &maps.wv, bar_wop, 16 * jlo, 6);
            }
            int u = w.u, v = w.v;
            uint32_t wait_bar = bar_use, wait_par = 1, slot = 0;
#pragma unroll 1
            for (int step = 0; step < 7 - w.corner; step++) {
                const bool first = step == 0 || (w.corner && step == 4);
                const int row = v + 4 + (first ? -w.step : w.step) / 2, ou = origin_u(u);
                uint32_t dst = s_ring + (first ? 0 : slot), mid = s_ring + kOffMid + 512, bar = first ? bar_a : bar_b;
                mbar_wait(wait_bar, wait_par);
                TRW(24 + step);
#pragma unroll 1
                for (int ch = (cta & 1) * kC; mid < s_m; ch += 64, dst += kRingChunk, mid += kRingChunk) {
                    if (elect()) {
                        mbar_expect_tx(bar, first ? kSlotBytes : kSlotBytes + kMidBytes);
                        tma_box(dst, map, bar, ch, ou, (cta >> 1) & 1, row);
                    }
                    if (!first) {
                        if (elect()) tma_box(mid, map + 1, bar, ch, ou, (cta >> 1) & 1, v + 6);
                        bar += 8;
                    }
                }
                if (TN(2, 0) && w.sv == kPixBytes && step >= TN(3, 0) && step < 6) {
                    if (step > 1) wait_until(clock_now(), TN(2, 0));
#pragma unroll 1
                    for (int ch = (cta & 1) * kC, n = 0; n < 3; ch += 64, n++)
                        if (elect()) {
                            tma_prefetch(map, ch, ou, (cta >> 1) & 1, v + 4 + w.step / 2 + (step ? w.step : 0));
                            tma_prefetch(map + 1, ch, ou, (cta >> 1) & 1, v + 6 + (step ? w.step : 0));
                        }
                }
                if (step == 0) {
                    launch /= kGrid;
                    asm volatile("st.shared.v2.u32 [%0], {%1, %2};" ::"r"(s_par), "r"((launch & 1) * 2 * kWBytes), "r"(0) : "memory");
                    asm volatile("bar.arrive 5, 128;\nbar.arrive 3, 160;\nbar.arrive 4, 160;" ::: "memory");
                }
                if (step < 2) {
                    if (step) {
                        if (lane == 0) count_up(&g->launches);
                        asm volatile("bar.sync 6, 128;" ::: "memory");
                    }
                    wait_until(t_start, step ? TN(5, kTimeW) : TN(6, kTimeM));
                    TRW(5 + 4 * step);
#pragma unroll 1
                    for (int c = 3 * step; c < 3 + 3 * step; c++)
                        if (elect()) {
                            mbar_expect_tx(bar_img + 8 * c, kWChunk);
                            bulk_g2s(s_m + c * kWChunk, g->img[launch & 1][0] + c * kWChunk, kWChunk, bar_img + 8 * c);
                        }
                }
                const bool again = w.corner && step == 3;
                wait_bar = step == 0 ? bar_img + 8 * TN(1, 1) : again ? bar_use + 8 : bar_use;
                if (!again) {
                    wait_par = slot ? 0 : step != 0;
                    slot ^= kSlotStride;
                    if (w.corner && step == 2) { u += 8; v -= 8; } else if (step) v += w.step;
                }
            }
        }
        TRDUMP();
        return;
    }
    if (wg == 1 && wq < 3) {
        if (!which) m_partial(wqkv, jhi, jlo, wq, lane, (uint32_t)dsc & 1);
        const uint32_t off = piece_offset(which, which ? jlo : jlo + wq, which ? 3 * jhi + wq : jhi, lane);
        asm volatile("bar.sync %0, 128;" ::"r"(5 + (off >> 31)) : "memory");
        const uint32_t par = lds_volatile(s_par);
        if (has_job && wq < 2 + which) {
            float d[2][4];
            if (wq == 0) TRX(which ? 1 : 18);
            if (which) {
                mbar_wait(bar_wop, 0);
                if (wq == 0) TRX(2);
                w_piece(wq, lane, d);
            } else {
                m_reduce(wq, lane, d);
            }
            piece_store(g, par, off, which, d);
            __syncwarp();
            piece_clear(g, 2 * kWBytes - par, off, which);
            if (wq == 0) TRX(which ? 3 : 0);
        }
        asm volatile("bar.arrive 7, 192;\nbar.arrive 6, 128;" ::: "memory");
    }
    const int order = w.step < 0 ? warp ^ 3 : warp;
    int tu = w.u, tv = w.v + w.step * wg;
    const int du2 = w.corner ? 8 : 0, dv2 = w.corner ? 0 : 2 * w.step;
    uint32_t o0, o1;
    wait_until(t_start, START_TIME);
    asm volatile("setmaxnreg.inc.sync.aligned.u32 240;");
    w.pixel_offsets(tu + r8, tv + 2 * wq, j, o0, o1);
    uint32_t fa[48];
    {
        RawX raw;
        load_raw(raw, x, o0, o1);
        asm volatile("bar.sync %0, 160;" ::"r"(3 + wg) : "memory");
        raw_to_frags(raw, 0, fa);
        pin(fa);
    }
    mbar_wait(bar_ok, 0);
    const uint64_t dA = dsc + wg * (kSlotStride >> 4), dB = dsc + (wg ^ 1) * (kSlotStride >> 4);

    float acc[96];
    uint32_t po[48];
    uint32_t c0, c1;
    asm volatile("" : "=r"(c0), "=r"(c1));
#pragma unroll
    for (int q = 0; q < 48; q++) asm volatile("" : "=r"(po[q]));
#pragma unroll 1
    for (int i = wg; i < w.ntiles; i += 2) {
        const bool first = i == 0, last = i == w.ntiles - 1;

        TRF(8 + 16 * k);
        wg_fence();
        if (!first) turn_wait(wg);
        proj_gemm(acc, fa, dsc, s_m, [&](int s) {
            if (s == 11 && !first) turn_pass(wg);
            const int n = __builtin_popcount(QSLOTS & ((1 << s) - 1));
            if (((QSLOTS >> s) & 1) && n < 12) store_one(i >= 2, out + c0, out + c1, po, n);
            if (s == 3 || s == 7) { mbar_wait(bar_ok + 2 * s + 2, 0); wg_fence(); }
        });
        __syncwarp();
        TRF(9 + 16 * k);
        uint8_t *p0 = out + c0, *p1 = out + c1;
        c0 = o0; c1 = o1;
        w.pixel_offsets(tu + du2 + r8, tv + dv2 + 2 * wq, j, o0, o1);
        if (i + 2 >= w.ntiles) o0 = o1 = 0;
        wg_wait<0>();
        pin(acc);
        TR(11 + 16 * k);
        TRT(80 + k);
#pragma unroll
        for (int n = __builtin_popcount(QSLOTS); n < 12 - __builtin_popcount(ASLOTS) - __builtin_popcount(BSLOTS); n++) store_one(i >= 2, p0, p1, po, n);
        acc_to_frags(acc, fa);
        pin(fa);

        float sA[44], sE[16], sB[44];
        RawX nxt;
        if (!first) turn_wait(wg);
        mbar_wait(bar_a, w.corner ? i >> 1 : 0);
        if (i == 0) TR(12);
        wg_fence();
#pragma unroll
        for (int s = 0; s < 12; s++) {
            if (s == 0) wgmma_n88<true>(sA, fa[4 * s], fa[4 * s + 1], fa[4 * s + 2], fa[4 * s + 3], desc_at(dA, (s >> 2) * kRingChunk + (s & 3) * 32));
            else wgmma_n88<false>(sA, fa[4 * s], fa[4 * s + 1], fa[4 * s + 2], fa[4 * s + 3], desc_at(dA, (s >> 2) * kRingChunk + (s & 3) * 32));
            if (s == 11) { wg_commit(); if (!first) turn_pass(wg); }
            if ((ASLOTS >> s) & 1) store_one(i >= 2, p0, p1, po, 12 - __builtin_popcount(BSLOTS) - __builtin_popcount(ASLOTS >> s));
        }
#pragma unroll
        for (int s = 12; s < 16; s++)
            if ((ASLOTS >> s) & 1) store_one(i >= 2, p0, p1, po, 12 - __builtin_popcount(BSLOTS) - __builtin_popcount(ASLOTS >> s));
        TRF(12 + 16 * k);
        const int vq = tv + 2 * wq;
        const uint4 tabu = lds128(s_tab + offsetof(Table, u) + (window_start(tu + r8) - origin_u(tu)) * 64 + j * 16);
        const uint4 tabv = lds128(s_tab + offsetof(Table, v) + (window_start(vq) + window_start(vq + 1) - 2 * tv) * 64 + j * 16);
        const uint4 route = lds128(s_tab + lane * 16);
        load_raw(nxt, x, o0, o1);
        float v0[14], v1[14];
#pragma unroll
        for (int b = 0; b < 14; b++) v0[b] = v1[b] = __int_as_float(0xff800000);
        wg_wait<0>();
        pin(sA);
        gather_outer(sA, tabu.x, tabv.x, v0, v1);
        pin(v0); pin(v1);
        if (!first) turn_wait(wg);
#pragma unroll
        for (int c = 0; c < 3; c++) {
            mbar_wait(bar_b + 8 * c, wg);
            if (i == 0 && c != 1) TR(13 + c);
            wg_fence();
#pragma unroll
            for (int s = 4 * c; s < 4 * c + 4; s++) {
                if (s == 0) wgmma_n88<true>(sB, fa[4 * s], fa[4 * s + 1], fa[4 * s + 2], fa[4 * s + 3], desc_at(dB, c * kRingChunk + (s & 3) * 32));
                else wgmma_n88<false>(sB, fa[4 * s], fa[4 * s + 1], fa[4 * s + 2], fa[4 * s + 3], desc_at(dB, c * kRingChunk + (s & 3) * 32));
                if ((BSLOTS >> s) & 1) store_one(i >= 2, p0, p1, po, 12 - __builtin_popcount(BSLOTS >> s));
            }
        }
        wg_commit();
#pragma unroll
        for (int s = 0; s < 12; s++)
            if (s == 0) wgmma_n32<true>(sE, fa[4 * s], fa[4 * s + 1], fa[4 * s + 2], fa[4 * s + 3], desc_at(dsc, kOffMid + (s >> 2) * kRingChunk + (s & 3) * 32));
            else wgmma_n32<false>(sE, fa[4 * s], fa[4 * s + 1], fa[4 * s + 2], fa[4 * s + 3], desc_at(dsc, kOffMid + (s >> 2) * kRingChunk + (s & 3) * 32));
        wg_commit();
        if (OSPLIT || !last) turn_pass(wg);
        TRF(13 + 16 * k);
        wg_wait<1>();
        pin(sB);
        gather_outer(sB, tabu.w, tabv.y, v0, v1);
        wg_wait<0>();
        pin(sE);
        TRF(14 + 16 * k);
        gather_mid(sE, tabu.w, tabv.z, v0, v1);
        const float m0 = quad_max(tree_max(v0)), m1 = quad_max(tree_max(v1));

        uint32_t y[14], pa[12], pb[12];
        exp_route<0, 14>(v0, v1, m0, m1, route, (j & 1) == 0, y);
        float s0 = tree_sum(v0), s1 = tree_sum(v1);
        asm volatile("" : "+f"(s0), "+f"(s1));
        unfold<0, 0, 6>(y, tabv.w, pa);
        if (OSPLIT || !last) turn_wait(wg + (y[0] >> 31));
        TRF(15 + 16 * k + (y[13] >> 31));
        wg_fence();
        wgmma_sp_n192_tb<true, 0>(acc, pa[0], pa[1], pa[2], pa[3], desc_at(dA, kToV), tabu.y);
        wgmma_sp_n192_tb<false, 1>(acc, pa[4], pa[5], pa[6], pa[7], desc_at(dA, kToV + 4096), tabu.y);
        wgmma_sp_n192_tb<false, 0>(acc, pa[8], pa[9], pa[10], pa[11], desc_at(dA, kToV + 8192), tabu.z);
        wgmma_sp_n192_tb<false, 1>(acc, y[10], y[11], y[12], y[13], desc_at(dsc, kToV + kOffMid), tabu.z);
        wg_commit();
        unfold<8, 0, 6>(y, tabv.w, pb);
        wg_fence();
        wgmma_sp_n192_tb<false, 0>(acc, pb[0], pb[1], pb[2], pb[3], desc_at(dB, kToV), tabu.y);
        wgmma_sp_n192_tb<false, 1>(acc, pb[4], pb[5], pb[6], pb[7], desc_at(dB, kToV + 4096), tabu.y);
        wgmma_sp_n192_tb<false, 0>(acc, pb[8], pb[9], pb[10], pb[11], desc_at(dB, kToV + 8192), tabu.z);
        wg_commit();
        if (!last) turn_pass(wg);
        TRF(16 + 16 * k);
        wg_wait<1>();
        if (lane == 0) mbar_arrive(bar_use);
        TRF(17 + 16 * k);
        mbar_wait(bar_ok + 24, 0);
        wg_wait<0>();
        if (lane == 0) mbar_arrive(bar_use + 8);
        pin(acc);
        TR(18 + 16 * k);

        acc_to_frags(acc, po);
        pin(po);
        if (!last) turn_wait(wg);
        wg_fence();
        proj_gemm(acc, po, dsc, s_wv, [&](int s) {
            if (s + 1 == OSPLIT && i + 2 == w.ntiles) { turn_pass(wg); turn_wait(wg); }
        });
        if (!last) turn_pass(wg);
        TRF(19 + 16 * k);
        const uint32_t zero = lds_volatile(s_late);
        const float inv0 = rcp(quad_sum(s0 + __uint_as_float(zero))), inv1 = rcp(quad_sum(s1 + __uint_as_float(zero)));
        raw_to_frags(nxt, zero, fa);
        pin(fa);
#pragma unroll
        for (int q = 0; q < 48; q += 4) keep(wqkv == nullptr, fa[q], fa[q + 1], fa[q + 2], fa[q + 3]);
        keep(wqkv == nullptr, __float_as_uint(inv0), __float_as_uint(inv1), zero, lane);
        TRF(20 + 16 * k);
        tu += du2; tv += dv2;
        wg_wait<0>();
        pin(acc);
        TR(21 + 16 * k);
#pragma unroll
        for (int q = 0; q < 96; q++) acc[q] *= q & 2 ? inv1 : inv0;
        pack_out(acc, po);
#pragma unroll
        for (int n = 0; n < INLOOP; n++) store_one<false>(last, out + c0, out + c1, po, n);
        pin(po);
    }
#pragma unroll
    for (int n = 0; n < 12; n++) {
        asm volatile("{\n.reg .pred p;\nsetp.eq.u32 p, %0, 0;\n@p nanosleep.u32 %1;\n}\n" ::"r"(wg), "n"(NAP) : "memory");
        store_one<false>(n >= INLOOP || wg == 0, out + c0, out + c1, po, n);
    }
    TRE(7);
    TRG(1);
    TRDUMP();
}

typedef CUresult (*EncodeTiledFn)(CUtensorMap*, CUtensorMapDataType, cuuint32_t, void*, const cuuint64_t*, const cuuint64_t*,
                                  const cuuint32_t*, const cuuint32_t*, CUtensorMapInterleave, CUtensorMapSwizzle,
                                  CUtensorMapL2promotion, CUtensorMapFloatOOBfill);

bool make_maps(EncodeTiledFn fn, Maps* maps, void* x, void* wqkv, void* wo) {
    const cuuint64_t pix2 = 2 * kPixBytes, row = (cuuint64_t)kHW * kPixBytes;
    const cuuint32_t estr[5] = {1, 1, 1, 1, 1};
    bool ok = true;
    for (int tr = 0; tr < 2; tr++)
        for (int b = 0; b < 2; b++) {
            const cuuint64_t su = tr ? 2 * row : pix2, sv = tr ? pix2 : 2 * row;
            const cuuint64_t dims[5] = {2 * kC, 2, 105, 2, 112};
            const cuuint64_t strides[4] = {7 * su, su, row, sv};
            const cuuint32_t box[5] = {64, 2, 7, 1, b ? 2u : 6u};
            ok = ok && fn(&maps->m[2 * tr + b], CU_TENSOR_MAP_DATA_TYPE_BFLOAT16, 5, x, dims, strides, box, estr,
                          CU_TENSOR_MAP_INTERLEAVE_NONE, CU_TENSOR_MAP_SWIZZLE_128B, CU_TENSOR_MAP_L2_PROMOTION_L2_128B,
                          CU_TENSOR_MAP_FLOAT_OOB_FILL_NONE) == CUDA_SUCCESS;
        }
    for (int b = 0; b < 2; b++) {
        const cuuint64_t dims[3] = {b ? 64u : 48u, kC, b ? 9u : 4u}, strides[2] = {(b ? 3u : 1u) * kPixBytes, b ? 128u : 96u};
        const cuuint32_t box[3] = {b ? 64u : 48u, b ? 16u : 192u, b ? 3u : 1u};
        ok = ok && fn(b ? &maps->wv : &maps->wo, CU_TENSOR_MAP_DATA_TYPE_BFLOAT16, 3, b ? wqkv : wo, dims, strides, box, estr,
                      CU_TENSOR_MAP_INTERLEAVE_NONE, b ? CU_TENSOR_MAP_SWIZZLE_128B : CU_TENSOR_MAP_SWIZZLE_NONE, CU_TENSOR_MAP_L2_PROMOTION_L2_128B,
                      CU_TENSOR_MAP_FLOAT_OOB_FILL_NONE) == CUDA_SUCCESS;
    }
    return ok;
}

}

extern "C" void kernel_launch(void* const* d_in, const int* in_sizes, int n_in, void* d_out, int out_size) {
    static EncodeTiledFn encode = nullptr;
    static Scratch* scratch = nullptr;
    static Tables* tables = nullptr;
    if (!encode) {
        int dev = 0, reserved = 0;
        cudaFuncAttributes attr;
        cudaGetDevice(&dev);
        cudaDeviceGetAttribute(&reserved, cudaDevAttrReservedSharedMemoryPerBlock, dev);
        cudaFuncGetAttributes(&attr, nat_fused_kernel);
        if (reserved != (int)kSmemBase || attr.sharedSizeBytes != 0) return;
        cudaGetSymbolAddress((void**)&scratch, g_scratch);
        cudaGetSymbolAddress((void**)&tables, g_tables);
        void* fn = nullptr;
        cudaDriverEntryPointQueryResult st;
        cudaGetDriverEntryPoint("cuTensorMapEncodeTiled", &fn, cudaEnableDefault, &st);
        encode = (EncodeTiledFn)fn;
        cudaFuncSetAttribute(nat_fused_kernel, cudaFuncAttributeMaxDynamicSharedMemorySize, kSmemBytes);
    }
    Maps maps;
    maps.tables = tables;
    if (!encode || !make_maps(encode, &maps, d_in[0], d_in[1], d_in[2])) return;
    nat_fused_kernel<<<kGrid, kThreads, kSmemBytes>>>((const uint8_t*)d_in[0], (const uint8_t*)d_in[1], (uint8_t*)d_out, scratch, (const uint8_t*)d_in[2],
                                                      kDescRing, maps);
}
```

```cpp
#include <cuda_runtime.h>
#include <cuda_bf16.h>
#include <cuda.h>
#include <stdint.h>
#include <type_traits>
#include <stdlib.h>
#include <stddef.h>

#define KEEPFA 1
#define ASLOTS 0x3800
#define BSLOTS 0x6
#define QSLOTS 0x78a
#define OSPLIT 3
#define NAP 40
#define LDGLATE 0
#define SPEC 1
#define INLOOP 3

namespace {

constexpr int kC          = 192;
constexpr int kHW         = 224;
constexpr int kPixBytes   = kC * 2;
constexpr int kSlotBytes  = 84 * 128;
constexpr int kMidBytes   = 28 * 128;
constexpr int kOffMid     = 88 * 128;
constexpr int kSlotStride = 120 * 128;
constexpr int kRingChunk  = 208 * 128;
constexpr int kWChunk     = 192 * 128;
constexpr int kWBytes     = 3 * kWChunk;
constexpr uint32_t kSmemBase = 1024;
constexpr uint32_t s_ring = kSmemBase, s_m = s_ring + 3 * kRingChunk, s_wv = s_m + kWBytes, s_bar = s_wv + kWBytes;
constexpr uint32_t bar_b = s_bar, bar_img = s_bar + 24, bar_redo = s_bar + 72, bar_wop = s_bar + 96, bar_a = s_bar + 104,
                   bar_ok = s_bar + 112, bar_use = s_bar + 144;
constexpr uint32_t s_par = s_bar + 160, s_late = s_bar + 164, s_again = s_bar + 168, s_tab = s_bar + 256, s_trace = s_tab + 2048;
constexpr int kSmemBytes  = s_trace + 2048 - kSmemBase;
constexpr int kThreads    = 384;
constexpr int kGrid       = 132;
constexpr int kTimeM = 2600, kTimeW = 5100;
constexpr float kScaleLog2e = 0.07216878364870322f * 1.4426950408889634f;

struct Maps {
    CUtensorMap m[4];
    CUtensorMap wo, wv;
    const struct Tables* tables;
};
#define TN(i, dflt) (dflt)
#define START_TIME (wg ? 850 + 500 * order : 250 + 560 * order)

struct Scratch {
    uint8_t img[2][2][kWBytes];
    uint32_t launches;
};
__device__ __align__(1024) Scratch g_scratch;

struct Table {
    uint32_t route[32][4];
    uint32_t u[8][4][4];
    uint32_t v[16][4][4];
};
struct Tables { Table t[2]; };
constexpr Tables make_tables() {
    Tables r = {};
    for (int rev = 0; rev < 2; rev++)
        for (int j = 0; j < 4; j++) {
            Table& t = r.t[rev];
            for (int q = 0; q < 8; q++) {
                uint32_t* e = t.route[4 * q + j];
                e[0] = 4 * q + 2 * (j & 1) + (j >> 1); e[1] = e[0] ^ 1;
                e[2] = j < 2 ? 0x5410u : 0x1054u; e[3] = e[2] + 0x2222u;
                e = t.u[q][j];
                for (int n = 0; n < 7; n++) e[0] |= ((n + j) % 7 < q ? 1u : 0u) << n;
                e[3] = e[0];
                for (int k = 0; k < 2; k++) {
                    const int step = 2 * k + (j >> 1), p0 = (step < 3 ? 16 * step : 40) + 8 * (j & 1);
                    uint32_t m = 0x8888u;
                    for (int n = 0; n < 8; n++) m |= ((p0 + n) % 7 < q ? 1u : 0u) << (2 * n);
                    e[1 + k] = m * 0x10001u;
                }
            }
            for (int sum = 0; sum < 15; sum++) {
                uint32_t* e = t.v[sum][j];
                for (int row = 0; row < 2; row++)
                    for (int b = 0; b < 14; b++) {
                        const int off = (sum + row) / 2, p = 4 * b + j;
                        const uint32_t bit = 1u << (2 * b + row);
                        if (p < 42 && p >= 7 * off) e[rev] |= bit;
                        if (p < 7 * off - 7) e[1 - rev] |= bit;
                        if (p >= 42 && p >= 7 * off && p < 7 * off + 49) e[2] |= bit;
                    }
                for (int n = 0; n < 6; n++)
                    if (8 * n + 2 * j < 42) e[3] |= 1u << (n + ((8 * n + 2 * j >= 7 * (sum / 2 & ~1)) != rev ? 0 : 8));
            }
        }
    return r;
}
__device__ __align__(128) const Tables g_tables = make_tables();

#define WO4(i) "=f"(d[i]), "=f"(d[i + 1]), "=f"(d[i + 2]), "=f"(d[i + 3])
#define RW4(i) "+f"(d[i]), "+f"(d[i + 1]), "+f"(d[i + 2]), "+f"(d[i + 3])

template <bool FIRST>
__device__ __forceinline__ void wgmma_n192(float (&d)[96], uint32_t a0, uint32_t a1, uint32_t a2, uint32_t a3, uint64_t descb) {
    if constexpr (FIRST) {
        asm volatile(
            "wgmma.mma_async.sync.aligned.m64n192k16.f32.bf16.bf16 "
            "{%0, %1, %2, %3, %4, %5, %6, %7, %8, %9, %10, %11, %12, %13, %14, %15, %16, %17, %18, %19, %20, %21, %22, %23, "
            "%24, %25, %26, %27, %28, %29, %30, %31, %32, %33, %34, %35, %36, %37, %38, %39, %40, %41, %42, %43, %44, %45, %46, %47, "
            "%48, %49, %50, %51, %52, %53, %54, %55, %56, %57, %58, %59, %60, %61, %62, %63, %64, %65, %66, %67, %68, %69, %70, %71, "
            "%72, %73, %74, %75, %76, %77, %78, %79, %80, %81, %82, %83, %84, %85, %86, %87, %88, %89, %90, %91, %92, %93, %94, %95}, "
            "{%96, %97, %98, %99}, %100, 0, 1, 1, 0;"
            : WO4(0), WO4(4), WO4(8), WO4(12), WO4(16), WO4(20), WO4(24), WO4(28), WO4(32), WO4(36), WO4(40), WO4(44),
              WO4(48), WO4(52), WO4(56), WO4(60), WO4(64), WO4(68), WO4(72), WO4(76), WO4(80), WO4(84), WO4(88), WO4(92)
            : "r"(a0), "r"(a1), "r"(a2), "r"(a3), "l"(descb));
    } else {
        asm volatile(
            "wgmma.mma_async.sync.aligned.m64n192k16.f32.bf16.bf16 "
            "{%0, %1, %2, %3, %4, %5, %6, %7, %8, %9, %10, %11, %12, %13, %14, %15, %16, %17, %18, %19, %20, %21, %22, %23, "
            "%24, %25, %26, %27, %28, %29, %30, %31, %32, %33, %34, %35, %36, %37, %38, %39, %40, %41, %42, %43, %44, %45, %46, %47, "
            "%48, %49, %50, %51, %52, %53, %54, %55, %56, %57, %58, %59, %60, %61, %62, %63, %64, %65, %66, %67, %68, %69, %70, %71, "
            "%72, %73, %74, %75, %76, %77, %78, %79, %80, %81, %82, %83, %84, %85, %86, %87, %88, %89, %90, %91, %92, %93, %94, %95}, "
            "{%96, %97, %98, %99}, %100, 1, 1, 1, 0;"
            : RW4(0), RW4(4), RW4(8), RW4(12), RW4(16), RW4(20), RW4(24), RW4(28), RW4(32), RW4(36), RW4(40), RW4(44),
              RW4(48), RW4(52), RW4(56), RW4(60), RW4(64), RW4(68), RW4(72), RW4(76), RW4(80), RW4(84), RW4(88), RW4(92)
            : "r"(a0), "r"(a1), "r"(a2), "r"(a3), "l"(descb));
    }
}

template <bool FIRST>
__device__ __forceinline__ void wgmma_n88(float (&d)[44], uint32_t a0, uint32_t a1, uint32_t a2, uint32_t a3, uint64_t descb) {
    if constexpr (FIRST) {
        asm volatile(
            "wgmma.mma_async.sync.aligned.m64n88k16.f32.bf16.bf16 "
            "{%0, %1, %2, %3, %4, %5, %6, %7, %8, %9, %10, %11, %12, %13, %14, %15, %16, %17, %18, %19, %20, %21, %22, %23, "
            "%24, %25, %26, %27, %28, %29, %30, %31, %32, %33, %34, %35, %36, %37, %38, %39, %40, %41, %42, %43}, "
            "{%44, %45, %46, %47}, %48, 0, 1, 1, 0;"
            : WO4(0), WO4(4), WO4(8), WO4(12), WO4(16), WO4(20), WO4(24), WO4(28), WO4(32), WO4(36), WO4(40)
            : "r"(a0), "r"(a1), "r"(a2), "r"(a3), "l"(descb));
    } else {
        asm volatile(
            "wgmma.mma_async.sync.aligned.m64n88k16.f32.bf16.bf16 "
            "{%0, %1, %2, %3, %4, %5, %6, %7, %8, %9, %10, %11, %12, %13, %14, %15, %16, %17, %18, %19, %20, %21, %22, %23, "
            "%24, %25, %26, %27, %28, %29, %30, %31, %32, %33, %34, %35, %36, %37, %38, %39, %40, %41, %42, %43}, "
            "{%44, %45, %46, %47}, %48, 1, 1, 1, 0;"
            : RW4(0), RW4(4), RW4(8), RW4(12), RW4(16), RW4(20), RW4(24), RW4(28), RW4(32), RW4(36), RW4(40)
            : "r"(a0), "r"(a1), "r"(a2), "r"(a3), "l"(descb));
    }
}

template <bool FIRST>
__device__ __forceinline__ void wgmma_n32(float (&d)[16], uint32_t a0, uint32_t a1, uint32_t a2, uint32_t a3, uint64_t descb) {
    if constexpr (FIRST) {
        asm volatile(
            "wgmma.mma_async.sync.aligned.m64n32k16.f32.bf16.bf16 "
            "{%0, %1, %2, %3, %4, %5, %6, %7, %8, %9, %10, %11, %12, %13, %14, %15}, "
            "{%16, %17, %18, %19}, %20, 0, 1, 1, 0;"
            : WO4(0), WO4(4), WO4(8), WO4(12)
            : "r"(a0), "r"(a1), "r"(a2), "r"(a3), "l"(descb));
    } else {
        asm volatile(
            "wgmma.mma_async.sync.aligned.m64n32k16.f32.bf16.bf16 "
            "{%0, %1, %2, %3, %4, %5, %6, %7, %8, %9, %10, %11, %12, %13, %14, %15}, "
            "{%16, %17, %18, %19}, %20, 1, 1, 1, 0;"
            : RW4(0), RW4(4), RW4(8), RW4(12)
            : "r"(a0), "r"(a1), "r"(a2), "r"(a3), "l"(descb));
    }
}

template <bool FIRST, int SEL>
__device__ __forceinline__ void wgmma_sp_n192_tb(float (&d)[96], uint32_t a0, uint32_t a1, uint32_t a2, uint32_t a3, uint64_t descb, uint32_t meta) {
    if constexpr (FIRST) {
        asm volatile(
            "wgmma.mma_async.sp.sync.aligned.m64n192k32.f32.bf16.bf16 "
            "{%0, %1, %2, %3, %4, %5, %6, %7, %8, %9, %10, %11, %12, %13, %14, %15, %16, %17, %18, %19, %20, %21, %22, %23, "
            "%24, %25, %26, %27, %28, %29, %30, %31, %32, %33, %34, %35, %36, %37, %38, %39, %40, %41, %42, %43, %44, %45, %46, %47, "
            "%48, %49, %50, %51, %52, %53, %54, %55, %56, %57, %58, %59, %60, %61, %62, %63, %64, %65, %66, %67, %68, %69, %70, %71, "
            "%72, %73, %74, %75, %76, %77, %78, %79, %80, %81, %82, %83, %84, %85, %86, %87, %88, %89, %90, %91, %92, %93, %94, %95}, "
            "{%96, %97, %98, %99}, %100, %101, %102, 0, 1, 1, 1;"
            : WO4(0), WO4(4), WO4(8), WO4(12), WO4(16), WO4(20), WO4(24), WO4(28), WO4(32), WO4(36), WO4(40), WO4(44),
              WO4(48), WO4(52), WO4(56), WO4(60), WO4(64), WO4(68), WO4(72), WO4(76), WO4(80), WO4(84), WO4(88), WO4(92)
            : "r"(a0), "r"(a1), "r"(a2), "r"(a3), "l"(descb), "r"(meta), "n"(SEL));
    } else {
        asm volatile(
            "wgmma.mma_async.sp.sync.aligned.m64n192k32.f32.bf16.bf16 "
            "{%0, %1, %2, %3, %4, %5, %6, %7, %8, %9, %10, %11, %12, %13, %14, %15, %16, %17, %18, %19, %20, %21, %22, %23, "
            "%24, %25, %26, %27, %28, %29, %30, %31, %32, %33, %34, %35, %36, %37, %38, %39, %40, %41, %42, %43, %44, %45, %46, %47, "
            "%48, %49, %50, %51, %52, %53, %54, %55, %56, %57, %58, %59, %60, %61, %62, %63, %64, %65, %66, %67, %68, %69, %70, %71, "
            "%72, %73, %74, %75, %76, %77, %78, %79, %80, %81, %82, %83, %84, %85, %86, %87, %88, %89, %90, %91, %92, %93, %94, %95}, "
            "{%96, %97, %98, %99}, %100, %101, %102, 1, 1, 1, 1;"
            : RW4(0), RW4(4), RW4(8), RW4(12), RW4(16), RW4(20), RW4(24), RW4(28), RW4(32), RW4(36), RW4(40), RW4(44),
              RW4(48), RW4(52), RW4(56), RW4(60), RW4(64), RW4(68), RW4(72), RW4(76), RW4(80), RW4(84), RW4(88), RW4(92)
            : "r"(a0), "r"(a1), "r"(a2), "r"(a3), "l"(descb), "r"(meta), "n"(SEL));
    }
}

#define TR(slot)
#define TRX(slot)
#define TRE(slot)
#define TRT(slot)
#define TRF(slot)
#define TRW(slot)
#define TRG(slot)
#define TRDUMP()

__device__ __forceinline__ void wg_fence() { asm volatile("wgmma.fence.sync.aligned;" ::: "memory"); }
__device__ __forceinline__ void wg_commit() { asm volatile("wgmma.commit_group.sync.aligned;" ::: "memory"); }
template <int N>
__device__ __forceinline__ void wg_wait() { asm volatile("wgmma.wait_group.sync.aligned %0;" ::"n"(N) : "memory"); }

template <int N>
__device__ __forceinline__ void pin(float (&d)[N]) {
#pragma unroll
    for (int i = 0; i < N; i++) asm volatile("" : "+f"(d[i])::"memory");
}
template <int N>
__device__ __forceinline__ void pin(uint32_t (&d)[N]) {
#pragma unroll
    for (int i = 0; i < N; i++) asm volatile("" : "+r"(d[i])::"memory");
}

constexpr uint64_t kDescRing = ((uint64_t)((1u << 30) | (1024u >> 4)) << 32) | (1u << 16) | (s_ring >> 4);
constexpr uint32_t kToV = ((kRingChunk >> 4) - 1) << 20;
__device__ __forceinline__ uint64_t desc_at(uint64_t base, uint32_t byte_off) {
    uint64_t d;
    asm volatile("add.s64 %0, %1, %2;" : "=l"(d) : "l"(base), "l"((uint64_t)(byte_off >> 4)));
    return d;
}

__device__ __forceinline__ void mbar_init(uint32_t bar, uint32_t count) {
    asm volatile("mbarrier.init.shared::cta.b64 [%0], %1;" ::"r"(bar), "r"(count) : "memory");
}
__device__ __forceinline__ void mbar_expect_tx(uint32_t bar, uint32_t bytes) {
    asm volatile("mbarrier.arrive.expect_tx.shared::cta.b64 _, [%0], %1;" ::"r"(bar), "r"(bytes) : "memory");
}
__device__ __forceinline__ void expect_tx_only(uint32_t bar, uint32_t bytes) {
    asm volatile("mbarrier.expect_tx.relaxed.cta.shared::cta.b64 [%0], %1;" ::"r"(bar), "r"(bytes) : "memory");
}
__device__ __forceinline__ void mbar_arrive(uint32_t bar) {
    asm volatile("mbarrier.arrive.shared::cta.b64 _, [%0];" ::"r"(bar) : "memory");
}
__device__ __forceinline__ void mbar_wait(uint32_t bar, uint32_t parity) {
    asm volatile(
        "{\n.reg .pred p;\n"
        "W: mbarrier.try_wait.parity.shared::cta.b64 p, [%0], %1;\n"
        "@!p bra W;\n}\n"
        ::"r"(bar), "r"(parity) : "memory");
}
__device__ __forceinline__ uint32_t clock_now() {
    uint32_t c;
    asm volatile("mov.u32 %0, %%clock;" : "=r"(c)::"memory");
    return c;
}
__device__ __forceinline__ void wait_until(uint32_t t0, int t) {
    if (t == 0) return;
    while ((int)(clock_now() - t0) < t) {}
}
__device__ __forceinline__ bool elect() {
    uint32_t ok;
    asm volatile("{\n.reg .pred p;\nelect.sync _|p, 0xffffffff;\nselp.u32 %0, 1, 0, p;\n}\n" : "=r"(ok));
    return ok != 0;
}
__device__ __forceinline__ void turn_wait(int wg) { asm volatile("bar.sync %0, 256;" ::"r"(1 + wg) : "memory"); }
__device__ __forceinline__ void turn_pass(int wg) { asm volatile("bar.arrive %0, 256;" ::"r"(2 - wg) : "memory"); }

__device__ __forceinline__ void tma_box(uint32_t dst, const CUtensorMap* map, uint32_t bar, int c0, int c2, int c3, int c4) {
    asm volatile(
        "cp.async.bulk.tensor.5d.shared::cluster.global.mbarrier::complete_tx::bytes [%0], [%1, {%3, %4, %5, %6, %7}], [%2];"
        ::"r"(dst), "l"(map), "r"(bar), "r"(c0), "r"(0), "r"(c2), "r"(c3), "r"(c4)
        : "memory");
}
__device__ __forceinline__ void tma_3d(uint32_t dst, const CUtensorMap* map, uint32_t bar, int c1, int c2) {
    asm volatile("cp.async.bulk.tensor.3d.shared::cluster.global.mbarrier::complete_tx::bytes [%0], [%1, {%3, %4, %5}], [%2];"
                 ::"r"(dst), "l"(map), "r"(bar), "r"(0), "r"(c1), "r"(c2)
                 : "memory");
}
__device__ __forceinline__ void prefetch_map(const CUtensorMap* map) {
    asm volatile("prefetch.tensormap [%0];" ::"l"(map) : "memory");
}
__device__ __forceinline__ uint4 ldg(const void* p) {
    uint4 v;
    asm volatile("ld.global.v4.u32 {%0, %1, %2, %3}, [%4];" : "=r"(v.x), "=r"(v.y), "=r"(v.z), "=r"(v.w) : "l"(p) : "memory");
    return v;
}
__device__ __forceinline__ uint32_t pack_bf16(float lo, float hi) {
    uint32_t r;
    asm("cvt.rn.bf16x2.f32 %0, %1, %2;" : "=r"(r) : "f"(hi), "f"(lo));
    return r;
}
__device__ __forceinline__ float ex2(float x) {
    float y;
    asm("ex2.approx.ftz.f32 %0, %1;" : "=f"(y) : "f"(x));
    return y;
}
__device__ __forceinline__ float rcp(float x) {
    float y;
    asm("rcp.approx.ftz.f32 %0, %1;" : "=f"(y) : "f"(x));
    return y;
}
__device__ __forceinline__ void mma16816(float (&d)[4], uint32_t a0, uint32_t a1, uint32_t a2, uint32_t a3, uint32_t b0, uint32_t b1) {
    asm volatile("mma.sync.aligned.m16n8k16.row.col.f32.bf16.bf16.f32 {%0, %1, %2, %3}, {%4, %5, %6, %7}, {%8, %9}, {%0, %1, %2, %3};"
                 : "+f"(d[0]), "+f"(d[1]), "+f"(d[2]), "+f"(d[3])
                 : "r"(a0), "r"(a1), "r"(a2), "r"(a3), "r"(b0), "r"(b1));
}
__device__ __forceinline__ uint4 lds128(uint32_t addr) {
    uint4 v;
    asm volatile("ld.volatile.shared.v4.u32 {%0, %1, %2, %3}, [%4];" : "=r"(v.x), "=r"(v.y), "=r"(v.z), "=r"(v.w) : "r"(addr) : "memory");
    return v;
}
__device__ __forceinline__ uint32_t lds_volatile(uint32_t addr) {
    uint32_t v;
    asm volatile("ld.volatile.shared.u32 %0, [%1];" : "=r"(v) : "r"(addr) : "memory");
    return v;
}

__device__ __forceinline__ int window_start(int n) { return min(max(n, 0), 105); }
__device__ __forceinline__ int origin_u(int u) { return min(max(u, 0), 98); }

struct Work {
    int u, v;
    int step;
    uint32_t su, sv;
    uint32_t base;
    bool corner;
    int ntiles;
    __device__ __forceinline__ void pixel_offsets(int qu, int qv, int j, uint32_t& o0, uint32_t& o1) const {
        const uint32_t b = (qu + window_start(qu)) * su + j * 16 + base;
        o0 = b + (qv + window_start(qv)) * sv;
        o1 = b + (qv + 1 + window_start(qv + 1)) * sv;
    }
};

__device__ __forceinline__ Work decode_work(int c) {
    Work w;
    const bool transposed = (c >> 4) == 7;
    const int px = 6 * (c & 1), py = 3 * (c & 2);
    w.corner = c >= 128;
    w.step = 8 - 4 * (c & 4);
    w.u = (c < 112 ? c & ~7 : 96 + (c & 8)) + (transposed ? py : px) - 6;
    w.v = (w.corner ? 96 : 48 - 2 * (c & 4)) + (transposed ? px : py) - 6;
    w.su = transposed ? kHW * kPixBytes : kPixBytes;
    w.sv = transposed ? kPixBytes : kHW * kPixBytes;
    w.base = px * (kPixBytes / 6) + py * (kHW * kPixBytes / 6) + 6 * (kHW + 1) * kPixBytes;
    w.ntiles = w.corner ? 4 : 6;
    return w;
}

struct RawX { uint4 a[6], b[6]; };
__device__ __forceinline__ void load_raw(RawX& r, const uint8_t* base, uint32_t o0, uint32_t o1) {
    __syncwarp();
#pragma unroll
    for (int c = 0; c < 6; c++) { r.a[c] = ldg(base + o0 + c * 64); r.b[c] = ldg(base + o1 + c * 64); }
    __syncwarp();
}
__device__ __forceinline__ void raw_to_frags(const RawX& r, uint32_t zero, uint32_t (&f)[48]) {
#pragma unroll
    for (int c = 0; c < 6; c++) {
        asm volatile("{\n.reg .b32 t, u;\nadd.u32 t, %4, %8;\nadd.u32 u, %5, %8;\nxor.b32 %0, %6, %8;\nxor.b32 %1, %7, %8;\n"
                     "xor.b32 %2, t, %8;\nxor.b32 %3, u, %8;\n}\n"
                     : "=&r"(f[8 * c + 1]), "=&r"(f[8 * c + 3]), "=&r"(f[8 * c + 4]), "=&r"(f[8 * c + 6])
                     : "r"(r.a[c].y), "r"(r.a[c].w), "r"(r.b[c].x), "r"(r.b[c].z), "r"(zero));
        f[8 * c + 0] = r.a[c].x; f[8 * c + 2] = r.a[c].z; f[8 * c + 5] = r.b[c].y; f[8 * c + 7] = r.b[c].w;
    }
}
__device__ __forceinline__ void acc_to_frags(const float (&d)[96], uint32_t (&f)[48]) {
#pragma unroll
    for (int i = 0; i < 48; i++) f[i] = pack_bf16(d[2 * i], d[2 * i + 1]);
}

template <class F>
__device__ __forceinline__ void proj_gemm(float (&d)[96], const uint32_t (&a)[48], uint64_t dsc, uint32_t img, F after) {
#pragma unroll
    for (int s = 0; s < 12; s++) {
        if (s == 0) wgmma_n192<true>(d, a[4 * s], a[4 * s + 1], a[4 * s + 2], a[4 * s + 3], desc_at(dsc, img - s_ring + (s >> 2) * kWChunk + (s & 3) * 32));
        else wgmma_n192<false>(d, a[4 * s], a[4 * s + 1], a[4 * s + 2], a[4 * s + 3], desc_at(dsc, img - s_ring + (s >> 2) * kWChunk + (s & 3) * 32));
        if (s == 11) wg_commit();
        after(s);
    }
}
__device__ __forceinline__ void pack_out(const float (&acc)[96], uint32_t (&po)[48]) {
#pragma unroll
    for (int g = 0; g < 6; g++)
#pragma unroll
        for (int q = 0; q < 4; q++) {
            po[8 * g + q] = pack_bf16(acc[16 * g + 4 * q], acc[16 * g + 4 * q + 1]);
            po[8 * g + 4 + q] = pack_bf16(acc[16 * g + 4 * q + 2], acc[16 * g + 4 * q + 3]);
        }
}
template <bool PINNED = true>
__device__ __forceinline__ void store_one(bool on, uint8_t* p0, uint8_t* p1, const uint32_t (&po)[48], int n) {
    if (PINNED) __syncwarp();
    asm volatile("{\n.reg .pred p;\nsetp.ne.u32 p, %5, 0;\n@p st.global.v4.u32 [%0], {%1, %2, %3, %4};\n}\n"
                 ::"l"(((n & 1) ? p1 : p0) + (n >> 1) * 64), "r"(po[4 * n]), "r"(po[4 * n + 1]), "r"(po[4 * n + 2]), "r"(po[4 * n + 3]), "r"((uint32_t)on) : "memory");
}

template <int N>
__device__ __forceinline__ float tree_max(const float (&v)[N]) {
    float t[N];
#pragma unroll
    for (int i = 0; i < N; i++) t[i] = v[i];
#pragma unroll
    for (int w = 1; w < N; w *= 2)
#pragma unroll
        for (int i = 0; i + w < N; i += 2 * w) t[i] = fmaxf(t[i], t[i + w]);
    return t[0];
}
template <int N>
__device__ __forceinline__ float tree_sum(const float (&v)[N]) {
    float t[N];
#pragma unroll
    for (int i = 0; i < N; i++) t[i] = v[i];
#pragma unroll
    for (int w = 1; w < N; w *= 2)
#pragma unroll
        for (int i = 0; i + w < N; i += 2 * w) t[i] += t[i + w];
    return t[0];
}

template <int B>
__device__ __forceinline__ void pick(uint32_t h, uint32_t ok, const float* s, float& v0, float& v1) {
    asm("{\n.reg .pred p, q0, q1;\n.reg .b32 t;\nand.b32 t, %6, %7;\nsetp.ne.u32 p, t, 0;\n"
        "and.b32 t, %8, %9;\nsetp.ne.u32 q0, t, 0;\nand.b32 t, %8, %10;\nsetp.ne.u32 q1, t, 0;\n"
        "@q0 selp.f32 %0, %3, %2, p;\n@q1 selp.f32 %1, %5, %4, p;\n}\n"
        : "+f"(v0), "+f"(v1)
        : "f"(s[0]), "f"(s[1]), "f"(s[2]), "f"(s[3]), "r"(h), "n"(1 << ((4 * B) % 7)), "r"(ok), "n"(1 << (2 * B)), "n"(2 << (2 * B)));
}
template <int B, class F>
__device__ __forceinline__ void for_blocks(F f) {
    if constexpr (B > 0) { for_blocks<B - 1>(f); f(std::integral_constant<int, B - 1>{}); }
}
__device__ __forceinline__ void gather_outer(const float (&s)[44], uint32_t h, uint32_t ok, float (&v0)[14], float (&v1)[14]) {
    for_blocks<11>([&](auto B) {
        constexpr int b = B.value < 8 ? (B.value >> 1) + 7 * (B.value & 1) : B.value - 4;
        pick<b>(h, ok, &s[4 * b], v0[b], v1[b]);
    });
}
__device__ __forceinline__ void gather_mid(const float (&sE)[16], uint32_t h, uint32_t ok, float (&v0)[14], float (&v1)[14]) {
    for_blocks<4>([&](auto B) { pick<10 + B.value>(h, ok, &sE[4 * B.value], v0[10 + B.value], v1[10 + B.value]); });
}
__device__ __forceinline__ float quad_max(float m) {
    m = fmaxf(m, __shfl_xor_sync(0xffffffffu, m, 1));
    return fmaxf(m, __shfl_xor_sync(0xffffffffu, m, 2));
}
__device__ __forceinline__ float quad_sum(float s) {
    s += __shfl_xor_sync(0xffffffffu, s, 1);
    return s + __shfl_xor_sync(0xffffffffu, s, 2);
}
template <int B0, int B1>
__device__ __forceinline__ void exp_route(float (&v0)[14], float (&v1)[14], float m0, float m1, const uint4& r, bool even, uint32_t (&y)[14]) {
#pragma unroll
    for (int b = B0; b < B1; b++) { v0[b] = ex2(v0[b] - m0); v1[b] = ex2(v1[b] - m1); }
#pragma unroll
    for (int b = B0; b < B1; b += 2) {
        const uint32_t x0 = pack_bf16(v0[b], v1[b]), x1 = pack_bf16(v0[b + 1], v1[b + 1]);
        const uint32_t u = __shfl_sync(0xffffffffu, even ? x0 : x1, r.x);
        const uint32_t w = __shfl_sync(0xffffffffu, even ? x1 : x0, r.y);
        y[b] = __byte_perm(u, w, r.z); y[b + 1] = __byte_perm(u, w, r.w);
    }
}
template <int BIT0, int N0, int N1>
__device__ __forceinline__ void unfold(const uint32_t (&y)[14], uint32_t fold, uint32_t (&p)[12]) {
    for_blocks<N1 - N0>([&](auto N) {
        constexpr int n = N0 + N.value;
        asm("{\n.reg .pred p;\n.reg .b32 t;\nand.b32 t, %4, %5;\nsetp.ne.u32 p, t, 0;\nselp.b32 %0, %2, 0, p;\nselp.b32 %1, %3, 0, p;\n}\n"
            : "=r"(p[2 * n]), "=r"(p[2 * n + 1]) : "r"(y[2 * n]), "r"(y[2 * n + 1]), "r"(fold), "n"(1 << (BIT0 + n)));
    });
}
__device__ __forceinline__ void keep(bool never, uint32_t a, uint32_t b, uint32_t c, uint32_t d) {
    asm volatile("{\n.reg .pred p;\nsetp.ne.u32 p, %4, 0;\n@p st.volatile.shared.v4.u32 [%5], {%0, %1, %2, %3};\n}\n"
                 ::"r"(a), "r"(b), "r"(c), "r"(d), "r"((uint32_t)never), "r"(s_trace) : "memory");
}

__device__ __forceinline__ uint32_t wimg_offset(uint32_t row, uint32_t s, uint32_t j) {
    return (s >> 2) * kWChunk + row * 128 + (((2 * (s & 3) + (j >> 1)) ^ (row & 7)) << 4) + (j & 1) * 8;
}

__device__ __forceinline__ void ldsm4(uint32_t (&r)[4], uint32_t addr) {
    asm volatile("ldmatrix.sync.aligned.m8n8.x4.shared.b16 {%0, %1, %2, %3}, [%4];" : "=r"(r[0]), "=r"(r[1]), "=r"(r[2]), "=r"(r[3]) : "r"(addr) : "memory");
}
__device__ __forceinline__ void ldsm4_t(uint32_t (&r)[4], uint32_t addr) {
    asm volatile("ldmatrix.sync.aligned.m8n8.x4.trans.shared.b16 {%0, %1, %2, %3}, [%4];" : "=r"(r[0]), "=r"(r[1]), "=r"(r[2]), "=r"(r[3]) : "r"(addr) : "memory");
}
__device__ __forceinline__ void m_partial(const uint8_t* wqkv, uint32_t mt, uint32_t s, uint32_t q, uint32_t lane, uint32_t zero) {
    const uint32_t r8 = lane >> 2, col = q * 128 + (lane & 3) * 16;
    const uint8_t* pa = wqkv + (16 * mt + r8) * 1152 + col;
    const uint8_t* pb = wqkv + (16 * s + 8 * (r8 & 2) + (r8 & 5)) * 1152 + col;
    uint4 A[2][2], B[4][2];
#pragma unroll
    for (int c = 0; c < 2; c++) {
#pragma unroll
        for (int h = 0; h < 2; h++) A[h][c] = ldg(pa + 384 + h * 8 * 1152 + c * 64);
#pragma unroll
        for (int n = 0; n < 4; n++) B[n][c] = ldg(pb + ((n & 1) * 8 + (n & 2)) * 1152 + c * 64);
    }
#pragma unroll
    for (int i = 0; i < 4; i++) { uint4& a = A[i >> 1][i & 1]; a.x ^= zero; a.y ^= zero; a.z ^= zero; a.w ^= zero; }
#pragma unroll
    for (int n = 0; n < 4; n++) {
        float d[4] = {0.f, 0.f, 0.f, 0.f};
#pragma unroll
        for (int c = 0; c < 2; c++) {
            mma16816(d, A[0][c].x, A[1][c].x, A[0][c].y, A[1][c].y, B[n][c].x, B[n][c].y);
            mma16816(d, A[0][c].z, A[1][c].z, A[0][c].w, A[1][c].w, B[n][c].z, B[n][c].w);
        }
        asm volatile("st.shared.v4.f32 [%0], {%1, %2, %3, %4};" ::"r"(s_wv + q * 2048 + n * 512 + lane * 16), "f"(d[0]), "f"(d[1]), "f"(d[2]), "f"(d[3]) : "memory");
    }
}
__device__ __forceinline__ void m_reduce(uint32_t e, uint32_t lane, float (&d)[2][4]) {
#pragma unroll
    for (int n = 0; n < 2; n++) {
        float t[3][4];
#pragma unroll
        for (int q = 0; q < 3; q++)
            asm volatile("ld.shared.v4.f32 {%0, %1, %2, %3}, [%4];" : "=f"(t[q][0]), "=f"(t[q][1]), "=f"(t[q][2]), "=f"(t[q][3]) : "r"(s_wv + q * 2048 + e * 1024 + n * 512 + lane * 16) : "memory");
#pragma unroll
        for (int i = 0; i < 4; i++) d[n][i] = (t[0][i] + t[1][i] + t[2][i]) * kScaleLog2e;
    }
}
__device__ __forceinline__ void w_piece(uint32_t q, uint32_t lane, float (&d)[2][4]) {
    const uint32_t rr = lane & 7, mi = lane >> 3, kr = 4 * (rr >> 1) + (mi & 2) + (rr & 1);
    const uint32_t pa = s_wv + q * 32 + (4 * (mi & 2) + rr) * 96 + ((mi & 1) << 4);
    const uint32_t pb = s_wv + 3 * 6144 + kr * 128 + (((mi & 1) ^ (kr & 7)) << 4);
    float e[2][4];
#pragma unroll
    for (int i = 0; i < 8; i++) (&d[0][0])[i] = (&e[0][0])[i] = 0.f;
#pragma unroll
    for (int k = 0; k < 12; k++) {
        uint32_t aq[4], bq[4];
        ldsm4_t(aq, pa + k * 1536);
        ldsm4(bq, (pb ^ ((k & 3) << 5)) + (k >> 2) * 2048);
        mma16816(k & 1 ? e[0] : d[0], aq[0], aq[1], aq[2], aq[3], bq[0], bq[1]);
        mma16816(k & 1 ? e[1] : d[1], aq[0], aq[1], aq[2], aq[3], bq[2], bq[3]);
    }
#pragma unroll
    for (int i = 0; i < 8; i++) (&d[0][0])[i] += (&e[0][0])[i];
}
__device__ __forceinline__ uint32_t piece_offset(uint32_t which, uint32_t s, uint32_t mt, uint32_t lane) {
    const uint32_t r8 = lane >> 2;
    return which * kWBytes + wimg_offset(which ? 32 * (mt >> 1) + 8 * (r8 >> 1) + 4 * (mt & 1) + (r8 & 1) : 16 * mt + r8, s, lane & 3);
}
__device__ __forceinline__ void piece_store(Scratch* g, uint32_t par, uint32_t off0, uint32_t which, const float (&d)[2][4]) {
#pragma unroll
    for (int hf = 0; hf < 2; hf++) {
        const uint32_t off = off0 ^ (hf ? which ? 288 : 1024 : 0);
        const uint32_t a = pack_bf16(d[0][2 * hf], d[0][2 * hf + 1]), b = pack_bf16(d[1][2 * hf], d[1][2 * hf + 1]);
        asm volatile("st.relaxed.gpu.global.v2.u32 [%0], {%1, %2};" ::"l"(g->img[0][0] + (par + off)), "r"(a ? a : 0x8000u), "r"(b) : "memory");
    }
}
__device__ __forceinline__ void piece_clear(Scratch* g, uint32_t par, uint32_t off0, uint32_t which) {
#pragma unroll
    for (int hf = 0; hf < 2; hf++)
        asm volatile("st.relaxed.gpu.global.v2.u32 [%0], {%1, %1};" ::"l"(g->img[0][0] + (par + (off0 ^ (hf ? which ? 288 : 1024 : 0)))), "r"(0) : "memory");
}

__device__ __forceinline__ uint32_t ld_relaxed(const uint32_t* p) {
    uint32_t v;
    asm volatile("ld.relaxed.gpu.global.u32 %0, [%1];" : "=r"(v) : "l"(p) : "memory");
    return v;
}
__device__ __forceinline__ void count_up(uint32_t* p) {
    asm volatile("red.relaxed.gpu.global.add.u32 [%0], %1;" ::"l"(p), "r"(1) : "memory");
}
__device__ __forceinline__ void bulk_g2s(uint32_t dst, const void* src, uint32_t bytes, uint32_t bar) {
    asm volatile("cp.async.bulk.shared::cluster.global.mbarrier::complete_tx::bytes [%0], [%1], %2, [%3];"
                 ::"r"(dst), "l"(src), "r"(bytes), "r"(bar)
                 : "memory");
}

__global__ void __launch_bounds__(kThreads, 1)
nat_fused_kernel(const uint8_t* __restrict__ x, const uint8_t* __restrict__ wqkv, uint8_t* __restrict__ out, Scratch* g,
                 const uint8_t* wo, uint64_t dsc, const __grid_constant__ Maps maps) {
    const int tid = threadIdx.x, lane = tid & 31;
    const int warp = __shfl_sync(0xffffffffu, tid >> 5, 0);
    const int wg = warp >> 2, wq = warp & 3, r8 = lane >> 2, j = lane & 3;
    const int cta = blockIdx.x;
    const Work w = decode_work(cta);
    const uint32_t jq = (cta < 124 ? cta + 8 : cta - 124) / 11u, jr = (cta < 124 ? cta + 8 : cta - 124) - 11 * jq;
    const uint32_t which = jr >= 6, jhi = which ? jr - 6 : jq, jlo = which ? jq : 2 * jr;
    const bool has_job = jr < 10;
    if (wg == 2 && wq < 3) {
#pragma unroll
        for (int r = 0; r < 3; r++)
            asm volatile("st.shared.v4.u32 [%0], {%1, %1, %1, %1};" ::"r"(s_ring + wq * kRingChunk + (r == 0 ? 84 : r == 1 ? 88 : 204) * 128 + lane * 16), "r"(0) : "memory");
        asm volatile("fence.proxy.async.shared::cta;" ::: "memory");
    }
    if (x == nullptr) return;
    const uint32_t t_start = clock_now();
    if (wg == 2) {
        asm volatile("setmaxnreg.dec.sync.aligned.u32 24;");
        if (wq < 3) {
            if (lane < 3 && cta < 128) {
                const uint32_t row = 3 * (cta >> 1) + wq;
                asm volatile("prefetch.global.L2 [%0];" ::"l"((cta & 1 ? wo + row * 384 : wqkv + row * 1152 + 768) + lane * 128));
            }
            asm volatile("bar.sync 7, 192;" ::: "memory");
            const uint32_t par = lds_volatile(s_par);
            uint32_t phase = 0;
#pragma unroll 1
            for (uint32_t c = 0; c < 6; c++) {
                const uint32_t part = c * kWChunk + wq * (kWChunk / 3), img = 8 * min(c, 3u);
                mbar_wait(bar_img + 8 * c, 0);
                if (SPEC && c == 0 && lane == 0) mbar_arrive(bar_ok);
                if (wq == 0) TRW(10 + c);
#pragma unroll 1
                while (true) {
                    uint32_t lo = ~0u;
#pragma unroll
                    for (int q = 0; q < 8; q++) lo = min(lo, lds_volatile(s_m + part + lane * 32 + (lane & 12) * 2 + q * 1024));
                    if (__all_sync(0xffffffffu, lo) || phase > 65535) break;
                    if (elect()) {
                        mbar_expect_tx(bar_redo + 8 * wq, kWChunk / 3);
                        bulk_g2s(s_m + part, g->img[0][0] + par + part, kWChunk / 3, bar_redo + 8 * wq);
                    }
                    mbar_wait(bar_redo + 8 * wq, phase++ & 1);
                }
                if (c == 2 && phase) asm volatile("st.shared.u32 [%0], %1;" ::"r"(s_again), "r"(1) : "memory");
                if ((c == 2 || c == 5) && lane == 0) mbar_arrive(bar_ok + img);
            }
        } else {
            uint32_t launch = ld_relaxed(&g->launches);
            const CUtensorMap* map = &maps.m[w.sv == kPixBytes ? 2 : 0];
            if (elect()) {
#pragma unroll
                for (int i = 0; i < 20; i++) mbar_init(s_bar + 8 * i, i < 13 ? 1 : i < 18 ? 3 : 4);
                asm volatile("fence.mbarrier_init.release.cluster;" ::: "memory");
                prefetch_map(map + 1);
                expect_tx_only(bar_a, sizeof(Table));
                bulk_g2s(s_tab, &maps.tables->t[w.step < 0], sizeof(Table), bar_a);
            }
            if (which && has_job && elect()) {
                mbar_expect_tx(bar_wop, 4 * 6144);
                tma_3d(s_wv, &maps.wo, bar_wop, 0, jhi);
                tma_3d(s_wv + 3 * 6144, &maps.wv, bar_wop, 16 * jlo, 6);
            }
            int u = w.u, v = w.v;
            uint32_t wait_bar = bar_use, wait_par = 1, slot = 0;
#pragma unroll 1
            for (int step = 0; step < 7 - w.corner; step++) {
                const bool first = step == 0 || (w.corner && step == 4);
                const int row = v + 4 + (first ? -w.step : w.step) / 2, ou = origin_u(u);
                uint32_t dst = s_ring + (first ? 0 : slot), mid = s_ring + kOffMid + 512, bar = first ? bar_a : bar_b;
                mbar_wait(wait_bar, wait_par);
                TRW(24 + step);
#pragma unroll 1
                for (int ch = (cta & 1) * kC; mid < s_m; ch += 64, dst += kRingChunk, mid += kRingChunk) {
                    if (elect()) {
                        mbar_expect_tx(bar, first ? kSlotBytes : kSlotBytes + kMidBytes);
                        tma_box(dst, map, bar, ch, ou, (cta >> 1) & 1, row);
                    }
                    if (!first) {
                        if (elect()) tma_box(mid, map + 1, bar, ch, ou, (cta >> 1) & 1, v + 6);
                        bar += 8;
                    }
                }
                if (step == 0) {
                    launch /= kGrid;
                    asm volatile("st.shared.v4.u32 [%0], {%1, %2, %2, %2};" ::"r"(s_par), "r"((launch & 1) * 2 * kWBytes), "r"(0) : "memory");
                    asm volatile("bar.arrive 5, 128;\nbar.arrive 3, 160;\nbar.arrive 4, 160;" ::: "memory");
                }
                if (step < 2) {
                    if (step) {
                        if (lane == 0) count_up(&g->launches);
                        asm volatile("bar.sync 6, 128;" ::: "memory");
                    }
                    wait_until(t_start, step ? TN(5, kTimeW) : TN(6, kTimeM));
                    TRW(5 + 4 * step);
#pragma unroll 1
                    for (int c = 3 * step; c < 3 + 3 * step; c++)
                        if (elect()) {
                            mbar_expect_tx(bar_img + 8 * c, kWChunk);
                            bulk_g2s(s_m + c * kWChunk, g->img[launch & 1][0] + c * kWChunk, kWChunk, bar_img + 8 * c);
                        }
                }
                const bool again = w.corner && step == 3;
                wait_bar = step == 0 ? bar_img + 8 * TN(1, 1) : again ? bar_use + 8 : bar_use;
                if (!again) {
                    wait_par = slot ? 0 : step != 0;
                    slot ^= kSlotStride;
                    if (w.corner && step == 2) { u += 8; v -= 8; } else if (step) v += w.step;
                }
            }
        }
        TRDUMP();
        return;
    }
    if (wg == 1 && wq < 3) {
        if (!which) m_partial(wqkv, jhi, jlo, wq, lane, (uint32_t)dsc & 1);
        const uint32_t off = piece_offset(which, which ? jlo : jlo + wq, which ? 3 * jhi + wq : jhi, lane);
        asm volatile("bar.sync %0, 128;" ::"r"(5 + (off >> 31)) : "memory");
        const uint32_t par = lds_volatile(s_par);
        if (has_job && wq < 2 + which) {
            float d[2][4];
            if (wq == 0) TRX(which ? 1 : 18);
            if (which) {
                mbar_wait(bar_wop, 0);
                if (wq == 0) TRX(2);
                w_piece(wq, lane, d);
            } else {
                m_reduce(wq, lane, d);
            }
            piece_store(g, par, off, which, d);
            __syncwarp();
            piece_clear(g, 2 * kWBytes - par, off, which);
            if (wq == 0) TRX(which ? 3 : 0);
        }
        asm volatile("bar.arrive 7, 192;\nbar.arrive 6, 128;" ::: "memory");
    }
    const int order = w.step < 0 ? warp ^ 3 : warp;
    int tu = w.u, tv = w.v + w.step * wg;
    const int du2 = w.corner ? 8 : 0, dv2 = w.corner ? 0 : 2 * w.step;
    uint32_t o0, o1;
    wait_until(t_start, START_TIME);
    asm volatile("setmaxnreg.inc.sync.aligned.u32 240;");
    w.pixel_offsets(tu + r8, tv + 2 * wq, j, o0, o1);
    uint32_t fa[48];
    {
        RawX raw;
        load_raw(raw, x, o0, o1);
        asm volatile("bar.sync %0, 160;" ::"r"(3 + wg) : "memory");
        raw_to_frags(raw, 0, fa);
        pin(fa);
    }
    mbar_wait(bar_ok, 0);
    const uint64_t dA = dsc + wg * (kSlotStride >> 4), dB = dsc + (wg ^ 1) * (kSlotStride >> 4);

    float acc[96];
    uint32_t po[48];
    uint32_t c0, c1;
    asm volatile("" : "=r"(c0), "=r"(c1));
#pragma unroll
    for (int q = 0; q < 48; q++) asm volatile("" : "=r"(po[q]));
#pragma unroll 1
    for (int i = wg; i < w.ntiles; i += 2) {
        const bool first = i == 0, last = i == w.ntiles - 1;

        TRF(8 + 16 * k);
        uint8_t *p0 = out + c0, *p1 = out + c1;
#pragma unroll 1
        for (uint32_t seen = 0;;) {
        wg_fence();
        if (!first) turn_wait(wg);
        proj_gemm(acc, fa, dsc, s_m, [&](int s) {
            if (s == 11 && !first) turn_pass(wg);
            const int n = __builtin_popcount(QSLOTS & ((1 << s) - 1));
            if (((QSLOTS >> s) & 1) && n < 12) store_one(i >= 2, out + c0, out + c1, po, n);
            if (s == 3 || s == 7) { mbar_wait((SPEC ? bar_img : bar_ok) + 2 * s + 2, 0); wg_fence(); }
        });
        __syncwarp();
        TRF(9 + 16 * k);
            if (!first) break;
            mbar_wait(bar_ok + 16, 0);
            if (lds_volatile(s_again) == seen) break;
            wg_wait<0>();
            seen = 1;
        }
        c0 = o0; c1 = o1;
        w.pixel_offsets(tu + du2 + r8, tv + dv2 + 2 * wq, j, o0, o1);
        if (i + 2 >= w.ntiles) o0 = o1 = 0;
        wg_wait<0>();
        pin(acc);
        TR(11 + 16 * k);
        TRT(80 + k);
#pragma unroll
        for (int n = __builtin_popcount(QSLOTS); n < 12 - __builtin_popcount(ASLOTS) - __builtin_popcount(BSLOTS); n++) store_one(i >= 2, p0, p1, po, n);
        acc_to_frags(acc, fa);
        pin(fa);

        float sA[44], sE[16], sB[44];
        RawX nxt;
        if (!first) turn_wait(wg);
        mbar_wait(bar_a, w.corner ? i >> 1 : 0);
        if (i == 0) TR(12);
        wg_fence();
#pragma unroll
        for (int s = 0; s < 12; s++) {
            if (s == 0) wgmma_n88<true>(sA, fa[4 * s], fa[4 * s + 1], fa[4 * s + 2], fa[4 * s + 3], desc_at(dA, (s >> 2) * kRingChunk + (s & 3) * 32));
            else wgmma_n88<false>(sA, fa[4 * s], fa[4 * s + 1], fa[4 * s + 2], fa[4 * s + 3], desc_at(dA, (s >> 2) * kRingChunk + (s & 3) * 32));
            if (s == 11) { wg_commit(); if (!first) turn_pass(wg); }
            if ((ASLOTS >> s) & 1) store_one(i >= 2, p0, p1, po, 12 - __builtin_popcount(BSLOTS) - __builtin_popcount(ASLOTS >> s));
        }
#pragma unroll
        for (int s = 12; s < 16; s++)
            if ((ASLOTS >> s) & 1) store_one(i >= 2, p0, p1, po, 12 - __builtin_popcount(BSLOTS) - __builtin_popcount(ASLOTS >> s));
        TRF(12 + 16 * k);
        const int vq = tv + 2 * wq;
        const uint4 tabu = lds128(s_tab + offsetof(Table, u) + (window_start(tu + r8) - origin_u(tu)) * 64 + j * 16);
        const uint4 tabv = lds128(s_tab + offsetof(Table, v) + (window_start(vq) + window_start(vq + 1) - 2 * tv) * 64 + j * 16);
        const uint4 route = lds128(s_tab + lane * 16);
        if (LDGLATE == 0) load_raw(nxt, x, o0, o1);
        float v0[14], v1[14];
#pragma unroll
        for (int b = 0; b < 14; b++) v0[b] = v1[b] = __int_as_float(0xff800000);
        wg_wait<0>();
        pin(sA);
        gather_outer(sA, tabu.x, tabv.x, v0, v1);
        pin(v0); pin(v1);
        if (!first) turn_wait(wg);
#pragma unroll
        for (int c = 0; c < 3; c++) {
            mbar_wait(bar_b + 8 * c, wg);
            if (i == 0 && c != 1) TR(13 + c);
            wg_fence();
#pragma unroll
            for (int s = 4 * c; s < 4 * c + 4; s++) {
                if (s == 0) wgmma_n88<true>(sB, fa[4 * s], fa[4 * s + 1], fa[4 * s + 2], fa[4 * s + 3], desc_at(dB, c * kRingChunk + (s & 3) * 32));
                else wgmma_n88<false>(sB, fa[4 * s], fa[4 * s + 1], fa[4 * s + 2], fa[4 * s + 3], desc_at(dB, c * kRingChunk + (s & 3) * 32));
                if (LDGLATE == s + 1) load_raw(nxt, x, o0, o1);
                if ((BSLOTS >> s) & 1) store_one(i >= 2, p0, p1, po, 12 - __builtin_popcount(BSLOTS >> s));
            }
        }
        wg_commit();
#pragma unroll
        for (int s = 0; s < 12; s++)
            if (s == 0) wgmma_n32<true>(sE, fa[4 * s], fa[4 * s + 1], fa[4 * s + 2], fa[4 * s + 3], desc_at(dsc, kOffMid + (s >> 2) * kRingChunk + (s & 3) * 32));
            else wgmma_n32<false>(sE, fa[4 * s], fa[4 * s + 1], fa[4 * s + 2], fa[4 * s + 3], desc_at(dsc, kOffMid + (s >> 2) * kRingChunk + (s & 3) * 32));
        wg_commit();
        if (OSPLIT || !last) turn_pass(wg);
        TRF(13 + 16 * k);
        wg_wait<1>();
        pin(sB);
        gather_outer(sB, tabu.w, tabv.y, v0, v1);
        wg_wait<0>();
        pin(sE);
        TRF(14 + 16 * k);
        gather_mid(sE, tabu.w, tabv.z, v0, v1);
        const float m0 = quad_max(tree_max(v0)), m1 = quad_max(tree_max(v1));

        uint32_t y[14], pa[12], pb[12];
        exp_route<0, 14>(v0, v1, m0, m1, route, (j & 1) == 0, y);
        float s0 = tree_sum(v0), s1 = tree_sum(v1);
        asm volatile("" : "+f"(s0), "+f"(s1));
        unfold<0, 0, 6>(y, tabv.w, pa);
        if (OSPLIT || !last) turn_wait(wg + (y[0] >> 31));
        TRF(15 + 16 * k + (y[13] >> 31));
        wg_fence();
        wgmma_sp_n192_tb<true, 0>(acc, pa[0], pa[1], pa[2], pa[3], desc_at(dA, kToV), tabu.y);
        wgmma_sp_n192_tb<false, 1>(acc, pa[4], pa[5], pa[6], pa[7], desc_at(dA, kToV + 4096), tabu.y);
        wgmma_sp_n192_tb<false, 0>(acc, pa[8], pa[9], pa[10], pa[11], desc_at(dA, kToV + 8192), tabu.z);
        wgmma_sp_n192_tb<false, 1>(acc, y[10], y[11], y[12], y[13], desc_at(dsc, kToV + kOffMid), tabu.z);
        wg_commit();
        unfold<8, 0, 6>(y, tabv.w, pb);
        wg_fence();
        wgmma_sp_n192_tb<false, 0>(acc, pb[0], pb[1], pb[2], pb[3], desc_at(dB, kToV), tabu.y);
        wgmma_sp_n192_tb<false, 1>(acc, pb[4], pb[5], pb[6], pb[7], desc_at(dB, kToV + 4096), tabu.y);
        wgmma_sp_n192_tb<false, 0>(acc, pb[8], pb[9], pb[10], pb[11], desc_at(dB, kToV + 8192), tabu.z);
        wg_commit();
        if (!last) turn_pass(wg);
        TRF(16 + 16 * k);
        wg_wait<1>();
        if (lane == 0) mbar_arrive(bar_use);
        TRF(17 + 16 * k);
        mbar_wait(bar_ok + 24, 0);
        wg_wait<0>();
        if (lane == 0) mbar_arrive(bar_use + 8);
        pin(acc);
        TR(18 + 16 * k);

        acc_to_frags(acc, po);
        pin(po);
        if (!last) turn_wait(wg);
        wg_fence();
        proj_gemm(acc, po, dsc, s_wv, [&](int s) {
            if (s + 1 == OSPLIT && i + 2 == w.ntiles) { turn_pass(wg); turn_wait(wg); }
        });
        if (!last) turn_pass(wg);
        TRF(19 + 16 * k);
        const uint32_t zero = lds_volatile(s_late);
        const float inv0 = rcp(quad_sum(s0 + __uint_as_float(zero))), inv1 = rcp(quad_sum(s1 + __uint_as_float(zero)));
        raw_to_frags(nxt, zero, fa);
        pin(fa);
#pragma unroll
        for (int q = 0; q < 48; q += 4) keep(wqkv == nullptr, fa[q], fa[q + 1], fa[q + 2], fa[q + 3]);
        keep(wqkv == nullptr, __float_as_uint(inv0), __float_as_uint(inv1), zero, lane);
        TRF(20 + 16 * k);
        tu += du2; tv += dv2;
        wg_wait<0>();
        pin(acc);
        TR(21 + 16 * k);
#pragma unroll
        for (int q = 0; q < 96; q++) acc[q] *= q & 2 ? inv1 : inv0;
        pack_out(acc, po);
#pragma unroll
        for (int n = 0; n < INLOOP; n++) store_one<false>(last, out + c0, out + c1, po, n);
        pin(po);
    }
#pragma unroll
    for (int n = 0; n < 12; n++) {
        asm volatile("{\n.reg .pred p;\nsetp.eq.u32 p, %0, 0;\n@p nanosleep.u32 %1;\n}\n" ::"r"(wg), "n"(NAP) : "memory");
        store_one<false>(n >= INLOOP || wg == 0, out + c0, out + c1, po, n);
    }
    TRE(7);
    TRG(1);
    TRDUMP();
}

typedef CUresult (*EncodeTiledFn)(CUtensorMap*, CUtensorMapDataType, cuuint32_t, void*, const cuuint64_t*, const cuuint64_t*,
                                  const cuuint32_t*, const cuuint32_t*, CUtensorMapInterleave, CUtensorMapSwizzle,
                                  CUtensorMapL2promotion, CUtensorMapFloatOOBfill);

bool make_maps(EncodeTiledFn fn, Maps* maps, void* x, void* wqkv, void* wo) {
    const cuuint64_t pix2 = 2 * kPixBytes, row = (cuuint64_t)kHW * kPixBytes;
    const cuuint32_t estr[5] = {1, 1, 1, 1, 1};
    bool ok = true;
    for (int tr = 0; tr < 2; tr++)
        for (int b = 0; b < 2; b++) {
            const cuuint64_t su = tr ? 2 * row : pix2, sv = tr ? pix2 : 2 * row;
            const cuuint64_t dims[5] = {2 * kC, 2, 105, 2, 112};
            const cuuint64_t strides[4] = {7 * su, su, row, sv};
            const cuuint32_t box[5] = {64, 2, 7, 1, b ? 2u : 6u};
            ok = ok && fn(&maps->m[2 * tr + b], CU_TENSOR_MAP_DATA_TYPE_BFLOAT16, 5, x, dims, strides, box, estr,
                          CU_TENSOR_MAP_INTERLEAVE_NONE, CU_TENSOR_MAP_SWIZZLE_128B, CU_TENSOR_MAP_L2_PROMOTION_L2_128B,
                          CU_TENSOR_MAP_FLOAT_OOB_FILL_NONE) == CUDA_SUCCESS;
        }
    for (int b = 0; b < 2; b++) {
        const cuuint64_t dims[3] = {b ? 64u : 48u, kC, b ? 9u : 4u}, strides[2] = {(b ? 3u : 1u) * kPixBytes, b ? 128u : 96u};
        const cuuint32_t box[3] = {b ? 64u : 48u, b ? 16u : 192u, b ? 3u : 1u};
        ok = ok && fn(b ? &maps->wv : &maps->wo, CU_TENSOR_MAP_DATA_TYPE_BFLOAT16, 3, b ? wqkv : wo, dims, strides, box, estr,
                      CU_TENSOR_MAP_INTERLEAVE_NONE, b ? CU_TENSOR_MAP_SWIZZLE_128B : CU_TENSOR_MAP_SWIZZLE_NONE, CU_TENSOR_MAP_L2_PROMOTION_L2_128B,
                      CU_TENSOR_MAP_FLOAT_OOB_FILL_NONE) == CUDA_SUCCESS;
    }
    return ok;
}

}

extern "C" void kernel_launch(void* const* d_in, const int* in_sizes, int n_in, void* d_out, int out_size) {
    static EncodeTiledFn encode = nullptr;
    static Scratch* scratch = nullptr;
    static Tables* tables = nullptr;
    if (!encode) {
        int dev = 0, reserved = 0;
        cudaFuncAttributes attr;
        cudaGetDevice(&dev);
        cudaDeviceGetAttribute(&reserved, cudaDevAttrReservedSharedMemoryPerBlock, dev);
        cudaFuncGetAttributes(&attr, nat_fused_kernel);
        if (reserved != (int)kSmemBase || attr.sharedSizeBytes != 0) return;
        cudaGetSymbolAddress((void**)&scratch, g_scratch);
        cudaGetSymbolAddress((void**)&tables, g_tables);
        void* fn = nullptr;
        cudaDriverEntryPointQueryResult st;
        cudaGetDriverEntryPoint("cuTensorMapEncodeTiled", &fn, cudaEnableDefault, &st);
        encode = (EncodeTiledFn)fn;
        cudaFuncSetAttribute(nat_fused_kernel, cudaFuncAttributeMaxDynamicSharedMemorySize, kSmemBytes);
    }
    Maps maps;
    maps.tables = tables;
    if (!encode || !make_maps(encode, &maps, d_in[0], d_in[1], d_in[2])) return;
    nat_fused_kernel<<<kGrid, kThreads, kSmemBytes>>>((const uint8_t*)d_in[0], (const uint8_t*)d_in[1], (uint8_t*)d_out, scratch, (const uint8_t*)d_in[2],
                                                      kDescRing, maps);
}
```

```cpp
#include <cuda_runtime.h>
#include <cuda_bf16.h>
#include <cuda.h>
#include <stdint.h>
#include <type_traits>
#include <stdlib.h>
#include <stddef.h>

#define KEEPFA 1
#define ASLOTS 0x3800
#define BSLOTS 0x6
#define QSLOTS 0x78a
#define OSPLIT 3
#define NAP 40
#define SPEC 1
#define INLOOP 3

namespace {

constexpr int kC          = 192;
constexpr int kHW         = 224;
constexpr int kPixBytes   = kC * 2;
constexpr int kSlotBytes  = 84 * 128;
constexpr int kMidBytes   = 28 * 128;
constexpr int kOffMid     = 88 * 128;
constexpr int kSlotStride = 120 * 128;
constexpr int kRingChunk  = 208 * 128;
constexpr int kWChunk     = 192 * 128;
constexpr int kWBytes     = 3 * kWChunk;
constexpr uint32_t kSmemBase = 1024;
constexpr uint32_t s_ring = kSmemBase, s_m = s_ring + 3 * kRingChunk, s_wv = s_m + kWBytes, s_bar = s_wv + kWBytes;
constexpr uint32_t bar_b = s_bar, bar_img = s_bar + 24, bar_redo = s_bar + 72, bar_wop = s_bar + 96, bar_a = s_bar + 104,
                   bar_ok = s_bar + 112, bar_use = s_bar + 144;
constexpr uint32_t s_par = s_bar + 160, s_late = s_bar + 164, s_again = s_bar + 168, s_tab = s_bar + 256, s_trace = s_tab + 2048;
constexpr int kSmemBytes  = s_trace + 2048 - kSmemBase;
constexpr int kThreads    = 384;
constexpr int kGrid       = 132;
constexpr int kTimeM = 2600, kTimeW = 5100;
constexpr float kScaleLog2e = 0.07216878364870322f * 1.4426950408889634f;

struct Maps {
    CUtensorMap m[4];
    CUtensorMap wo, wv;
    const struct Tables* tables;
};
#define TN(i, dflt) (dflt)
#define START_TIME (wg ? 850 + 500 * order : 250 + 560 * order)

struct Scratch {
    uint8_t img[2][2][kWBytes];
    uint32_t launches;
};
__device__ __align__(1024) Scratch g_scratch;

struct Table {
    uint32_t route[32][4];
    uint32_t u[8][4][4];
    uint32_t v[16][4][4];
};
struct Tables { Table t[2]; };
constexpr Tables make_tables() {
    Tables r = {};
    for (int rev = 0; rev < 2; rev++)
        for (int j = 0; j < 4; j++) {
            Table& t = r.t[rev];
            for (int q = 0; q < 8; q++) {
                uint32_t* e = t.route[4 * q + j];
                e[0] = 4 * q + 2 * (j & 1) + (j >> 1); e[1] = e[0] ^ 1;
                e[2] = j < 2 ? 0x5410u : 0x1054u; e[3] = e[2] + 0x2222u;
                e = t.u[q][j];
                for (int n = 0; n < 7; n++) e[0] |= ((n + j) % 7 < q ? 1u : 0u) << n;
                e[3] = e[0];
                for (int k = 0; k < 2; k++) {
                    const int step = 2 * k + (j >> 1), p0 = (step < 3 ? 16 * step : 40) + 8 * (j & 1);
                    uint32_t m = 0x8888u;
                    for (int n = 0; n < 8; n++) m |= ((p0 + n) % 7 < q ? 1u : 0u) << (2 * n);
                    e[1 + k] = m * 0x10001u;
                }
            }
            for (int sum = 0; sum < 15; sum++) {
                uint32_t* e = t.v[sum][j];
                for (int row = 0; row < 2; row++)
                    for (int b = 0; b < 14; b++) {
                        const int off = (sum + row) / 2, p = 4 * b + j;
                        const uint32_t bit = 1u << (2 * b + row);
                        if (p < 42 && p >= 7 * off) e[rev] |= bit;
                        if (p < 7 * off - 7) e[1 - rev] |= bit;
                        if (p >= 42 && p >= 7 * off && p < 7 * off + 49) e[2] |= bit;
                    }
                for (int n = 0; n < 6; n++)
                    if (8 * n + 2 * j < 42) e[3] |= 1u << (n + ((8 * n + 2 * j >= 7 * (sum / 2 & ~1)) != rev ? 0 : 8));
            }
        }
    return r;
}
__device__ __align__(128) const Tables g_tables = make_tables();

#define WO4(i) "=f"(d[i]), "=f"(d[i + 1]), "=f"(d[i + 2]), "=f"(d[i + 3])
#define RW4(i) "+f"(d[i]), "+f"(d[i + 1]), "+f"(d[i + 2]), "+f"(d[i + 3])

template <bool FIRST>
__device__ __forceinline__ void wgmma_n192(float (&d)[96], uint32_t a0, uint32_t a1, uint32_t a2, uint32_t a3, uint64_t descb) {
    if constexpr (FIRST) {
        asm volatile(
            "wgmma.mma_async.sync.aligned.m64n192k16.f32.bf16.bf16 "
            "{%0, %1, %2, %3, %4, %5, %6, %7, %8, %9, %10, %11, %12, %13, %14, %15, %16, %17, %18, %19, %20, %21, %22, %23, "
            "%24, %25, %26, %27, %28, %29, %30, %31, %32, %33, %34, %35, %36, %37, %38, %39, %40, %41, %42, %43, %44, %45, %46, %47, "
            "%48, %49, %50, %51, %52, %53, %54, %55, %56, %57, %58, %59, %60, %61, %62, %63, %64, %65, %66, %67, %68, %69, %70, %71, "
            "%72, %73, %74, %75, %76, %77, %78, %79, %80, %81, %82, %83, %84, %85, %86, %87, %88, %89, %90, %91, %92, %93, %94, %95}, "
            "{%96, %97, %98, %99}, %100, 0, 1, 1, 0;"
            : WO4(0), WO4(4), WO4(8), WO4(12), WO4(16), WO4(20), WO4(24), WO4(28), WO4(32), WO4(36), WO4(40), WO4(44),
              WO4(48), WO4(52), WO4(56), WO4(60), WO4(64), WO4(68), WO4(72), WO4(76), WO4(80), WO4(84), WO4(88), WO4(92)
            : "r"(a0), "r"(a1), "r"(a2), "r"(a3), "l"(descb));
    } else {
        asm volatile(
            "wgmma.mma_async.sync.aligned.m64n192k16.f32.bf16.bf16 "
            "{%0, %1, %2, %3, %4, %5, %6, %7, %8, %9, %10, %11, %12, %13, %14, %15, %16, %17, %18, %19, %20, %21, %22, %23, "
            "%24, %25, %26, %27, %28, %29, %30, %31, %32, %33, %34, %35, %36, %37, %38, %39, %40, %41, %42, %43, %44, %45, %46, %47, "
            "%48, %49, %50, %51, %52, %53, %54, %55, %56, %57, %58, %59, %60, %61, %62, %63, %64, %65, %66, %67, %68, %69, %70, %71, "
            "%72, %73, %74, %75, %76, %77, %78, %79, %80, %81, %82, %83, %84, %85, %86, %87, %88, %89, %90, %91, %92, %93, %94, %95}, "
            "{%96, %97, %98, %99}, %100, 1, 1, 1, 0;"
            : RW4(0), RW4(4), RW4(8), RW4(12), RW4(16), RW4(20), RW4(24), RW4(28), RW4(32), RW4(36), RW4(40), RW4(44),
              RW4(48), RW4(52), RW4(56), RW4(60), RW4(64), RW4(68), RW4(72), RW4(76), RW4(80), RW4(84), RW4(88), RW4(92)
            : "r"(a0), "r"(a1), "r"(a2), "r"(a3), "l"(descb));
    }
}

template <bool FIRST>
__device__ __forceinline__ void wgmma_n88(float (&d)[44], uint32_t a0, uint32_t a1, uint32_t a2, uint32_t a3, uint64_t descb) {
    if constexpr (FIRST) {
        asm volatile(
            "wgmma.mma_async.sync.aligned.m64n88k16.f32.bf16.bf16 "
            "{%0, %1, %2, %3, %4, %5, %6, %7, %8, %9, %10, %11, %12, %13, %14, %15, %16, %17, %18, %19, %20, %21, %22, %23, "
            "%24, %25, %26, %27, %28, %29, %30, %31, %32, %33, %34, %35, %36, %37, %38, %39, %40, %41, %42, %43}, "
            "{%44, %45, %46, %47}, %48, 0, 1, 1, 0;"
            : WO4(0), WO4(4), WO4(8), WO4(12), WO4(16), WO4(20), WO4(24), WO4(28), WO4(32), WO4(36), WO4(40)
            : "r"(a0), "r"(a1), "r"(a2), "r"(a3), "l"(descb));
    } else {
        asm volatile(
            "wgmma.mma_async.sync.aligned.m64n88k16.f32.bf16.bf16 "
            "{%0, %1, %2, %3, %4, %5, %6, %7, %8, %9, %10, %11, %12, %13, %14, %15, %16, %17, %18, %19, %20, %21, %22, %23, "
            "%24, %25, %26, %27, %28, %29, %30, %31, %32, %33, %34, %35, %36, %37, %38, %39, %40, %41, %42, %43}, "
            "{%44, %45, %46, %47}, %48, 1, 1, 1, 0;"
            : RW4(0), RW4(4), RW4(8), RW4(12), RW4(16), RW4(20), RW4(24), RW4(28), RW4(32), RW4(36), RW4(40)
            : "r"(a0), "r"(a1), "r"(a2), "r"(a3), "l"(descb));
    }
}

template <bool FIRST>
__device__ __forceinline__ void wgmma_n32(float (&d)[16], uint32_t a0, uint32_t a1, uint32_t a2, uint32_t a3, uint64_t descb) {
    if constexpr (FIRST) {
        asm volatile(
            "wgmma.mma_async.sync.aligned.m64n32k16.f32.bf16.bf16 "
            "{%0, %1, %2, %3, %4, %5, %6, %7, %8, %9, %10, %11, %12, %13, %14, %15}, "
            "{%16, %17, %18, %19}, %20, 0, 1, 1, 0;"
            : WO4(0), WO4(4), WO4(8), WO4(12)
            : "r"(a0), "r"(a1), "r"(a2), "r"(a3), "l"(descb));
    } else {
        asm volatile(
            "wgmma.mma_async.sync.aligned.m64n32k16.f32.bf16.bf16 "
            "{%0, %1, %2, %3, %4, %5, %6, %7, %8, %9, %10, %11, %12, %13, %14, %15}, "
            "{%16, %17, %18, %19}, %20, 1, 1, 1, 0;"
            : RW4(0), RW4(4), RW4(8), RW4(12)
            : "r"(a0), "r"(a1), "r"(a2), "r"(a3), "l"(descb));
    }
}

template <bool FIRST, int SEL>
__device__ __forceinline__ void wgmma_sp_n192_tb(float (&d)[96], uint32_t a0, uint32_t a1, uint32_t a2, uint32_t a3, uint64_t descb, uint32_t meta) {
    if constexpr (FIRST) {
        asm volatile(
            "wgmma.mma_async.sp.sync.aligned.m64n192k32.f32.bf16.bf16 "
            "{%0, %1, %2, %3, %4, %5, %6, %7, %8, %9, %10, %11, %12, %13, %14, %15, %16, %17, %18, %19, %20, %21, %22, %23, "
            "%24, %25, %26, %27, %28, %29, %30, %31, %32, %33, %34, %35, %36, %37, %38, %39, %40, %41, %42, %43, %44, %45, %46, %47, "
            "%48, %49, %50, %51, %52, %53, %54, %55, %56, %57, %58, %59, %60, %61, %62, %63, %64, %65, %66, %67, %68, %69, %70, %71, "
            "%72, %73, %74, %75, %76, %77, %78, %79, %80, %81, %82, %83, %84, %85, %86, %87, %88, %89, %90, %91, %92, %93, %94, %95}, "
            "{%96, %97, %98, %99}, %100, %101, %102, 0, 1, 1, 1;"
            : WO4(0), WO4(4), WO4(8), WO4(12), WO4(16), WO4(20), WO4(24), WO4(28), WO4(32), WO4(36), WO4(40), WO4(44),
              WO4(48), WO4(52), WO4(56), WO4(60), WO4(64), WO4(68), WO4(72), WO4(76), WO4(80), WO4(84), WO4(88), WO4(92)
            : "r"(a0), "r"(a1), "r"(a2), "r"(a3), "l"(descb), "r"(meta), "n"(SEL));
    } else {
        asm volatile(
            "wgmma.mma_async.sp.sync.aligned.m64n192k32.f32.bf16.bf16 "
            "{%0, %1, %2, %3, %4, %5, %6, %7, %8, %9, %10, %11, %12, %13, %14, %15, %16, %17, %18, %19, %20, %21, %22, %23, "
            "%24, %25, %26, %27, %28, %29, %30, %31, %32, %33, %34, %35, %36, %37, %38, %39, %40, %41, %42, %43, %44, %45, %46, %47, "
            "%48, %49, %50, %51, %52, %53, %54, %55, %56, %57, %58, %59, %60, %61, %62, %63, %64, %65, %66, %67, %68, %69, %70, %71, "
            "%72, %73, %74, %75, %76, %77, %78, %79, %80, %81, %82, %83, %84, %85, %86, %87, %88, %89, %90, %91, %92, %93, %94, %95}, "
            "{%96, %97, %98, %99}, %100, %101, %102, 1, 1, 1, 1;"
            : RW4(0), RW4(4), RW4(8), RW4(12), RW4(16), RW4(20), RW4(24), RW4(28), RW4(32), RW4(36), RW4(40), RW4(44),
              RW4(48), RW4(52), RW4(56), RW4(60), RW4(64), RW4(68), RW4(72), RW4(76), RW4(80), RW4(84), RW4(88), RW4(92)
            : "r"(a0), "r"(a1), "r"(a2), "r"(a3), "l"(descb), "r"(meta), "n"(SEL));
    }
}

#define TR(slot)
#define TRX(slot)
#define TRE(slot)
#define TRT(slot)
#define TRF(slot)
#define TRW(slot)
#define TRG(slot)
#define TRDUMP()

__device__ __forceinline__ void wg_fence() { asm volatile("wgmma.fence.sync.aligned;" ::: "memory"); }
__device__ __forceinline__ void wg_commit() { asm volatile("wgmma.commit_group.sync.aligned;" ::: "memory"); }
template <int N>
__device__ __forceinline__ void wg_wait() { asm volatile("wgmma.wait_group.sync.aligned %0;" ::"n"(N) : "memory"); }

template <int N>
__device__ __forceinline__ void pin(float (&d)[N]) {
#pragma unroll
    for (int i = 0; i < N; i++) asm volatile("" : "+f"(d[i])::"memory");
}
template <int N>
__device__ __forceinline__ void pin(uint32_t (&d)[N]) {
#pragma unroll
    for (int i = 0; i < N; i++) asm volatile("" : "+r"(d[i])::"memory");
}

constexpr uint64_t kDescRing = ((uint64_t)((1u << 30) | (1024u >> 4)) << 32) | (1u << 16) | (s_ring >> 4);
constexpr uint32_t kToV = ((kRingChunk >> 4) - 1) << 20;
__device__ __forceinline__ uint64_t desc_at(uint64_t base, uint32_t byte_off) {
    uint64_t d;
    asm volatile("add.s64 %0, %1, %2;" : "=l"(d) : "l"(base), "l"((uint64_t)(byte_off >> 4)));
    return d;
}

__device__ __forceinline__ void mbar_init(uint32_t bar, uint32_t count) {
    asm volatile("mbarrier.init.shared::cta.b64 [%0], %1;" ::"r"(bar), "r"(count) : "memory");
}
__device__ __forceinline__ void mbar_expect_tx(uint32_t bar, uint32_t bytes) {
    asm volatile("mbarrier.arrive.expect_tx.shared::cta.b64 _, [%0], %1;" ::"r"(bar), "r"(bytes) : "memory");
}
__device__ __forceinline__ void expect_tx_only(uint32_t bar, uint32_t bytes) {
    asm volatile("mbarrier.expect_tx.relaxed.cta.shared::cta.b64 [%0], %1;" ::"r"(bar), "r"(bytes) : "memory");
}
__device__ __forceinline__ void mbar_arrive(uint32_t bar) {
    asm volatile("mbarrier.arrive.shared::cta.b64 _, [%0];" ::"r"(bar) : "memory");
}
__device__ __forceinline__ void mbar_wait(uint32_t bar, uint32_t parity) {
    asm volatile(
        "{\n.reg .pred p;\n"
        "W: mbarrier.try_wait.parity.shared::cta.b64 p, [%0], %1;\n"
        "@!p bra W;\n}\n"
        ::"r"(bar), "r"(parity) : "memory");
}
__device__ __forceinline__ uint32_t clock_now() {
    uint32_t c;
    asm volatile("mov.u32 %0, %%clock;" : "=r"(c)::"memory");
    return c;
}
__device__ __forceinline__ void wait_until(uint32_t t0, int t) {
    if (t == 0) return;
    while ((int)(clock_now() - t0) < t) {}
}
__device__ __forceinline__ bool elect() {
    uint32_t ok;
    asm volatile("{\n.reg .pred p;\nelect.sync _|p, 0xffffffff;\nselp.u32 %0, 1, 0, p;\n}\n" : "=r"(ok));
    return ok != 0;
}
__device__ __forceinline__ void turn_wait(int wg) { asm volatile("bar.sync %0, 256;" ::"r"(1 + wg) : "memory"); }
__device__ __forceinline__ void turn_pass(int wg) { asm volatile("bar.arrive %0, 256;" ::"r"(2 - wg) : "memory"); }

__device__ __forceinline__ void tma_box(uint32_t dst, const CUtensorMap* map, uint32_t bar, int c0, int c2, int c3, int c4) {
    asm volatile(
        "cp.async.bulk.tensor.5d.shared::cluster.global.mbarrier::complete_tx::bytes [%0], [%1, {%3, %4, %5, %6, %7}], [%2];"
        ::"r"(dst), "l"(map), "r"(bar), "r"(c0), "r"(0), "r"(c2), "r"(c3), "r"(c4)
        : "memory");
}
__device__ __forceinline__ void tma_3d(uint32_t dst, const CUtensorMap* map, uint32_t bar, int c1, int c2) {
    asm volatile("cp.async.bulk.tensor.3d.shared::cluster.global.mbarrier::complete_tx::bytes [%0], [%1, {%3, %4, %5}], [%2];"
                 ::"r"(dst), "l"(map), "r"(bar), "r"(0), "r"(c1), "r"(c2)
                 : "memory");
}
__device__ __forceinline__ void prefetch_map(const CUtensorMap* map) {
    asm volatile("prefetch.tensormap [%0];" ::"l"(map) : "memory");
}
__device__ __forceinline__ uint4 ldg(const void* p) {
    uint4 v;
    asm volatile("ld.global.v4.u32 {%0, %1, %2, %3}, [%4];" : "=r"(v.x), "=r"(v.y), "=r"(v.z), "=r"(v.w) : "l"(p) : "memory");
    return v;
}
__device__ __forceinline__ uint32_t pack_bf16(float lo, float hi) {
    uint32_t r;
    asm("cvt.rn.bf16x2.f32 %0, %1, %2;" : "=r"(r) : "f"(hi), "f"(lo));
    return r;
}
__device__ __forceinline__ float ex2(float x) {
    float y;
    asm("ex2.approx.ftz.f32 %0, %1;" : "=f"(y) : "f"(x));
    return y;
}
__device__ __forceinline__ float rcp(float x) {
    float y;
    asm("rcp.approx.ftz.f32 %0, %1;" : "=f"(y) : "f"(x));
    return y;
}
__device__ __forceinline__ void mma16816(float (&d)[4], uint32_t a0, uint32_t a1, uint32_t a2, uint32_t a3, uint32_t b0, uint32_t b1) {
    asm volatile("mma.sync.aligned.m16n8k16.row.col.f32.bf16.bf16.f32 {%0, %1, %2, %3}, {%4, %5, %6, %7}, {%8, %9}, {%0, %1, %2, %3};"
                 : "+f"(d[0]), "+f"(d[1]), "+f"(d[2]), "+f"(d[3])
                 : "r"(a0), "r"(a1), "r"(a2), "r"(a3), "r"(b0), "r"(b1));
}
__device__ __forceinline__ uint4 lds128(uint32_t addr) {
    uint4 v;
    asm volatile("ld.volatile.shared.v4.u32 {%0, %1, %2, %3}, [%4];" : "=r"(v.x), "=r"(v.y), "=r"(v.z), "=r"(v.w) : "r"(addr) : "memory");
    return v;
}
__device__ __forceinline__ uint32_t lds_volatile(uint32_t addr) {
    uint32_t v;
    asm volatile("ld.volatile.shared.u32 %0, [%1];" : "=r"(v) : "r"(addr) : "memory");
    return v;
}

__device__ __forceinline__ int window_start(int n) { return min(max(n, 0), 105); }
__device__ __forceinline__ int origin_u(int u) { return min(max(u, 0), 98); }

struct Work {
    int u, v;
    int step;
    uint32_t su, sv;
    uint32_t base;
    bool corner;
    int ntiles;
    __device__ __forceinline__ void pixel_offsets(int qu, int qv, int j, uint32_t& o0, uint32_t& o1) const {
        const uint32_t b = (qu + window_start(qu)) * su + j * 16 + base;
        o0 = b + (qv + window_start(qv)) * sv;
        o1 = b + (qv + 1 + window_start(qv + 1)) * sv;
    }
};

__device__ __forceinline__ Work decode_work(int c) {
    Work w;
    const bool transposed = (c >> 4) == 7;
    const int px = 6 * (c & 1), py = 3 * (c & 2);
    w.corner = c >= 128;
    w.step = 8 - 4 * (c & 4);
    w.u = (c < 112 ? c & ~7 : 96 + (c & 8)) + (transposed ? py : px) - 6;
    w.v = (w.corner ? 96 : 48 - 2 * (c & 4)) + (transposed ? px : py) - 6;
    w.su = transposed ? kHW * kPixBytes : kPixBytes;
    w.sv = transposed ? kPixBytes : kHW * kPixBytes;
    w.base = px * (kPixBytes / 6) + py * (kHW * kPixBytes / 6) + 6 * (kHW + 1) * kPixBytes;
    w.ntiles = w.corner ? 4 : 6;
    return w;
}

struct RawX { uint4 a[6], b[6]; };
__device__ __forceinline__ void load_raw(RawX& r, const uint8_t* base, uint32_t o0, uint32_t o1) {
    __syncwarp();
#pragma unroll
    for (int c = 0; c < 6; c++) { r.a[c] = ldg(base + o0 + c * 64); r.b[c] = ldg(base + o1 + c * 64); }
    __syncwarp();
}
__device__ __forceinline__ void raw_to_frags(const RawX& r, uint32_t zero, uint32_t (&f)[48]) {
#pragma unroll
    for (int c = 0; c < 6; c++) {
        asm volatile("{\n.reg .b32 t, u;\nadd.u32 t, %4, %8;\nadd.u32 u, %5, %8;\nxor.b32 %0, %6, %8;\nxor.b32 %1, %7, %8;\n"
                     "xor.b32 %2, t, %8;\nxor.b32 %3, u, %8;\n}\n"
                     : "=&r"(f[8 * c + 1]), "=&r"(f[8 * c + 3]), "=&r"(f[8 * c + 4]), "=&r"(f[8 * c + 6])
                     : "r"(r.a[c].y), "r"(r.a[c].w), "r"(r.b[c].x), "r"(r.b[c].z), "r"(zero));
        f[8 * c + 0] = r.a[c].x; f[8 * c + 2] = r.a[c].z; f[8 * c + 5] = r.b[c].y; f[8 * c + 7] = r.b[c].w;
    }
}
__device__ __forceinline__ void acc_to_frags(const float (&d)[96], uint32_t (&f)[48]) {
#pragma unroll
    for (int i = 0; i < 48; i++) f[i] = pack_bf16(d[2 * i], d[2 * i + 1]);
}

template <class F>
__device__ __forceinline__ void proj_gemm(float (&d)[96], const uint32_t (&a)[48], uint64_t dsc, uint32_t img, F after) {
#pragma unroll
    for (int s = 0; s < 12; s++) {
        if (s == 0) wgmma_n192<true>(d, a[4 * s], a[4 * s + 1], a[4 * s + 2], a[4 * s + 3], desc_at(dsc, img - s_ring + (s >> 2) * kWChunk + (s & 3) * 32));
        else wgmma_n192<false>(d, a[4 * s], a[4 * s + 1], a[4 * s + 2], a[4 * s + 3], desc_at(dsc, img - s_ring + (s >> 2) * kWChunk + (s & 3) * 32));
        if (s == 11) wg_commit();
        after(s);
    }
}
__device__ __forceinline__ void pack_out(const float (&acc)[96], uint32_t (&po)[48]) {
#pragma unroll
    for (int g = 0; g < 6; g++)
#pragma unroll
        for (int q = 0; q < 4; q++) {
            po[8 * g + q] = pack_bf16(acc[16 * g + 4 * q], acc[16 * g + 4 * q + 1]);
            po[8 * g + 4 + q] = pack_bf16(acc[16 * g + 4 * q + 2], acc[16 * g + 4 * q + 3]);
        }
}
template <bool PINNED = true>
__device__ __forceinline__ void store_one(bool on, uint8_t* p0, uint8_t* p1, const uint32_t (&po)[48], int n) {
    if (PINNED) __syncwarp();
    asm volatile("{\n.reg .pred p;\nsetp.ne.u32 p, %5, 0;\n@p st.global.v4.u32 [%0], {%1, %2, %3, %4};\n}\n"
                 ::"l"(((n & 1) ? p1 : p0) + (n >> 1) * 64), "r"(po[4 * n]), "r"(po[4 * n + 1]), "r"(po[4 * n + 2]), "r"(po[4 * n + 3]), "r"((uint32_t)on) : "memory");
}

template <int N>
__device__ __forceinline__ float tree_max(const float (&v)[N]) {
    float t[N];
#pragma unroll
    for (int i = 0; i < N; i++) t[i] = v[i];
#pragma unroll
    for (int w = 1; w < N; w *= 2)
#pragma unroll
        for (int i = 0; i + w < N; i += 2 * w) t[i] = fmaxf(t[i], t[i + w]);
    return t[0];
}
template <int N>
__device__ __forceinline__ float tree_sum(const float (&v)[N]) {
    float t[N];
#pragma unroll
    for (int i = 0; i < N; i++) t[i] = v[i];
#pragma unroll
    for (int w = 1; w < N; w *= 2)
#pragma unroll
        for (int i = 0; i + w < N; i += 2 * w) t[i] += t[i + w];
    return t[0];
}

template <int B>
__device__ __forceinline__ void pick(uint32_t h, uint32_t ok, const float* s, float& v0, float& v1) {
    asm("{\n.reg .pred p, q0, q1;\n.reg .b32 t;\nand.b32 t, %6, %7;\nsetp.ne.u32 p, t, 0;\n"
        "and.b32 t, %8, %9;\nsetp.ne.u32 q0, t, 0;\nand.b32 t, %8, %10;\nsetp.ne.u32 q1, t, 0;\n"
        "@q0 selp.f32 %0, %3, %2, p;\n@q1 selp.f32 %1, %5, %4, p;\n}\n"
        : "+f"(v0), "+f"(v1)
        : "f"(s[0]), "f"(s[1]), "f"(s[2]), "f"(s[3]), "r"(h), "n"(1 << ((4 * B) % 7)), "r"(ok), "n"(1 << (2 * B)), "n"(2 << (2 * B)));
}
template <int B, class F>
__device__ __forceinline__ void for_blocks(F f) {
    if constexpr (B > 0) { for_blocks<B - 1>(f); f(std::integral_constant<int, B - 1>{}); }
}
__device__ __forceinline__ void gather_outer(const float (&s)[44], uint32_t h, uint32_t ok, float (&v0)[14], float (&v1)[14]) {
    for_blocks<11>([&](auto B) {
        constexpr int b = B.value < 8 ? (B.value >> 1) + 7 * (B.value & 1) : B.value - 4;
        pick<b>(h, ok, &s[4 * b], v0[b], v1[b]);
    });
}
__device__ __forceinline__ void gather_mid(const float (&sE)[16], uint32_t h, uint32_t ok, float (&v0)[14], float (&v1)[14]) {
    for_blocks<4>([&](auto B) { pick<10 + B.value>(h, ok, &sE[4 * B.value], v0[10 + B.value], v1[10 + B.value]); });
}
__device__ __forceinline__ float quad_max(float m) {
    m = fmaxf(m, __shfl_xor_sync(0xffffffffu, m, 1));
    return fmaxf(m, __shfl_xor_sync(0xffffffffu, m, 2));
}
__device__ __forceinline__ float quad_sum(float s) {
    s += __shfl_xor_sync(0xffffffffu, s, 1);
    return s + __shfl_xor_sync(0xffffffffu, s, 2);
}
template <int B0, int B1>
__device__ __forceinline__ void exp_route(float (&v0)[14], float (&v1)[14], float m0, float m1, const uint4& r, bool even, uint32_t (&y)[14]) {
#pragma unroll
    for (int b = B0; b < B1; b++) { v0[b] = ex2(v0[b] - m0); v1[b] = ex2(v1[b] - m1); }
#pragma unroll
    for (int b = B0; b < B1; b += 2) {
        const uint32_t x0 = pack_bf16(v0[b], v1[b]), x1 = pack_bf16(v0[b + 1], v1[b + 1]);
        const uint32_t u = __shfl_sync(0xffffffffu, even ? x0 : x1, r.x);
        const uint32_t w = __shfl_sync(0xffffffffu, even ? x1 : x0, r.y);
        y[b] = __byte_perm(u, w, r.z); y[b + 1] = __byte_perm(u, w, r.w);
    }
}
template <int BIT0, int N0, int N1>
__device__ __forceinline__ void unfold(const uint32_t (&y)[14], uint32_t fold, uint32_t (&p)[12]) {
    for_blocks<N1 - N0>([&](auto N) {
        constexpr int n = N0 + N.value;
        asm("{\n.reg .pred p;\n.reg .b32 t;\nand.b32 t, %4, %5;\nsetp.ne.u32 p, t, 0;\nselp.b32 %0, %2, 0, p;\nselp.b32 %1, %3, 0, p;\n}\n"
            : "=r"(p[2 * n]), "=r"(p[2 * n + 1]) : "r"(y[2 * n]), "r"(y[2 * n + 1]), "r"(fold), "n"(1 << (BIT0 + n)));
    });
}
__device__ __forceinline__ void keep(bool never, uint32_t a, uint32_t b, uint32_t c, uint32_t d) {
    asm volatile("{\n.reg .pred p;\nsetp.ne.u32 p, %4, 0;\n@p st.volatile.shared.v4.u32 [%5], {%0, %1, %2, %3};\n}\n"
                 ::"r"(a), "r"(b), "r"(c), "r"(d), "r"((uint32_t)never), "r"(s_trace) : "memory");
}

__device__ __forceinline__ uint32_t wimg_offset(uint32_t row, uint32_t s, uint32_t j) {
    return (s >> 2) * kWChunk + row * 128 + (((2 * (s & 3) + (j >> 1)) ^ (row & 7)) << 4) + (j & 1) * 8;
}

__device__ __forceinline__ void ldsm4(uint32_t (&r)[4], uint32_t addr) {
    asm volatile("ldmatrix.sync.aligned.m8n8.x4.shared.b16 {%0, %1, %2, %3}, [%4];" : "=r"(r[0]), "=r"(r[1]), "=r"(r[2]), "=r"(r[3]) : "r"(addr) : "memory");
}
__device__ __forceinline__ void ldsm4_t(uint32_t (&r)[4], uint32_t addr) {
    asm volatile("ldmatrix.sync.aligned.m8n8.x4.trans.shared.b16 {%0, %1, %2, %3}, [%4];" : "=r"(r[0]), "=r"(r[1]), "=r"(r[2]), "=r"(r[3]) : "r"(addr) : "memory");
}
__device__ __forceinline__ void m_partial(const uint8_t* wqkv, uint32_t mt, uint32_t s, uint32_t q, uint32_t lane, uint32_t zero) {
    const uint32_t r8 = lane >> 2, col = q * 128 + (lane & 3) * 16;
    const uint8_t* pa = wqkv + (16 * mt + r8) * 1152 + col;
    const uint8_t* pb = wqkv + (16 * s + 8 * (r8 & 2) + (r8 & 5)) * 1152 + col;
    uint4 A[2][2], B[4][2];
#pragma unroll
    for (int c = 0; c < 2; c++) {
#pragma unroll
        for (int h = 0; h < 2; h++) A[h][c] = ldg(pa + 384 + h * 8 * 1152 + c * 64);
#pragma unroll
        for (int n = 0; n < 4; n++) B[n][c] = ldg(pb + ((n & 1) * 8 + (n & 2)) * 1152 + c * 64);
    }
#pragma unroll
    for (int i = 0; i < 4; i++) { uint4& a = A[i >> 1][i & 1]; a.x ^= zero; a.y ^= zero; a.z ^= zero; a.w ^= zero; }
#pragma unroll
    for (int n = 0; n < 4; n++) {
        float d[4] = {0.f, 0.f, 0.f, 0.f};
#pragma unroll
        for (int c = 0; c < 2; c++) {
            mma16816(d, A[0][c].x, A[1][c].x, A[0][c].y, A[1][c].y, B[n][c].x, B[n][c].y);
            mma16816(d, A[0][c].z, A[1][c].z, A[0][c].w, A[1][c].w, B[n][c].z, B[n][c].w);
        }
        asm volatile("st.shared.v4.f32 [%0], {%1, %2, %3, %4};" ::"r"(s_wv + q * 2048 + n * 512 + lane * 16), "f"(d[0]), "f"(d[1]), "f"(d[2]), "f"(d[3]) : "memory");
    }
}
__device__ __forceinline__ void m_reduce(uint32_t e, uint32_t lane, float (&d)[2][4]) {
#pragma unroll
    for (int n = 0; n < 2; n++) {
        float t[3][4];
#pragma unroll
        for (int q = 0; q < 3; q++)
            asm volatile("ld.shared.v4.f32 {%0, %1, %2, %3}, [%4];" : "=f"(t[q][0]), "=f"(t[q][1]), "=f"(t[q][2]), "=f"(t[q][3]) : "r"(s_wv + q * 2048 + e * 1024 + n * 512 + lane * 16) : "memory");
#pragma unroll
        for (int i = 0; i < 4; i++) d[n][i] = (t[0][i] + t[1][i] + t[2][i]) * kScaleLog2e;
    }
}
__device__ __forceinline__ void w_piece(uint32_t q, uint32_t lane, float (&d)[2][4]) {
    const uint32_t rr = lane & 7, mi = lane >> 3, kr = 4 * (rr >> 1) + (mi & 2) + (rr & 1);
    const uint32_t pa = s_wv + q * 32 + (4 * (mi & 2) + rr) * 96 + ((mi & 1) << 4);
    const uint32_t pb = s_wv + 3 * 6144 + kr * 128 + (((mi & 1) ^ (kr & 7)) << 4);
    float e[2][4];
#pragma unroll
    for (int i = 0; i < 8; i++) (&d[0][0])[i] = (&e[0][0])[i] = 0.f;
#pragma unroll
    for (int k = 0; k < 12; k++) {
        uint32_t aq[4], bq[4];
        ldsm4_t(aq, pa + k * 1536);
        ldsm4(bq, (pb ^ ((k & 3) << 5)) + (k >> 2) * 2048);
        mma16816(k & 1 ? e[0] : d[0], aq[0], aq[1], aq[2], aq[3], bq[0], bq[1]);
        mma16816(k & 1 ? e[1] : d[1], aq[0], aq[1], aq[2], aq[3], bq[2], bq[3]);
    }
#pragma unroll
    for (int i = 0; i < 8; i++) (&d[0][0])[i] += (&e[0][0])[i];
}
__device__ __forceinline__ uint32_t piece_offset(uint32_t which, uint32_t s, uint32_t mt, uint32_t lane) {
    const uint32_t r8 = lane >> 2;
    return which * kWBytes + wimg_offset(which ? 32 * (mt >> 1) + 8 * (r8 >> 1) + 4 * (mt & 1) + (r8 & 1) : 16 * mt + r8, s, lane & 3);
}
__device__ __forceinline__ void piece_store(Scratch* g, uint32_t par, uint32_t off0, uint32_t which, const float (&d)[2][4]) {
#pragma unroll
    for (int hf = 0; hf < 2; hf++) {
        const uint32_t off = off0 ^ (hf ? which ? 288 : 1024 : 0);
        const uint32_t a = pack_bf16(d[0][2 * hf], d[0][2 * hf + 1]), b = pack_bf16(d[1][2 * hf], d[1][2 * hf + 1]);
        asm volatile("st.relaxed.gpu.global.v2.u32 [%0], {%1, %2};" ::"l"(g->img[0][0] + (par + off)), "r"(a ? a : 0x8000u), "r"(b) : "memory");
    }
}
__device__ __forceinline__ void piece_clear(Scratch* g, uint32_t par, uint32_t off0, uint32_t which) {
#pragma unroll
    for (int hf = 0; hf < 2; hf++)
        asm volatile("st.relaxed.gpu.global.v2.u32 [%0], {%1, %1};" ::"l"(g->img[0][0] + (par + (off0 ^ (hf ? which ? 288 : 1024 : 0)))), "r"(0) : "memory");
}

__device__ __forceinline__ uint32_t ld_relaxed(const uint32_t* p) {
    uint32_t v;
    asm volatile("ld.relaxed.gpu.global.u32 %0, [%1];" : "=r"(v) : "l"(p) : "memory");
    return v;
}
__device__ __forceinline__ void count_up(uint32_t* p) {
    asm volatile("red.relaxed.gpu.global.add.u32 [%0], %1;" ::"l"(p), "r"(1) : "memory");
}
__device__ __forceinline__ void bulk_g2s(uint32_t dst, const void* src, uint32_t bytes, uint32_t bar) {
    asm volatile("cp.async.bulk.shared::cluster.global.mbarrier::complete_tx::bytes [%0], [%1], %2, [%3];"
                 ::"r"(dst), "l"(src), "r"(bytes), "r"(bar)
                 : "memory");
}

__global__ void __launch_bounds__(kThreads, 1)
nat_fused_kernel(const uint8_t* __restrict__ x, const uint8_t* __restrict__ wqkv, uint8_t* __restrict__ out, Scratch* g,
                 const uint8_t* wo, uint64_t dsc, const __grid_constant__ Maps maps) {
    const int tid = threadIdx.x, lane = tid & 31;
    const int warp = __shfl_sync(0xffffffffu, tid >> 5, 0);
    const int wg = warp >> 2, wq = warp & 3, r8 = lane >> 2, j = lane & 3;
    const int cta = blockIdx.x;
    const Work w = decode_work(cta);
    const uint32_t jq = (cta < 124 ? cta + 8 : cta - 124) / 11u, jr = (cta < 124 ? cta + 8 : cta - 124) - 11 * jq;
    const uint32_t which = jr >= 6, jhi = which ? jr - 6 : jq, jlo = which ? jq : 2 * jr;
    const bool has_job = jr < 10;
    if (wg == 2 && wq < 3) {
#pragma unroll
        for (int r = 0; r < 3; r++)
            asm volatile("st.shared.v4.u32 [%0], {%1, %1, %1, %1};" ::"r"(s_ring + wq * kRingChunk + (r == 0 ? 84 : r == 1 ? 88 : 204) * 128 + lane * 16), "r"(0) : "memory");
        asm volatile("fence.proxy.async.shared::cta;" ::: "memory");
    }
    if (x == nullptr) return;
    const uint32_t t_start = clock_now();
    if (wg == 2) {
        asm volatile("setmaxnreg.dec.sync.aligned.u32 24;");
        if (wq < 3) {
            if (lane < 3 && cta < 128) {
                const uint32_t row = 3 * (cta >> 1) + wq;
                asm volatile("prefetch.global.L2 [%0];" ::"l"((cta & 1 ? wo + row * 384 : wqkv + row * 1152 + 768) + lane * 128));
            }
            asm volatile("bar.sync 7, 192;" ::: "memory");
            const uint32_t par = lds_volatile(s_par);
            uint32_t phase = 0;
#pragma unroll 1
            for (uint32_t c = 0; c < 6; c++) {
                const uint32_t part = c * kWChunk + wq * (kWChunk / 3), img = 8 * min(c, 3u);
                mbar_wait(bar_img + 8 * c, 0);
                if (SPEC && c == 0 && lane == 0) mbar_arrive(bar_ok);
                if (wq == 0) TRW(10 + c);
#pragma unroll 1
                while (true) {
                    uint32_t lo = ~0u;
#pragma unroll
                    for (int q = 0; q < 8; q++) lo = min(lo, lds_volatile(s_m + part + lane * 32 + (lane & 12) * 2 + q * 1024));
                    if (__all_sync(0xffffffffu, lo) || phase > 65535) break;
                    if (elect()) {
                        mbar_expect_tx(bar_redo + 8 * wq, kWChunk / 3);
                        bulk_g2s(s_m + part, g->img[0][0] + par + part, kWChunk / 3, bar_redo + 8 * wq);
                    }
                    mbar_wait(bar_redo + 8 * wq, phase++ & 1);
                }
                if (c == 2 && phase) asm volatile("st.shared.u32 [%0], %1;" ::"r"(s_again), "r"(1) : "memory");
                if ((c == 2 || c == 5) && lane == 0) mbar_arrive(bar_ok + img);
            }
        } else {
            uint32_t launch = ld_relaxed(&g->launches);
            const CUtensorMap* map = &maps.m[w.sv == kPixBytes ? 2 : 0];
            if (elect()) {
#pragma unroll
                for (int i = 0; i < 20; i++) mbar_init(s_bar + 8 * i, i < 13 ? 1 : i < 18 ? 3 : 4);
                asm volatile("fence.mbarrier_init.release.cluster;" ::: "memory");
                prefetch_map(map + 1);
                expect_tx_only(bar_a, sizeof(Table));
                bulk_g2s(s_tab, &maps.tables->t[w.step < 0], sizeof(Table), bar_a);
            }
            if (which && has_job && elect()) {
                mbar_expect_tx(bar_wop, 4 * 6144);
                tma_3d(s_wv, &maps.wo, bar_wop, 0, jhi);
                tma_3d(s_wv + 3 * 6144, &maps.wv, bar_wop, 16 * jlo, 6);
            }
            int u = w.u, v = w.v;
            uint32_t wait_bar = bar_use, wait_par = 1, slot = 0;
#pragma unroll 1
            for (int step = 0; step < 7 - w.corner; step++) {
                const bool first = step == 0 || (w.corner && step == 4);
                const int row = v + 4 + (first ? -w.step : w.step) / 2, ou = origin_u(u);
                uint32_t dst = s_ring + (first ? 0 : slot), mid = s_ring + kOffMid + 512, bar = first ? bar_a : bar_b;
                mbar_wait(wait_bar, wait_par);
                TRW(24 + step);
#pragma unroll 1
                for (int ch = (cta & 1) * kC; mid < s_m; ch += 64, dst += kRingChunk, mid += kRingChunk) {
                    if (elect()) {
                        mbar_expect_tx(bar, first ? kSlotBytes : kSlotBytes + kMidBytes);
                        tma_box(dst, map, bar, ch, ou, (cta >> 1) & 1, row);
                    }
                    if (!first) {
                        if (elect()) tma_box(mid, map + 1, bar, ch, ou, (cta >> 1) & 1, v + 6);
                        bar += 8;
                    }
                }
                if (step == 0) {
                    launch /= kGrid;
                    asm volatile("st.shared.v4.u32 [%0], {%1, %2, %2, %2};" ::"r"(s_par), "r"((launch & 1) * 2 * kWBytes), "r"(0) : "memory");
                    asm volatile("bar.arrive 5, 128;\nbar.arrive 3, 160;\nbar.arrive 4, 160;" ::: "memory");
                }
                if (step < 2) {
                    if (step) {
                        if (lane == 0) count_up(&g->launches);
                        asm volatile("bar.sync 6, 128;" ::: "memory");
                    }
                    wait_until(t_start, step ? TN(5, kTimeW) : TN(6, kTimeM));
                    TRW(5 + 4 * step);
#pragma unroll 1
                    for (int c = 3 * step; c < 3 + 3 * step; c++)
                        if (elect()) {
                            mbar_expect_tx(bar_img + 8 * c, kWChunk);
                            bulk_g2s(s_m + c * kWChunk, g->img[launch & 1][0] + c * kWChunk, kWChunk, bar_img + 8 * c);
                        }
                }
                const bool again = w.corner && step == 3;
                wait_bar = step == 0 ? bar_img + 8 * TN(1, 1) : again ? bar_use + 8 : bar_use;
                if (!again) {
                    wait_par = slot ? 0 : step != 0;
                    slot ^= kSlotStride;
                    if (w.corner && step == 2) { u += 8; v -= 8; } else if (step) v += w.step;
                }
            }
        }
        TRDUMP();
        return;
    }
    if (wg == 1 && wq < 3) {
        if (!which) m_partial(wqkv, jhi, jlo, wq, lane, (uint32_t)dsc & 1);
        const uint32_t off = piece_offset(which, which ? jlo : jlo + wq, which ? 3 * jhi + wq : jhi, lane);
        asm volatile("bar.sync %0, 128;" ::"r"(5 + (off >> 31)) : "memory");
        const uint32_t par = lds_volatile(s_par);
        if (has_job && wq < 2 + which) {
            float d[2][4];
            if (wq == 0) TRX(which ? 1 : 18);
            if (which) {
                mbar_wait(bar_wop, 0);
                if (wq == 0) TRX(2);
                w_piece(wq, lane, d);
            } else {
                m_reduce(wq, lane, d);
            }
            piece_store(g, par, off, which, d);
            __syncwarp();
            piece_clear(g, 2 * kWBytes - par, off, which);
            if (wq == 0) TRX(which ? 3 : 0);
        }
        asm volatile("bar.arrive 7, 192;\nbar.arrive 6, 128;" ::: "memory");
    }
    const int order = w.step < 0 ? warp ^ 3 : warp;
    int tu = w.u, tv = w.v + w.step * wg;
    const int du2 = w.corner ? 8 : 0, dv2 = w.corner ? 0 : 2 * w.step;
    uint32_t o0, o1;
    wait_until(t_start, START_TIME);
    asm volatile("setmaxnreg.inc.sync.aligned.u32 240;");
    w.pixel_offsets(tu + r8, tv + 2 * wq, j, o0, o1);
    uint32_t fa[48];
    {
        RawX raw;
        load_raw(raw, x, o0, o1);
        asm volatile("bar.sync %0, 160;" ::"r"(3 + wg) : "memory");
        raw_to_frags(raw, 0, fa);
        pin(fa);
    }
    mbar_wait(bar_ok, 0);
    const uint64_t dA = dsc + wg * (kSlotStride >> 4), dB = dsc + (wg ^ 1) * (kSlotStride >> 4);

    float acc[96];
    uint32_t po[48];
    uint32_t c0, c1;
    asm volatile("" : "=r"(c0), "=r"(c1));
#pragma unroll
    for (int q = 0; q < 48; q++) asm volatile("" : "=r"(po[q]));
#pragma unroll 1
    for (int i = wg; i < w.ntiles; i += 2) {
        const bool first = i == 0, last = i == w.ntiles - 1;

        TRF(8 + 16 * k);
        uint8_t *p0 = out + c0, *p1 = out + c1;
#pragma unroll 1
        for (uint32_t seen = 0;;) {
        wg_fence();
        if (!first) turn_wait(wg);
        proj_gemm(acc, fa, dsc, s_m, [&](int s) {
            if (s == 11 && !first) turn_pass(wg);
            const int n = __builtin_popcount(QSLOTS & ((1 << s) - 1));
            if (((QSLOTS >> s) & 1) && n < 12) store_one(i >= 2, out + c0, out + c1, po, n);
            if (s == 3 || s == 7) { mbar_wait((SPEC ? bar_img : bar_ok) + 2 * s + 2, 0); wg_fence(); }
        });
        __syncwarp();
        TRF(9 + 16 * k);
            if (!first) break;
            mbar_wait(bar_ok + 16, 0);
            if (lds_volatile(s_again) == seen) break;
            wg_wait<0>();
            seen = 1;
        }
        c0 = o0; c1 = o1;
        w.pixel_offsets(tu + du2 + r8, tv + dv2 + 2 * wq, j, o0, o1);
        if (i + 2 >= w.ntiles) o0 = o1 = 0;
        wg_wait<0>();
        pin(acc);
        TR(11 + 16 * k);
        TRT(80 + k);
#pragma unroll
        for (int n = __builtin_popcount(QSLOTS); n < 12 - __builtin_popcount(ASLOTS) - __builtin_popcount(BSLOTS); n++) store_one(i >= 2, p0, p1, po, n);
        acc_to_frags(acc, fa);
        pin(fa);

        float sA[44], sE[16], sB[44];
        RawX nxt;
        if (!first) turn_wait(wg);
        mbar_wait(bar_a, w.corner ? i >> 1 : 0);
        wg_fence();
#pragma unroll
        for (int s = 0; s < 12; s++) {
            if (s == 0) wgmma_n88<true>(sA, fa[4 * s], fa[4 * s + 1], fa[4 * s + 2], fa[4 * s + 3], desc_at(dA, (s >> 2) * kRingChunk + (s & 3) * 32));
            else wgmma_n88<false>(sA, fa[4 * s], fa[4 * s + 1], fa[4 * s + 2], fa[4 * s + 3], desc_at(dA, (s >> 2) * kRingChunk + (s & 3) * 32));
            if (s == 11) { wg_commit(); if (!first) turn_pass(wg); }
            if ((ASLOTS >> s) & 1) store_one(i >= 2, p0, p1, po, 12 - __builtin_popcount(BSLOTS) - __builtin_popcount(ASLOTS >> s));
        }
#pragma unroll
        for (int s = 12; s < 16; s++)
            if ((ASLOTS >> s) & 1) store_one(i >= 2, p0, p1, po, 12 - __builtin_popcount(BSLOTS) - __builtin_popcount(ASLOTS >> s));
        TRF(12 + 16 * k);
        const int vq = tv + 2 * wq;
        const uint4 tabu = lds128(s_tab + offsetof(Table, u) + (window_start(tu + r8) - origin_u(tu)) * 64 + j * 16);
        const uint4 tabv = lds128(s_tab + offsetof(Table, v) + (window_start(vq) + window_start(vq + 1) - 2 * tv) * 64 + j * 16);
        const uint4 route = lds128(s_tab + lane * 16);
        load_raw(nxt, x, o0, o1);
        float v0[14], v1[14];
#pragma unroll
        for (int b = 0; b < 14; b++) v0[b] = v1[b] = __int_as_float(0xff800000);
        wg_wait<0>();
        pin(sA);
        gather_outer(sA, tabu.x, tabv.x, v0, v1);
        pin(v0); pin(v1);
        if (!first) turn_wait(wg);
#pragma unroll
        for (int c = 0; c < 3; c++) {
            mbar_wait(bar_b + 8 * c, wg);
            TRF(64 + 4 * k + c);
            wg_fence();
#pragma unroll
            for (int s = 4 * c; s < 4 * c + 4; s++) {
                if (s == 0) wgmma_n88<true>(sB, fa[4 * s], fa[4 * s + 1], fa[4 * s + 2], fa[4 * s + 3], desc_at(dB, c * kRingChunk + (s & 3) * 32));
                else wgmma_n88<false>(sB, fa[4 * s], fa[4 * s + 1], fa[4 * s + 2], fa[4 * s + 3], desc_at(dB, c * kRingChunk + (s & 3) * 32));
                if ((BSLOTS >> s) & 1) store_one(i >= 2, p0, p1, po, 12 - __builtin_popcount(BSLOTS >> s));
            }
        }
        wg_commit();
#pragma unroll
        for (int s = 0; s < 12; s++)
            if (s == 0) wgmma_n32<true>(sE, fa[4 * s], fa[4 * s + 1], fa[4 * s + 2], fa[4 * s + 3], desc_at(dsc, kOffMid + (s >> 2) * kRingChunk + (s & 3) * 32));
            else wgmma_n32<false>(sE, fa[4 * s], fa[4 * s + 1], fa[4 * s + 2], fa[4 * s + 3], desc_at(dsc, kOffMid + (s >> 2) * kRingChunk + (s & 3) * 32));
        wg_commit();
        if (OSPLIT || !last) turn_pass(wg);
        TRF(13 + 16 * k);
        wg_wait<1>();
        pin(sB);
        gather_outer(sB, tabu.w, tabv.y, v0, v1);
        wg_wait<0>();
        pin(sE);
        TRF(14 + 16 * k);
        gather_mid(sE, tabu.w, tabv.z, v0, v1);
        const float m0 = quad_max(tree_max(v0)), m1 = quad_max(tree_max(v1));

        uint32_t y[14], pa[12], pb[12];
        exp_route<0, 14>(v0, v1, m0, m1, route, (j & 1) == 0, y);
        float s0 = tree_sum(v0), s1 = tree_sum(v1);
        asm volatile("" : "+f"(s0), "+f"(s1));
        unfold<0, 0, 6>(y, tabv.w, pa);
        if (OSPLIT || !last) turn_wait(wg + (y[0] >> 31));
        TRF(15 + 16 * k + (y[13] >> 31));
        wg_fence();
        wgmma_sp_n192_tb<true, 0>(acc, pa[0], pa[1], pa[2], pa[3], desc_at(dA, kToV), tabu.y);
        wgmma_sp_n192_tb<false, 1>(acc, pa[4], pa[5], pa[6], pa[7], desc_at(dA, kToV + 4096), tabu.y);
        wgmma_sp_n192_tb<false, 0>(acc, pa[8], pa[9], pa[10], pa[11], desc_at(dA, kToV + 8192), tabu.z);
        wgmma_sp_n192_tb<false, 1>(acc, y[10], y[11], y[12], y[13], desc_at(dsc, kToV + kOffMid), tabu.z);
        wg_commit();
        unfold<8, 0, 6>(y, tabv.w, pb);
        wg_fence();
        wgmma_sp_n192_tb<false, 0>(acc, pb[0], pb[1], pb[2], pb[3], desc_at(dB, kToV), tabu.y);
        wgmma_sp_n192_tb<false, 1>(acc, pb[4], pb[5], pb[6], pb[7], desc_at(dB, kToV + 4096), tabu.y);
        wgmma_sp_n192_tb<false, 0>(acc, pb[8], pb[9], pb[10], pb[11], desc_at(dB, kToV + 8192), tabu.z);
        wg_commit();
        if (!last) turn_pass(wg);
        TRF(16 + 16 * k);
        wg_wait<1>();
        if (lane == 0) mbar_arrive(bar_use);
        TRF(17 + 16 * k);
        mbar_wait(bar_ok + 24, 0);
        wg_wait<0>();
        if (lane == 0) mbar_arrive(bar_use + 8);
        pin(acc);
        TR(18 + 16 * k);

        acc_to_frags(acc, po);
        pin(po);
        if (!last) turn_wait(wg);
        wg_fence();
        proj_gemm(acc, po, dsc, s_wv, [&](int s) {
            if (s + 1 == OSPLIT && i + 2 == w.ntiles) { turn_pass(wg); turn_wait(wg); }
        });
        if (!last) turn_pass(wg);
        TRF(19 + 16 * k);
        const uint32_t zero = lds_volatile(s_late);
        const float inv0 = rcp(quad_sum(s0 + __uint_as_float(zero))), inv1 = rcp(quad_sum(s1 + __uint_as_float(zero)));
        raw_to_frags(nxt, zero, fa);
        pin(fa);
#pragma unroll
        for (int q = 0; q < 48; q += 4) keep(wqkv == nullptr, fa[q], fa[q + 1], fa[q + 2], fa[q + 3]);
        keep(wqkv == nullptr, __float_as_uint(inv0), __float_as_uint(inv1), zero, lane);
        TRF(20 + 16 * k);
        tu += du2; tv += dv2;
        wg_wait<0>();
        pin(acc);
        TR(21 + 16 * k);
#pragma unroll
        for (int q = 0; q < 96; q++) acc[q] *= q & 2 ? inv1 : inv0;
        pack_out(acc, po);
#pragma unroll
        for (int n = 0; n < INLOOP; n++) store_one<false>(last, out + c0, out + c1, po, n);
        pin(po);
    }
#pragma unroll
    for (int n = 0; n < 12; n++) {
        asm volatile("{\n.reg .pred p;\nsetp.eq.u32 p, %0, 0;\n@p nanosleep.u32 %1;\n}\n" ::"r"(wg), "n"(NAP) : "memory");
        store_one<false>(n >= INLOOP || wg == 0, out + c0, out + c1, po, n);
    }
    TRE(7);
    TRG(1);
    TRDUMP();
}

typedef CUresult (*EncodeTiledFn)(CUtensorMap*, CUtensorMapDataType, cuuint32_t, void*, const cuuint64_t*, const cuuint64_t*,
                                  const cuuint32_t*, const cuuint32_t*, CUtensorMapInterleave, CUtensorMapSwizzle,
                                  CUtensorMapL2promotion, CUtensorMapFloatOOBfill);

bool make_maps(EncodeTiledFn fn, Maps* maps, void* x, void* wqkv, void* wo) {
    const cuuint64_t pix2 = 2 * kPixBytes, row = (cuuint64_t)kHW * kPixBytes;
    const cuuint32_t estr[5] = {1, 1, 1, 1, 1};
    bool ok = true;
    for (int tr = 0; tr < 2; tr++)
        for (int b = 0; b < 2; b++) {
            const cuuint64_t su = tr ? 2 * row : pix2, sv = tr ? pix2 : 2 * row;
            const cuuint64_t dims[5] = {2 * kC, 2, 105, 2, 112};
            const cuuint64_t strides[4] = {7 * su, su, row, sv};
            const cuuint32_t box[5] = {64, 2, 7, 1, b ? 2u : 6u};
            ok = ok && fn(&maps->m[2 * tr + b], CU_TENSOR_MAP_DATA_TYPE_BFLOAT16, 5, x, dims, strides, box, estr,
                          CU_TENSOR_MAP_INTERLEAVE_NONE, CU_TENSOR_MAP_SWIZZLE_128B, CU_TENSOR_MAP_L2_PROMOTION_L2_128B,
                          CU_TENSOR_MAP_FLOAT_OOB_FILL_NONE) == CUDA_SUCCESS;
        }
    for (int b = 0; b < 2; b++) {
        const cuuint64_t dims[3] = {b ? 64u : 48u, kC, b ? 9u : 4u}, strides[2] = {(b ? 3u : 1u) * kPixBytes, b ? 128u : 96u};
        const cuuint32_t box[3] = {b ? 64u : 48u, b ? 16u : 192u, b ? 3u : 1u};
        ok = ok && fn(b ? &maps->wv : &maps->wo, CU_TENSOR_MAP_DATA_TYPE_BFLOAT16, 3, b ? wqkv : wo, dims, strides, box, estr,
                      CU_TENSOR_MAP_INTERLEAVE_NONE, b ? CU_TENSOR_MAP_SWIZZLE_128B : CU_TENSOR_MAP_SWIZZLE_NONE, CU_TENSOR_MAP_L2_PROMOTION_L2_128B,
                      CU_TENSOR_MAP_FLOAT_OOB_FILL_NONE) == CUDA_SUCCESS;
    }
    return ok;
}

}

extern "C" void kernel_launch(void* const* d_in, const int* in_sizes, int n_in, void* d_out, int out_size) {
    static EncodeTiledFn encode = nullptr;
    static Scratch* scratch = nullptr;
    static Tables* tables = nullptr;
    if (!encode) {
        int dev = 0, reserved = 0;
        cudaFuncAttributes attr;
        cudaGetDevice(&dev);
        cudaDeviceGetAttribute(&reserved, cudaDevAttrReservedSharedMemoryPerBlock, dev);
        cudaFuncGetAttributes(&attr, nat_fused_kernel);
        if (reserved != (int)kSmemBase || attr.sharedSizeBytes != 0) return;
        cudaGetSymbolAddress((void**)&scratch, g_scratch);
        cudaGetSymbolAddress((void**)&tables, g_tables);
        void* fn = nullptr;
        cudaDriverEntryPointQueryResult st;
        cudaGetDriverEntryPoint("cuTensorMapEncodeTiled", &fn, cudaEnableDefault, &st);
        encode = (EncodeTiledFn)fn;
        cudaFuncSetAttribute(nat_fused_kernel, cudaFuncAttributeMaxDynamicSharedMemorySize, kSmemBytes);
    }
    Maps maps;
    maps.tables = tables;
    if (!encode || !make_maps(encode, &maps, d_in[0], d_in[1], d_in[2])) return;
    nat_fused_kernel<<<kGrid, kThreads, kSmemBytes>>>((const uint8_t*)d_in[0], (const uint8_t*)d_in[1], (uint8_t*)d_out, scratch, (const uint8_t*)d_in[2],
                                                      kDescRing, maps);
}
```

```cpp
#include <cuda_runtime.h>
#include <cuda_bf16.h>
#include <cuda.h>
#include <stdint.h>
#include <type_traits>
#include <stdlib.h>
#include <stddef.h>

#define KEEPFA 1
#define ASLOTS 0x3800
#define BSLOTS 0x6
#define QSLOTS 0x78a
#define OSPLIT 2
#define NAP 40
#define SPEC 1
#define EARLY 2
#define INLOOP 3

namespace {

constexpr int kC          = 192;
constexpr int kHW         = 224;
constexpr int kPixBytes   = kC * 2;
constexpr int kSlotBytes  = 84 * 128;
constexpr int kMidBytes   = 28 * 128;
constexpr int kOffMid     = 88 * 128;
constexpr int kSlotStride = 120 * 128;
constexpr int kRingChunk  = 208 * 128;
constexpr int kWChunk     = 192 * 128;
constexpr int kWBytes     = 3 * kWChunk;
constexpr uint32_t kSmemBase = 1024;
constexpr uint32_t s_ring = kSmemBase, s_m = s_ring + 3 * kRingChunk, s_wv = s_m + kWBytes, s_bar = s_wv + kWBytes;
constexpr uint32_t bar_b = s_bar, bar_img = s_bar + 24, bar_redo = s_bar + 72, bar_wop = s_bar + 96, bar_a = s_bar + 104,
                   bar_ok = s_bar + 112, bar_use = s_bar + 144, bar_free = s_bar + 160;
constexpr uint32_t s_par = s_bar + 192, s_late = s_bar + 196, s_again = s_bar + 200, s_tab = s_bar + 256, s_trace = s_tab + 2048;
constexpr int kSmemBytes  = s_trace + 2048 - kSmemBase;
constexpr int kThreads    = 384;
constexpr int kGrid       = 132;
constexpr int kTimeM = 2600, kTimeW = 5100;
constexpr float kScaleLog2e = 0.07216878364870322f * 1.4426950408889634f;

struct Maps {
    CUtensorMap m[4];
    CUtensorMap wo, wv;
    const struct Tables* tables;
};
#define TN(i, dflt) (dflt)
#define START_TIME (wg ? 850 + 500 * order : 250 + 560 * order)

struct Scratch {
    uint8_t img[2][2][kWBytes];
    uint32_t launches;
};
__device__ __align__(1024) Scratch g_scratch;

struct Table {
    uint32_t route[32][4];
    uint32_t u[8][4][4];
    uint32_t v[16][4][4];
};
struct Tables { Table t[2]; };
constexpr Tables make_tables() {
    Tables r = {};
    for (int rev = 0; rev < 2; rev++)
        for (int j = 0; j < 4; j++) {
            Table& t = r.t[rev];
            for (int q = 0; q < 8; q++) {
                uint32_t* e = t.route[4 * q + j];
                e[0] = 4 * q + 2 * (j & 1) + (j >> 1); e[1] = e[0] ^ 1;
                e[2] = j < 2 ? 0x5410u : 0x1054u; e[3] = e[2] + 0x2222u;
                e = t.u[q][j];
                for (int n = 0; n < 7; n++) e[0] |= ((n + j) % 7 < q ? 1u : 0u) << n;
                e[3] = e[0];
                for (int k = 0; k < 2; k++) {
                    const int step = 2 * k + (j >> 1), p0 = (step < 3 ? 16 * step : 40) + 8 * (j & 1);
                    uint32_t m = 0x8888u;
                    for (int n = 0; n < 8; n++) m |= ((p0 + n) % 7 < q ? 1u : 0u) << (2 * n);
                    e[1 + k] = m * 0x10001u;
                }
            }
            for (int sum = 0; sum < 15; sum++) {
                uint32_t* e = t.v[sum][j];
                for (int row = 0; row < 2; row++)
                    for (int b = 0; b < 14; b++) {
                        const int off = (sum + row) / 2, p = 4 * b + j;
                        const uint32_t bit = 1u << (2 * b + row);
                        if (p < 42 && p >= 7 * off) e[rev] |= bit;
                        if (p < 7 * off - 7) e[1 - rev] |= bit;
                        if (p >= 42 && p >= 7 * off && p < 7 * off + 49) e[2] |= bit;
                    }
                for (int n = 0; n < 6; n++)
                    if (8 * n + 2 * j < 42) e[3] |= 1u << (n + ((8 * n + 2 * j >= 7 * (sum / 2 & ~1)) != rev ? 0 : 8));
            }
        }
    return r;
}
__device__ __align__(128) const Tables g_tables = make_tables();

#define WO4(i) "=f"(d[i]), "=f"(d[i + 1]), "=f"(d[i + 2]), "=f"(d[i + 3])
#define RW4(i) "+f"(d[i]), "+f"(d[i + 1]), "+f"(d[i + 2]), "+f"(d[i + 3])

template <bool FIRST>
__device__ __forceinline__ void wgmma_n192(float (&d)[96], uint32_t a0, uint32_t a1, uint32_t a2, uint32_t a3, uint64_t descb) {
    if constexpr (FIRST) {
        asm volatile(
            "wgmma.mma_async.sync.aligned.m64n192k16.f32.bf16.bf16 "
            "{%0, %1, %2, %3, %4, %5, %6, %7, %8, %9, %10, %11, %12, %13, %14, %15, %16, %17, %18, %19, %20, %21, %22, %23, "
            "%24, %25, %26, %27, %28, %29, %30, %31, %32, %33, %34, %35, %36, %37, %38, %39, %40, %41, %42, %43, %44, %45, %46, %47, "
            "%48, %49, %50, %51, %52, %53, %54, %55, %56, %57, %58, %59, %60, %61, %62, %63, %64, %65, %66, %67, %68, %69, %70, %71, "
            "%72, %73, %74, %75, %76, %77, %78, %79, %80, %81, %82, %83, %84, %85, %86, %87, %88, %89, %90, %91, %92, %93, %94, %95}, "
            "{%96, %97, %98, %99}, %100, 0, 1, 1, 0;"
            : WO4(0), WO4(4), WO4(8), WO4(12), WO4(16), WO4(20), WO4(24), WO4(28), WO4(32), WO4(36), WO4(40), WO4(44),
              WO4(48), WO4(52), WO4(56), WO4(60), WO4(64), WO4(68), WO4(72), WO4(76), WO4(80), WO4(84), WO4(88), WO4(92)
            : "r"(a0), "r"(a1), "r"(a2), "r"(a3), "l"(descb));
    } else {
        asm volatile(
            "wgmma.mma_async.sync.aligned.m64n192k16.f32.bf16.bf16 "
            "{%0, %1, %2, %3, %4, %5, %6, %7, %8, %9, %10, %11, %12, %13, %14, %15, %16, %17, %18, %19, %20, %21, %22, %23, "
            "%24, %25, %26, %27, %28, %29, %30, %31, %32, %33, %34, %35, %36, %37, %38, %39, %40, %41, %42, %43, %44, %45, %46, %47, "
            "%48, %49, %50, %51, %52, %53, %54, %55, %56, %57, %58, %59, %60, %61, %62, %63, %64, %65, %66, %67, %68, %69, %70, %71, "
            "%72, %73, %74, %75, %76, %77, %78, %79, %80, %81, %82, %83, %84, %85, %86, %87, %88, %89, %90, %91, %92, %93, %94, %95}, "
            "{%96, %97, %98, %99}, %100, 1, 1, 1, 0;"
            : RW4(0), RW4(4), RW4(8), RW4(12), RW4(16), RW4(20), RW4(24), RW4(28), RW4(32), RW4(36), RW4(40), RW4(44),
              RW4(48), RW4(52), RW4(56), RW4(60), RW4(64), RW4(68), RW4(72), RW4(76), RW4(80), RW4(84), RW4(88), RW4(92)
            : "r"(a0), "r"(a1), "r"(a2), "r"(a3), "l"(descb));
    }
}

template <bool FIRST>
__device__ __forceinline__ void wgmma_n88(float (&d)[44], uint32_t a0, uint32_t a1, uint32_t a2, uint32_t a3, uint64_t descb) {
    if constexpr (FIRST) {
        asm volatile(
            "wgmma.mma_async.sync.aligned.m64n88k16.f32.bf16.bf16 "
            "{%0, %1, %2, %3, %4, %5, %6, %7, %8, %9, %10, %11, %12, %13, %14, %15, %16, %17, %18, %19, %20, %21, %22, %23, "
            "%24, %25, %26, %27, %28, %29, %30, %31, %32, %33, %34, %35, %36, %37, %38, %39, %40, %41, %42, %43}, "
            "{%44, %45, %46, %47}, %48, 0, 1, 1, 0;"
            : WO4(0), WO4(4), WO4(8), WO4(12), WO4(16), WO4(20), WO4(24), WO4(28), WO4(32), WO4(36), WO4(40)
            : "r"(a0), "r"(a1), "r"(a2), "r"(a3), "l"(descb));
    } else {
        asm volatile(
            "wgmma.mma_async.sync.aligned.m64n88k16.f32.bf16.bf16 "
            "{%0, %1, %2, %3, %4, %5, %6, %7, %8, %9, %10, %11, %12, %13, %14, %15, %16, %17, %18, %19, %20, %21, %22, %23, "
            "%24, %25, %26, %27, %28, %29, %30, %31, %32, %33, %34, %35, %36, %37, %38, %39, %40, %41, %42, %43}, "
            "{%44, %45, %46, %47}, %48, 1, 1, 1, 0;"
            : RW4(0), RW4(4), RW4(8), RW4(12), RW4(16), RW4(20), RW4(24), RW4(28), RW4(32), RW4(36), RW4(40)
            : "r"(a0), "r"(a1), "r"(a2), "r"(a3), "l"(descb));
    }
}

template <bool FIRST>
__device__ __forceinline__ void wgmma_n32(float (&d)[16], uint32_t a0, uint32_t a1, uint32_t a2, uint32_t a3, uint64_t descb) {
    if constexpr (FIRST) {
        asm volatile(
            "wgmma.mma_async.sync.aligned.m64n32k16.f32.bf16.bf16 "
            "{%0, %1, %2, %3, %4, %5, %6, %7, %8, %9, %10, %11, %12, %13, %14, %15}, "
            "{%16, %17, %18, %19}, %20, 0, 1, 1, 0;"
            : WO4(0), WO4(4), WO4(8), WO4(12)
            : "r"(a0), "r"(a1), "r"(a2), "r"(a3), "l"(descb));
    } else {
        asm volatile(
            "wgmma.mma_async.sync.aligned.m64n32k16.f32.bf16.bf16 "
            "{%0, %1, %2, %3, %4, %5, %6, %7, %8, %9, %10, %11, %12, %13, %14, %15}, "
            "{%16, %17, %18, %19}, %20, 1, 1, 1, 0;"
            : RW4(0), RW4(4), RW4(8), RW4(12)
            : "r"(a0), "r"(a1), "r"(a2), "r"(a3), "l"(descb));
    }
}

template <bool FIRST, int SEL>
__device__ __forceinline__ void wgmma_sp_n192_tb(float (&d)[96], uint32_t a0, uint32_t a1, uint32_t a2, uint32_t a3, uint64_t descb, uint32_t meta) {
    if constexpr (FIRST) {
        asm volatile(
            "wgmma.mma_async.sp.sync.aligned.m64n192k32.f32.bf16.bf16 "
            "{%0, %1, %2, %3, %4, %5, %6, %7, %8, %9, %10, %11, %12, %13, %14, %15, %16, %17, %18, %19, %20, %21, %22, %23, "
            "%24, %25, %26, %27, %28, %29, %30, %31, %32, %33, %34, %35, %36, %37, %38, %39, %40, %41, %42, %43, %44, %45, %46, %47, "
            "%48, %49, %50, %51, %52, %53, %54, %55, %56, %57, %58, %59, %60, %61, %62, %63, %64, %65, %66, %67, %68, %69, %70, %71, "
            "%72, %73, %74, %75, %76, %77, %78, %79, %80, %81, %82, %83, %84, %85, %86, %87, %88, %89, %90, %91, %92, %93, %94, %95}, "
            "{%96, %97, %98, %99}, %100, %101, %102, 0, 1, 1, 1;"
            : WO4(0), WO4(4), WO4(8), WO4(12), WO4(16), WO4(20), WO4(24), WO4(28), WO4(32), WO4(36), WO4(40), WO4(44),
              WO4(48), WO4(52), WO4(56), WO4(60), WO4(64), WO4(68), WO4(72), WO4(76), WO4(80), WO4(84), WO4(88), WO4(92)
            : "r"(a0), "r"(a1), "r"(a2), "r"(a3), "l"(descb), "r"(meta), "n"(SEL));
    } else {
        asm volatile(
            "wgmma.mma_async.sp.sync.aligned.m64n192k32.f32.bf16.bf16 "
            "{%0, %1, %2, %3, %4, %5, %6, %7, %8, %9, %10, %11, %12, %13, %14, %15, %16, %17, %18, %19, %20, %21, %22, %23, "
            "%24, %25, %26, %27, %28, %29, %30, %31, %32, %33, %34, %35, %36, %37, %38, %39, %40, %41, %42, %43, %44, %45, %46, %47, "
            "%48, %49, %50, %51, %52, %53, %54, %55, %56, %57, %58, %59, %60, %61, %62, %63, %64, %65, %66, %67, %68, %69, %70, %71, "
            "%72, %73, %74, %75, %76, %77, %78, %79, %80, %81, %82, %83, %84, %85, %86, %87, %88, %89, %90, %91, %92, %93, %94, %95}, "
            "{%96, %97, %98, %99}, %100, %101, %102, 1, 1, 1, 1;"
            : RW4(0), RW4(4), RW4(8), RW4(12), RW4(16), RW4(20), RW4(24), RW4(28), RW4(32), RW4(36), RW4(40), RW4(44),
              RW4(48), RW4(52), RW4(56), RW4(60), RW4(64), RW4(68), RW4(72), RW4(76), RW4(80), RW4(84), RW4(88), RW4(92)
            : "r"(a0), "r"(a1), "r"(a2), "r"(a3), "l"(descb), "r"(meta), "n"(SEL));
    }
}

#define TR(slot)
#define TRX(slot)
#define TRE(slot)
#define TRT(slot)
#define TRF(slot)
#define TRW(slot)
#define TRG(slot)
#define TRDUMP()

__device__ __forceinline__ void wg_fence() { asm volatile("wgmma.fence.sync.aligned;" ::: "memory"); }
__device__ __forceinline__ void wg_commit() { asm volatile("wgmma.commit_group.sync.aligned;" ::: "memory"); }
template <int N>
__device__ __forceinline__ void wg_wait() { asm volatile("wgmma.wait_group.sync.aligned %0;" ::"n"(N) : "memory"); }

template <int N>
__device__ __forceinline__ void pin(float (&d)[N]) {
#pragma unroll
    for (int i = 0; i < N; i++) asm volatile("" : "+f"(d[i])::"memory");
}
template <int N>
__device__ __forceinline__ void pin(uint32_t (&d)[N]) {
#pragma unroll
    for (int i = 0; i < N; i++) asm volatile("" : "+r"(d[i])::"memory");
}

constexpr uint64_t kDescRing = ((uint64_t)((1u << 30) | (1024u >> 4)) << 32) | (1u << 16) | (s_ring >> 4);
constexpr uint32_t kToV = ((kRingChunk >> 4) - 1) << 20;
__device__ __forceinline__ uint64_t desc_at(uint64_t base, uint32_t byte_off) {
    uint64_t d;
    asm volatile("add.s64 %0, %1, %2;" : "=l"(d) : "l"(base), "l"((uint64_t)(byte_off >> 4)));
    return d;
}

__device__ __forceinline__ void mbar_init(uint32_t bar, uint32_t count) {
    asm volatile("mbarrier.init.shared::cta.b64 [%0], %1;" ::"r"(bar), "r"(count) : "memory");
}
__device__ __forceinline__ void mbar_expect_tx(uint32_t bar, uint32_t bytes) {
    asm volatile("mbarrier.arrive.expect_tx.shared::cta.b64 _, [%0], %1;" ::"r"(bar), "r"(bytes) : "memory");
}
__device__ __forceinline__ void expect_tx_only(uint32_t bar, uint32_t bytes) {
    asm volatile("mbarrier.expect_tx.relaxed.cta.shared::cta.b64 [%0], %1;" ::"r"(bar), "r"(bytes) : "memory");
}
__device__ __forceinline__ void mbar_arrive(uint32_t bar) {
    asm volatile("mbarrier.arrive.shared::cta.b64 _, [%0];" ::"r"(bar) : "memory");
}
__device__ __forceinline__ void mbar_wait(uint32_t bar, uint32_t parity) {
    asm volatile(
        "{\n.reg .pred p;\n"
        "W: mbarrier.try_wait.parity.shared::cta.b64 p, [%0], %1;\n"
        "@!p bra W;\n}\n"
        ::"r"(bar), "r"(parity) : "memory");
}
__device__ __forceinline__ uint32_t clock_now() {
    uint32_t c;
    asm volatile("mov.u32 %0, %%clock;" : "=r"(c)::"memory");
    return c;
}
__device__ __forceinline__ void wait_until(uint32_t t0, int t) {
    if (t == 0) return;
    while ((int)(clock_now() - t0) < t) {}
}
__device__ __forceinline__ bool elect() {
    uint32_t ok;
    asm volatile("{\n.reg .pred p;\nelect.sync _|p, 0xffffffff;\nselp.u32 %0, 1, 0, p;\n}\n" : "=r"(ok));
    return ok != 0;
}
__device__ __forceinline__ void turn_wait(int wg) { asm volatile("bar.sync %0, 256;" ::"r"(1 + wg) : "memory"); }
__device__ __forceinline__ void turn_pass(int wg) { asm volatile("bar.arrive %0, 256;" ::"r"(2 - wg) : "memory"); }

__device__ __forceinline__ void tma_box(uint32_t dst, const CUtensorMap* map, uint32_t bar, int c0, int c2, int c3, int c4) {
    asm volatile(
        "cp.async.bulk.tensor.5d.shared::cluster.global.mbarrier::complete_tx::bytes [%0], [%1, {%3, %4, %5, %6, %7}], [%2];"
        ::"r"(dst), "l"(map), "r"(bar), "r"(c0), "r"(0), "r"(c2), "r"(c3), "r"(c4)
        : "memory");
}
__device__ __forceinline__ void tma_3d(uint32_t dst, const CUtensorMap* map, uint32_t bar, int c1, int c2) {
    asm volatile("cp.async.bulk.tensor.3d.shared::cluster.global.mbarrier::complete_tx::bytes [%0], [%1, {%3, %4, %5}], [%2];"
                 ::"r"(dst), "l"(map), "r"(bar), "r"(0), "r"(c1), "r"(c2)
                 : "memory");
}
__device__ __forceinline__ void prefetch_map(const CUtensorMap* map) {
    asm volatile("prefetch.tensormap [%0];" ::"l"(map) : "memory");
}
__device__ __forceinline__ uint4 ldg(const void* p) {
    uint4 v;
    asm volatile("ld.global.v4.u32 {%0, %1, %2, %3}, [%4];" : "=r"(v.x), "=r"(v.y), "=r"(v.z), "=r"(v.w) : "l"(p) : "memory");
    return v;
}
__device__ __forceinline__ uint32_t pack_bf16(float lo, float hi) {
    uint32_t r;
    asm("cvt.rn.bf16x2.f32 %0, %1, %2;" : "=r"(r) : "f"(hi), "f"(lo));
    return r;
}
__device__ __forceinline__ float ex2(float x) {
    float y;
    asm("ex2.approx.ftz.f32 %0, %1;" : "=f"(y) : "f"(x));
    return y;
}
__device__ __forceinline__ float rcp(float x) {
    float y;
    asm("rcp.approx.ftz.f32 %0, %1;" : "=f"(y) : "f"(x));
    return y;
}
__device__ __forceinline__ void mma16816(float (&d)[4], uint32_t a0, uint32_t a1, uint32_t a2, uint32_t a3, uint32_t b0, uint32_t b1) {
    asm volatile("mma.sync.aligned.m16n8k16.row.col.f32.bf16.bf16.f32 {%0, %1, %2, %3}, {%4, %5, %6, %7}, {%8, %9}, {%0, %1, %2, %3};"
                 : "+f"(d[0]), "+f"(d[1]), "+f"(d[2]), "+f"(d[3])
                 : "r"(a0), "r"(a1), "r"(a2), "r"(a3), "r"(b0), "r"(b1));
}
__device__ __forceinline__ uint4 lds128(uint32_t addr) {
    uint4 v;
    asm volatile("ld.volatile.shared.v4.u32 {%0, %1, %2, %3}, [%4];" : "=r"(v.x), "=r"(v.y), "=r"(v.z), "=r"(v.w) : "r"(addr) : "memory");
    return v;
}
__device__ __forceinline__ uint32_t lds_volatile(uint32_t addr) {
    uint32_t v;
    asm volatile("ld.volatile.shared.u32 %0, [%1];" : "=r"(v) : "r"(addr) : "memory");
    return v;
}

__device__ __forceinline__ int window_start(int n) { return min(max(n, 0), 105); }
__device__ __forceinline__ int origin_u(int u) { return min(max(u, 0), 98); }

struct Work {
    int u, v;
    int step;
    uint32_t su, sv;
    uint32_t base;
    bool corner;
    int ntiles;
    __device__ __forceinline__ void pixel_offsets(int qu, int qv, int j, uint32_t& o0, uint32_t& o1) const {
        const uint32_t b = (qu + window_start(qu)) * su + j * 16 + base;
        o0 = b + (qv + window_start(qv)) * sv;
        o1 = b + (qv + 1 + window_start(qv + 1)) * sv;
    }
};

__device__ __forceinline__ Work decode_work(int c) {
    Work w;
    const bool transposed = (c >> 4) == 7;
    const int px = 6 * (c & 1), py = 3 * (c & 2);
    w.corner = c >= 128;
    w.step = 8 - 4 * (c & 4);
    w.u = (c < 112 ? c & ~7 : 96 + (c & 8)) + (transposed ? py : px) - 6;
    w.v = (w.corner ? 96 : 48 - 2 * (c & 4)) + (transposed ? px : py) - 6;
    w.su = transposed ? kHW * kPixBytes : kPixBytes;
    w.sv = transposed ? kPixBytes : kHW * kPixBytes;
    w.base = px * (kPixBytes / 6) + py * (kHW * kPixBytes / 6) + 6 * (kHW + 1) * kPixBytes;
    w.ntiles = w.corner ? 4 : 6;
    return w;
}

struct RawX { uint4 a[6], b[6]; };
__device__ __forceinline__ void load_raw(RawX& r, const uint8_t* base, uint32_t o0, uint32_t o1) {
    __syncwarp();
#pragma unroll
    for (int c = 0; c < 6; c++) { r.a[c] = ldg(base + o0 + c * 64); r.b[c] = ldg(base + o1 + c * 64); }
    __syncwarp();
}
__device__ __forceinline__ void raw_to_frags(const RawX& r, uint32_t zero, uint32_t (&f)[48]) {
#pragma unroll
    for (int c = 0; c < 6; c++) {
        asm volatile("{\n.reg .b32 t, u;\nadd.u32 t, %4, %8;\nadd.u32 u, %5, %8;\nxor.b32 %0, %6, %8;\nxor.b32 %1, %7, %8;\n"
                     "xor.b32 %2, t, %8;\nxor.b32 %3, u, %8;\n}\n"
                     : "=&r"(f[8 * c + 1]), "=&r"(f[8 * c + 3]), "=&r"(f[8 * c + 4]), "=&r"(f[8 * c + 6])
                     : "r"(r.a[c].y), "r"(r.a[c].w), "r"(r.b[c].x), "r"(r.b[c].z), "r"(zero));
        f[8 * c + 0] = r.a[c].x; f[8 * c + 2] = r.a[c].z; f[8 * c + 5] = r.b[c].y; f[8 * c + 7] = r.b[c].w;
    }
}
__device__ __forceinline__ void acc_to_frags(const float (&d)[96], uint32_t (&f)[48]) {
#pragma unroll
    for (int i = 0; i < 48; i++) f[i] = pack_bf16(d[2 * i], d[2 * i + 1]);
}

template <class F>
__device__ __forceinline__ void proj_gemm(float (&d)[96], const uint32_t (&a)[48], uint64_t dsc, uint32_t img, F after) {
#pragma unroll
    for (int s = 0; s < 12; s++) {
        if (s == 0) wgmma_n192<true>(d, a[4 * s], a[4 * s + 1], a[4 * s + 2], a[4 * s + 3], desc_at(dsc, img - s_ring + (s >> 2) * kWChunk + (s & 3) * 32));
        else wgmma_n192<false>(d, a[4 * s], a[4 * s + 1], a[4 * s + 2], a[4 * s + 3], desc_at(dsc, img - s_ring + (s >> 2) * kWChunk + (s & 3) * 32));
        if (s == 11) wg_commit();
        after(s);
    }
}
__device__ __forceinline__ void pack_out(const float (&acc)[96], uint32_t (&po)[48]) {
#pragma unroll
    for (int g = 0; g < 6; g++)
#pragma unroll
        for (int q = 0; q < 4; q++) {
            po[8 * g + q] = pack_bf16(acc[16 * g + 4 * q], acc[16 * g + 4 * q + 1]);
            po[8 * g + 4 + q] = pack_bf16(acc[16 * g + 4 * q + 2], acc[16 * g + 4 * q + 3]);
        }
}
template <bool PINNED = true>
__device__ __forceinline__ void store_one(bool on, uint8_t* p0, uint8_t* p1, const uint32_t (&po)[48], int n) {
    if (PINNED) __syncwarp();
    asm volatile("{\n.reg .pred p;\nsetp.ne.u32 p, %5, 0;\n@p st.global.v4.u32 [%0], {%1, %2, %3, %4};\n}\n"
                 ::"l"(((n & 1) ? p1 : p0) + (n >> 1) * 64), "r"(po[4 * n]), "r"(po[4 * n + 1]), "r"(po[4 * n + 2]), "r"(po[4 * n + 3]), "r"((uint32_t)on) : "memory");
}

template <int N>
__device__ __forceinline__ float tree_max(const float (&v)[N]) {
    float t[N];
#pragma unroll
    for (int i = 0; i < N; i++) t[i] = v[i];
#pragma unroll
    for (int w = 1; w < N; w *= 2)
#pragma unroll
        for (int i = 0; i + w < N; i += 2 * w) t[i] = fmaxf(t[i], t[i + w]);
    return t[0];
}
template <int N>
__device__ __forceinline__ float tree_sum(const float (&v)[N]) {
    float t[N];
#pragma unroll
    for (int i = 0; i < N; i++) t[i] = v[i];
#pragma unroll
    for (int w = 1; w < N; w *= 2)
#pragma unroll
        for (int i = 0; i + w < N; i += 2 * w) t[i] += t[i + w];
    return t[0];
}

template <int B>
__device__ __forceinline__ void pick(uint32_t h, uint32_t ok, const float* s, float& v0, float& v1) {
    asm("{\n.reg .pred p, q0, q1;\n.reg .b32 t;\nand.b32 t, %6, %7;\nsetp.ne.u32 p, t, 0;\n"
        "and.b32 t, %8, %9;\nsetp.ne.u32 q0, t, 0;\nand.b32 t, %8, %10;\nsetp.ne.u32 q1, t, 0;\n"
        "@q0 selp.f32 %0, %3, %2, p;\n@q1 selp.f32 %1, %5, %4, p;\n}\n"
        : "+f"(v0), "+f"(v1)
        : "f"(s[0]), "f"(s[1]), "f"(s[2]), "f"(s[3]), "r"(h), "n"(1 << ((4 * B) % 7)), "r"(ok), "n"(1 << (2 * B)), "n"(2 << (2 * B)));
}
template <int B, class F>
__device__ __forceinline__ void for_blocks(F f) {
    if constexpr (B > 0) { for_blocks<B - 1>(f); f(std::integral_constant<int, B - 1>{}); }
}
__device__ __forceinline__ void gather_outer(const float (&s)[44], uint32_t h, uint32_t ok, float (&v0)[14], float (&v1)[14]) {
    for_blocks<11>([&](auto B) {
        constexpr int b = B.value < 8 ? (B.value >> 1) + 7 * (B.value & 1) : B.value - 4;
        pick<b>(h, ok, &s[4 * b], v0[b], v1[b]);
    });
}
__device__ __forceinline__ void gather_mid(const float (&sE)[16], uint32_t h, uint32_t ok, float (&v0)[14], float (&v1)[14]) {
    for_blocks<4>([&](auto B) { pick<10 + B.value>(h, ok, &sE[4 * B.value], v0[10 + B.value], v1[10 + B.value]); });
}
__device__ __forceinline__ float quad_max(float m) {
    m = fmaxf(m, __shfl_xor_sync(0xffffffffu, m, 1));
    return fmaxf(m, __shfl_xor_sync(0xffffffffu, m, 2));
}
__device__ __forceinline__ float quad_sum(float s) {
    s += __shfl_xor_sync(0xffffffffu, s, 1);
    return s + __shfl_xor_sync(0xffffffffu, s, 2);
}
template <int B0, int B1>
__device__ __forceinline__ void exp_route(float (&v0)[14], float (&v1)[14], float m0, float m1, const uint4& r, bool even, uint32_t (&y)[14]) {
#pragma unroll
    for (int b = B0; b < B1; b++) { v0[b] = ex2(v0[b] - m0); v1[b] = ex2(v1[b] - m1); }
#pragma unroll
    for (int b = B0; b < B1; b += 2) {
        const uint32_t x0 = pack_bf16(v0[b], v1[b]), x1 = pack_bf16(v0[b + 1], v1[b + 1]);
        const uint32_t u = __shfl_sync(0xffffffffu, even ? x0 : x1, r.x);
        const uint32_t w = __shfl_sync(0xffffffffu, even ? x1 : x0, r.y);
        y[b] = __byte_perm(u, w, r.z); y[b + 1] = __byte_perm(u, w, r.w);
    }
}
template <int BIT0, int N0, int N1>
__device__ __forceinline__ void unfold(const uint32_t (&y)[14], uint32_t fold, uint32_t (&p)[12]) {
    for_blocks<N1 - N0>([&](auto N) {
        constexpr int n = N0 + N.value;
        asm("{\n.reg .pred p;\n.reg .b32 t;\nand.b32 t, %4, %5;\nsetp.ne.u32 p, t, 0;\nselp.b32 %0, %2, 0, p;\nselp.b32 %1, %3, 0, p;\n}\n"
            : "=r"(p[2 * n]), "=r"(p[2 * n + 1]) : "r"(y[2 * n]), "r"(y[2 * n + 1]), "r"(fold), "n"(1 << (BIT0 + n)));
    });
}
__device__ __forceinline__ void keep(bool never, uint32_t a, uint32_t b, uint32_t c, uint32_t d) {
    asm volatile("{\n.reg .pred p;\nsetp.ne.u32 p, %4, 0;\n@p st.volatile.shared.v4.u32 [%5], {%0, %1, %2, %3};\n}\n"
                 ::"r"(a), "r"(b), "r"(c), "r"(d), "r"((uint32_t)never), "r"(s_trace) : "memory");
}

__device__ __forceinline__ uint32_t wimg_offset(uint32_t row, uint32_t s, uint32_t j) {
    return (s >> 2) * kWChunk + row * 128 + (((2 * (s & 3) + (j >> 1)) ^ (row & 7)) << 4) + (j & 1) * 8;
}

__device__ __forceinline__ void ldsm4(uint32_t (&r)[4], uint32_t addr) {
    asm volatile("ldmatrix.sync.aligned.m8n8.x4.shared.b16 {%0, %1, %2, %3}, [%4];" : "=r"(r[0]), "=r"(r[1]), "=r"(r[2]), "=r"(r[3]) : "r"(addr) : "memory");
}
__device__ __forceinline__ void ldsm4_t(uint32_t (&r)[4], uint32_t addr) {
    asm volatile("ldmatrix.sync.aligned.m8n8.x4.trans.shared.b16 {%0, %1, %2, %3}, [%4];" : "=r"(r[0]), "=r"(r[1]), "=r"(r[2]), "=r"(r[3]) : "r"(addr) : "memory");
}
__device__ __forceinline__ void m_partial(const uint8_t* wqkv, uint32_t mt, uint32_t s, uint32_t q, uint32_t lane, uint32_t zero) {
    const uint32_t r8 = lane >> 2, col = q * 128 + (lane & 3) * 16;
    const uint8_t* pa = wqkv + (16 * mt + r8) * 1152 + col;
    const uint8_t* pb = wqkv + (16 * s + 8 * (r8 & 2) + (r8 & 5)) * 1152 + col;
    uint4 A[2][2], B[4][2];
#pragma unroll
    for (int c = 0; c < 2; c++) {
#pragma unroll
        for (int h = 0; h < 2; h++) A[h][c] = ldg(pa + 384 + h * 8 * 1152 + c * 64);
#pragma unroll
        for (int n = 0; n < 4; n++) B[n][c] = ldg(pb + ((n & 1) * 8 + (n & 2)) * 1152 + c * 64);
    }
#pragma unroll
    for (int i = 0; i < 4; i++) { uint4& a = A[i >> 1][i & 1]; a.x ^= zero; a.y ^= zero; a.z ^= zero; a.w ^= zero; }
#pragma unroll
    for (int n = 0; n < 4; n++) {
        float d[4] = {0.f, 0.f, 0.f, 0.f};
#pragma unroll
        for (int c = 0; c < 2; c++) {
            mma16816(d, A[0][c].x, A[1][c].x, A[0][c].y, A[1][c].y, B[n][c].x, B[n][c].y);
            mma16816(d, A[0][c].z, A[1][c].z, A[0][c].w, A[1][c].w, B[n][c].z, B[n][c].w);
        }
        asm volatile("st.shared.v4.f32 [%0], {%1, %2, %3, %4};" ::"r"(s_wv + q * 2048 + n * 512 + lane * 16), "f"(d[0]), "f"(d[1]), "f"(d[2]), "f"(d[3]) : "memory");
    }
}
__device__ __forceinline__ void m_reduce(uint32_t e, uint32_t lane, float (&d)[2][4]) {
#pragma unroll
    for (int n = 0; n < 2; n++) {
        float t[3][4];
#pragma unroll
        for (int q = 0; q < 3; q++)
            asm volatile("ld.shared.v4.f32 {%0, %1, %2, %3}, [%4];" : "=f"(t[q][0]), "=f"(t[q][1]), "=f"(t[q][2]), "=f"(t[q][3]) : "r"(s_wv + q * 2048 + e * 1024 + n * 512 + lane * 16) : "memory");
#pragma unroll
        for (int i = 0; i < 4; i++) d[n][i] = (t[0][i] + t[1][i] + t[2][i]) * kScaleLog2e;
    }
}
__device__ __forceinline__ void w_piece(uint32_t q, uint32_t lane, float (&d)[2][4]) {
    const uint32_t rr = lane & 7, mi = lane >> 3, kr = 4 * (rr >> 1) + (mi & 2) + (rr & 1);
    const uint32_t pa = s_wv + q * 32 + (4 * (mi & 2) + rr) * 96 + ((mi & 1) << 4);
    const uint32_t pb = s_wv + 3 * 6144 + kr * 128 + (((mi & 1) ^ (kr & 7)) << 4);
    float e[2][4];
#pragma unroll
    for (int i = 0; i < 8; i++) (&d[0][0])[i] = (&e[0][0])[i] = 0.f;
#pragma unroll
    for (int k = 0; k < 12; k++) {
        uint32_t aq[4], bq[4];
        ldsm4_t(aq, pa + k * 1536);
        ldsm4(bq, (pb ^ ((k & 3) << 5)) + (k >> 2) * 2048);
        mma16816(k & 1 ? e[0] : d[0], aq[0], aq[1], aq[2], aq[3], bq[0], bq[1]);
        mma16816(k & 1 ? e[1] : d[1], aq[0], aq[1], aq[2], aq[3], bq[2], bq[3]);
    }
#pragma unroll
    for (int i = 0; i < 8; i++) (&d[0][0])[i] += (&e[0][0])[i];
}
__device__ __forceinline__ uint32_t piece_offset(uint32_t which, uint32_t s, uint32_t mt, uint32_t lane) {
    const uint32_t r8 = lane >> 2;
    return which * kWBytes + wimg_offset(which ? 32 * (mt >> 1) + 8 * (r8 >> 1) + 4 * (mt & 1) + (r8 & 1) : 16 * mt + r8, s, lane & 3);
}
__device__ __forceinline__ void piece_store(Scratch* g, uint32_t par, uint32_t off0, uint32_t which, const float (&d)[2][4]) {
#pragma unroll
    for (int hf = 0; hf < 2; hf++) {
        const uint32_t off = off0 ^ (hf ? which ? 288 : 1024 : 0);
        const uint32_t a = pack_bf16(d[0][2 * hf], d[0][2 * hf + 1]), b = pack_bf16(d[1][2 * hf], d[1][2 * hf + 1]);
        asm volatile("st.relaxed.gpu.global.v2.u32 [%0], {%1, %2};" ::"l"(g->img[0][0] + (par + off)), "r"(a ? a : 0x8000u), "r"(b) : "memory");
    }
}
__device__ __forceinline__ void piece_clear(Scratch* g, uint32_t par, uint32_t off0, uint32_t which) {
#pragma unroll
    for (int hf = 0; hf < 2; hf++)
        asm volatile("st.relaxed.gpu.global.v2.u32 [%0], {%1, %1};" ::"l"(g->img[0][0] + (par + (off0 ^ (hf ? which ? 288 : 1024 : 0)))), "r"(0) : "memory");
}

__device__ __forceinline__ uint32_t ld_relaxed(const uint32_t* p) {
    uint32_t v;
    asm volatile("ld.relaxed.gpu.global.u32 %0, [%1];" : "=r"(v) : "l"(p) : "memory");
    return v;
}
__device__ __forceinline__ void count_up(uint32_t* p) {
    asm volatile("red.relaxed.gpu.global.add.u32 [%0], %1;" ::"l"(p), "r"(1) : "memory");
}
__device__ __forceinline__ void bulk_g2s(uint32_t dst, const void* src, uint32_t bytes, uint32_t bar) {
    asm volatile("cp.async.bulk.shared::cluster.global.mbarrier::complete_tx::bytes [%0], [%1], %2, [%3];"
                 ::"r"(dst), "l"(src), "r"(bytes), "r"(bar)
                 : "memory");
}

__global__ void __launch_bounds__(kThreads, 1)
nat_fused_kernel(const uint8_t* __restrict__ x, const uint8_t* __restrict__ wqkv, uint8_t* __restrict__ out, Scratch* g,
                 const uint8_t* wo, uint64_t dsc, const __grid_constant__ Maps maps) {
    const int tid = threadIdx.x, lane = tid & 31;
    const int warp = __shfl_sync(0xffffffffu, tid >> 5, 0);
    const int wg = warp >> 2, wq = warp & 3, r8 = lane >> 2, j = lane & 3;
    const int cta = blockIdx.x;
    const Work w = decode_work(cta);
    const uint32_t jq = (cta < 124 ? cta + 8 : cta - 124) / 11u, jr = (cta < 124 ? cta + 8 : cta - 124) - 11 * jq;
    const uint32_t which = jr >= 6, jhi = which ? jr - 6 : jq, jlo = which ? jq : 2 * jr;
    const bool has_job = jr < 10;
    if (wg == 2 && wq < 3) {
#pragma unroll
        for (int r = 0; r < 3; r++)
            asm volatile("st.shared.v4.u32 [%0], {%1, %1, %1, %1};" ::"r"(s_ring + wq * kRingChunk + (r == 0 ? 84 : r == 1 ? 88 : 204) * 128 + lane * 16), "r"(0) : "memory");
        asm volatile("fence.proxy.async.shared::cta;" ::: "memory");
    }
    if (x == nullptr) return;
    const uint32_t t_start = clock_now();
    if (wg == 2) {
        asm volatile("setmaxnreg.dec.sync.aligned.u32 24;");
        if (wq < 3) {
            if (lane < 3 && cta < 128) {
                const uint32_t row = 3 * (cta >> 1) + wq;
                asm volatile("prefetch.global.L2 [%0];" ::"l"((cta & 1 ? wo + row * 384 : wqkv + row * 1152 + 768) + lane * 128));
            }
            asm volatile("bar.sync 7, 192;" ::: "memory");
            const uint32_t par = lds_volatile(s_par);
            uint32_t phase = 0;
#pragma unroll 1
            for (uint32_t c = 0; c < 6; c++) {
                const uint32_t part = c * kWChunk + wq * (kWChunk / 3), img = 8 * min(c, 3u);
                mbar_wait(bar_img + 8 * c, 0);
                if (SPEC && c == 0 && lane == 0) mbar_arrive(bar_ok);
                if (wq == 0) TRW(10 + c);
#pragma unroll 1
                while (true) {
                    uint32_t lo = ~0u;
#pragma unroll
                    for (int q = 0; q < 8; q++) lo = min(lo, lds_volatile(s_m + part + lane * 32 + (lane & 12) * 2 + q * 1024));
                    if (__all_sync(0xffffffffu, lo) || phase > 65535) break;
                    if (elect()) {
                        mbar_expect_tx(bar_redo + 8 * wq, kWChunk / 3);
                        bulk_g2s(s_m + part, g->img[0][0] + par + part, kWChunk / 3, bar_redo + 8 * wq);
                    }
                    mbar_wait(bar_redo + 8 * wq, phase++ & 1);
                }
                if (c == 2 && phase) asm volatile("st.shared.u32 [%0], %1;" ::"r"(s_again), "r"(1) : "memory");
                if ((c == 2 || c == 5) && lane == 0) mbar_arrive(bar_ok + img);
            }
        } else {
            uint32_t launch = ld_relaxed(&g->launches);
            const CUtensorMap* map = &maps.m[w.sv == kPixBytes ? 2 : 0];
            if (elect()) {
#pragma unroll
                for (int i = 0; i < 20 + 3 * !!EARLY; i++) mbar_init(s_bar + 8 * i, i < 13 ? 1 : i < 18 ? 3 : 4);
                asm volatile("fence.mbarrier_init.release.cluster;" ::: "memory");
                prefetch_map(map + 1);
                expect_tx_only(bar_a, sizeof(Table));
                bulk_g2s(s_tab, &maps.tables->t[w.step < 0], sizeof(Table), bar_a);
            }
            if (which && has_job && elect()) {
                mbar_expect_tx(bar_wop, 4 * 6144);
                tma_3d(s_wv, &maps.wo, bar_wop, 0, jhi);
                tma_3d(s_wv + 3 * 6144, &maps.wv, bar_wop, 16 * jlo, 6);
            }
            int u = w.u, v = w.v;
            uint32_t wait_bar = bar_use, wait_par = 1, slot = 0;
#pragma unroll 1
            for (int step = 0; step < 7 - w.corner; step++) {
                const bool first = step == 0 || (w.corner && step == 4);
                const int row = v + 4 + (first ? -w.step : w.step) / 2, ou = origin_u(u);
                const bool final = EARLY && step == 6 - w.corner;
                uint32_t dst = final ? s_m : s_ring + (first ? 0 : slot), mid = (final ? s_m : s_ring) + kOffMid + 512, bar = first ? bar_a : bar_b;
                if (final) { wait_bar = bar_free; wait_par = 0; }
                if (!EARLY) mbar_wait(wait_bar, wait_par);
                if (!EARLY) TRW(24 + step);
#pragma unroll 1
                for (int ch = (cta & 1) * kC, n = 0; n < 3; n++, ch += 64, dst += kRingChunk, mid += kRingChunk) {
                    if (EARLY) mbar_wait(wait_bar, wait_par);
                    if (EARLY && n == 0) TRW(24 + step);
                    if (final && EARLY == 2) wait_bar += 8;
                    if (elect()) {
                        mbar_expect_tx(bar, first ? kSlotBytes : kSlotBytes + kMidBytes);
                        tma_box(dst, map, bar, ch, ou, (cta >> 1) & 1, row);
                    }
                    if (!first) {
                        if (elect()) tma_box(mid, map + 1, bar, ch, ou, (cta >> 1) & 1, v + 6);
                        bar += 8;
                    }
                }
                if (step == 0) {
                    launch /= kGrid;
                    asm volatile("st.shared.v4.u32 [%0], {%1, %2, %2, %2};" ::"r"(s_par), "r"((launch & 1) * 2 * kWBytes), "r"(0) : "memory");
                    asm volatile("bar.arrive 5, 128;\nbar.arrive 3, 160;\nbar.arrive 4, 160;" ::: "memory");
                }
                if (step < 2) {
                    if (step) {
                        if (lane == 0) count_up(&g->launches);
                        asm volatile("bar.sync 6, 128;" ::: "memory");
                    }
                    wait_until(t_start, step ? TN(5, kTimeW) : TN(6, kTimeM));
                    TRW(5 + 4 * step);
#pragma unroll 1
                    for (int c = 3 * step; c < 3 + 3 * step; c++)
                        if (elect()) {
                            mbar_expect_tx(bar_img + 8 * c, kWChunk);
                            bulk_g2s(s_m + c * kWChunk, g->img[launch & 1][0] + c * kWChunk, kWChunk, bar_img + 8 * c);
                        }
                }
                const bool again = w.corner && step == 3;
                wait_bar = step == 0 ? bar_img + 8 * TN(1, 1) : again ? bar_use + 8 : bar_use;
                if (!again) {
                    wait_par = slot ? 0 : step != 0;
                    slot ^= kSlotStride;
                    if (w.corner && step == 2) { u += 8; v -= 8; } else if (step) v += w.step;
                }
            }
        }
        TRDUMP();
        return;
    }
    if (wg == 1 && wq < 3) {
        if (!which) m_partial(wqkv, jhi, jlo, wq, lane, (uint32_t)dsc & 1);
        const uint32_t off = piece_offset(which, which ? jlo : jlo + wq, which ? 3 * jhi + wq : jhi, lane);
        asm volatile("bar.sync %0, 128;" ::"r"(5 + (off >> 31)) : "memory");
        const uint32_t par = lds_volatile(s_par);
        if (has_job && wq < 2 + which) {
            float d[2][4];
            if (wq == 0) TRX(which ? 1 : 18);
            if (which) {
                mbar_wait(bar_wop, 0);
                if (wq == 0) TRX(2);
                w_piece(wq, lane, d);
            } else {
                m_reduce(wq, lane, d);
            }
            piece_store(g, par, off, which, d);
            __syncwarp();
            piece_clear(g, 2 * kWBytes - par, off, which);
            if (wq == 0) TRX(which ? 3 : 0);
        }
        asm volatile("bar.arrive 7, 192;\nbar.arrive 6, 128;" ::: "memory");
    }
    const int order = w.step < 0 ? warp ^ 3 : warp;
    int tu = w.u, tv = w.v + w.step * wg;
    const int du2 = w.corner ? 8 : 0, dv2 = w.corner ? 0 : 2 * w.step;
    uint32_t o0, o1;
    wait_until(t_start, START_TIME);
    asm volatile("setmaxnreg.inc.sync.aligned.u32 240;");
    w.pixel_offsets(tu + r8, tv + 2 * wq, j, o0, o1);
    uint32_t fa[48];
    {
        RawX raw;
        load_raw(raw, x, o0, o1);
        asm volatile("bar.sync %0, 160;" ::"r"(3 + wg) : "memory");
        raw_to_frags(raw, 0, fa);
        pin(fa);
    }
    mbar_wait(bar_ok, 0);
    const uint64_t dA = dsc + wg * (kSlotStride >> 4), dB = dsc + (wg ^ 1) * (kSlotStride >> 4);

    float acc[96];
    uint32_t po[48];
    uint32_t c0, c1;
    asm volatile("" : "=r"(c0), "=r"(c1));
#pragma unroll
    for (int q = 0; q < 48; q++) asm volatile("" : "=r"(po[q]));
#pragma unroll 1
    for (int i = wg; i < w.ntiles; i += 2) {
        const bool first = i == 0, last = i == w.ntiles - 1;

        TRF(8 + 16 * k);
        uint8_t *p0 = out + c0, *p1 = out + c1;
#pragma unroll 1
        for (uint32_t seen = 0;;) {
        wg_fence();
        if (!first) turn_wait(wg);
        proj_gemm(acc, fa, dsc, s_m, [&](int s) {
            if (s == 11 && !first) turn_pass(wg);
            const int n = __builtin_popcount(QSLOTS & ((1 << s) - 1));
            if (((QSLOTS >> s) & 1) && n < 12) store_one(i >= 2, out + c0, out + c1, po, n);
            if (s == 3 || s == 7) { if (EARLY == 2) wg_commit(); mbar_wait((SPEC ? bar_img : bar_ok) + 2 * s + 2, 0); wg_fence(); }
        });
        __syncwarp();
        TRF(9 + 16 * k);
            if (!first) break;
            mbar_wait(bar_ok + 16, 0);
            if (lds_volatile(s_again) == seen) break;
            wg_wait<0>();
            seen = 1;
        }
        c0 = o0; c1 = o1;
        w.pixel_offsets(tu + du2 + r8, tv + dv2 + 2 * wq, j, o0, o1);
        if (i + 2 >= w.ntiles) o0 = o1 = 0;
        if (EARLY == 2) {
            wg_wait<2>();
            if (last && lane == 0) mbar_arrive(bar_free);
            wg_wait<1>();
            if (last && lane == 0) mbar_arrive(bar_free + 8);
        }
        wg_wait<0>();
        if (EARLY && last && lane == 0) mbar_arrive(bar_free + (EARLY == 2 ? 16 : 0));
        const uint64_t dE = EARLY && last ? dsc + ((s_m - s_ring) >> 4) : dsc, dN = EARLY && last ? dE : dB;
        pin(acc);
        TR(11 + 16 * k);
        TRT(80 + k);
#pragma unroll
        for (int n = __builtin_popcount(QSLOTS); n < 12 - __builtin_popcount(ASLOTS) - __builtin_popcount(BSLOTS); n++) store_one(i >= 2, p0, p1, po, n);
        acc_to_frags(acc, fa);
        pin(fa);

        float sA[44], sE[16], sB[44];
        RawX nxt;
        if (!first) turn_wait(wg);
        mbar_wait(bar_a, w.corner ? i >> 1 : 0);
        wg_fence();
#pragma unroll
        for (int s = 0; s < 12; s++) {
            if (s == 0) wgmma_n88<true>(sA, fa[4 * s], fa[4 * s + 1], fa[4 * s + 2], fa[4 * s + 3], desc_at(dA, (s >> 2) * kRingChunk + (s & 3) * 32));
            else wgmma_n88<false>(sA, fa[4 * s], fa[4 * s + 1], fa[4 * s + 2], fa[4 * s + 3], desc_at(dA, (s >> 2) * kRingChunk + (s & 3) * 32));
            if (s == 11) { wg_commit(); if (!first) turn_pass(wg); }
            if ((ASLOTS >> s) & 1) store_one(i >= 2, p0, p1, po, 12 - __builtin_popcount(BSLOTS) - __builtin_popcount(ASLOTS >> s));
        }
#pragma unroll
        for (int s = 12; s < 16; s++)
            if ((ASLOTS >> s) & 1) store_one(i >= 2, p0, p1, po, 12 - __builtin_popcount(BSLOTS) - __builtin_popcount(ASLOTS >> s));
        TRF(12 + 16 * k);
        const int vq = tv + 2 * wq;
        const uint4 tabu = lds128(s_tab + offsetof(Table, u) + (window_start(tu + r8) - origin_u(tu)) * 64 + j * 16);
        const uint4 tabv = lds128(s_tab + offsetof(Table, v) + (window_start(vq) + window_start(vq + 1) - 2 * tv) * 64 + j * 16);
        const uint4 route = lds128(s_tab + lane * 16);
        load_raw(nxt, x, o0, o1);
        float v0[14], v1[14];
#pragma unroll
        for (int b = 0; b < 14; b++) v0[b] = v1[b] = __int_as_float(0xff800000);
        wg_wait<0>();
        pin(sA);
        gather_outer(sA, tabu.x, tabv.x, v0, v1);
        pin(v0); pin(v1);
        if (!first) turn_wait(wg);
#pragma unroll
        for (int c = 0; c < 3; c++) {
            mbar_wait(bar_b + 8 * c, wg);
            TRF(64 + 4 * k + c);
            wg_fence();
#pragma unroll
            for (int s = 4 * c; s < 4 * c + 4; s++) {
                if (s == 0) wgmma_n88<true>(sB, fa[4 * s], fa[4 * s + 1], fa[4 * s + 2], fa[4 * s + 3], desc_at(dN, c * kRingChunk + (s & 3) * 32));
                else wgmma_n88<false>(sB, fa[4 * s], fa[4 * s + 1], fa[4 * s + 2], fa[4 * s + 3], desc_at(dN, c * kRingChunk + (s & 3) * 32));
                if ((BSLOTS >> s) & 1) store_one(i >= 2, p0, p1, po, 12 - __builtin_popcount(BSLOTS >> s));
            }
        }
        wg_commit();
#pragma unroll
        for (int s = 0; s < 12; s++)
            if (s == 0) wgmma_n32<true>(sE, fa[4 * s], fa[4 * s + 1], fa[4 * s + 2], fa[4 * s + 3], desc_at(dE, kOffMid + (s >> 2) * kRingChunk + (s & 3) * 32));
            else wgmma_n32<false>(sE, fa[4 * s], fa[4 * s + 1], fa[4 * s + 2], fa[4 * s + 3], desc_at(dE, kOffMid + (s >> 2) * kRingChunk + (s & 3) * 32));
        wg_commit();
        if (OSPLIT || !last) turn_pass(wg);
        TRF(13 + 16 * k);
        wg_wait<1>();
        pin(sB);
        gather_outer(sB, tabu.w, tabv.y, v0, v1);
        wg_wait<0>();
        pin(sE);
        TRF(14 + 16 * k);
        gather_mid(sE, tabu.w, tabv.z, v0, v1);
        const float m0 = quad_max(tree_max(v0)), m1 = quad_max(tree_max(v1));

        uint32_t y[14], pa[12], pb[12];
        exp_route<0, 14>(v0, v1, m0, m1, route, (j & 1) == 0, y);
        float s0 = tree_sum(v0), s1 = tree_sum(v1);
        asm volatile("" : "+f"(s0), "+f"(s1));
        unfold<0, 0, 6>(y, tabv.w, pa);
        if (OSPLIT || !last) turn_wait(wg + (y[0] >> 31));
        TRF(15 + 16 * k + (y[13] >> 31));
        wg_fence();
        wgmma_sp_n192_tb<true, 0>(acc, pa[0], pa[1], pa[2], pa[3], desc_at(dA, kToV), tabu.y);
        wgmma_sp_n192_tb<false, 1>(acc, pa[4], pa[5], pa[6], pa[7], desc_at(dA, kToV + 4096), tabu.y);
        wgmma_sp_n192_tb<false, 0>(acc, pa[8], pa[9], pa[10], pa[11], desc_at(dA, kToV + 8192), tabu.z);
        wgmma_sp_n192_tb<false, 1>(acc, EARLY && j == 0 ? 0u : y[10], EARLY && j == 0 ? 0u : y[11], y[12], y[13], desc_at(dE, kToV + kOffMid), tabu.z);
        wg_commit();
        unfold<8, 0, 6>(y, tabv.w, pb);
        wg_fence();
        wgmma_sp_n192_tb<false, 0>(acc, pb[0], pb[1], pb[2], pb[3], desc_at(dN, kToV), tabu.y);
        wgmma_sp_n192_tb<false, 1>(acc, pb[4], pb[5], pb[6], pb[7], desc_at(dN, kToV + 4096), tabu.y);
        wgmma_sp_n192_tb<false, 0>(acc, pb[8], pb[9], pb[10], pb[11], desc_at(dN, kToV + 8192), tabu.z);
        wg_commit();
        if (!last) turn_pass(wg);
        TRF(16 + 16 * k);
        wg_wait<1>();
        if (lane == 0) mbar_arrive(bar_use);
        TRF(17 + 16 * k);
        mbar_wait(bar_ok + 24, 0);
        wg_wait<0>();
        if (lane == 0) mbar_arrive(bar_use + 8);
        pin(acc);
        TR(18 + 16 * k);

        acc_to_frags(acc, po);
        pin(po);
        if (!last) turn_wait(wg);
        wg_fence();
        proj_gemm(acc, po, dsc, s_wv, [&](int s) {
            if (s + 1 == OSPLIT && i + 2 == w.ntiles) { turn_pass(wg); turn_wait(wg); }
        });
        if (!last) turn_pass(wg);
        TRF(19 + 16 * k);
        const uint32_t zero = lds_volatile(s_late);
        const float inv0 = rcp(quad_sum(s0 + __uint_as_float(zero))), inv1 = rcp(quad_sum(s1 + __uint_as_float(zero)));
        raw_to_frags(nxt, zero, fa);
        pin(fa);
#pragma unroll
        for (int q = 0; q < 48; q += 4) keep(wqkv == nullptr, fa[q], fa[q + 1], fa[q + 2], fa[q + 3]);
        keep(wqkv == nullptr, __float_as_uint(inv0), __float_as_uint(inv1), zero, lane);
        TRF(20 + 16 * k);
        tu += du2; tv += dv2;
        wg_wait<0>();
        pin(acc);
        TR(21 + 16 * k);
#pragma unroll
        for (int q = 0; q < 96; q++) acc[q] *= q & 2 ? inv1 : inv0;
        pack_out(acc, po);
#pragma unroll
        for (int n = 0; n < INLOOP; n++) store_one<false>(last, out + c0, out + c1, po, n);
        pin(po);
    }
#pragma unroll
    for (int n = 0; n < 12; n++) {
        if (NAP) asm volatile("{\n.reg .pred p;\nsetp.eq.u32 p, %0, 0;\n@p nanosleep.u32 %1;\n}\n" ::"r"(wg), "n"(NAP) : "memory");
        store_one<false>(n >= INLOOP || wg == 0, out + c0, out + c1, po, n);
    }
    TRE(7);
    TRG(1);
    TRDUMP();
}

typedef CUresult (*EncodeTiledFn)(CUtensorMap*, CUtensorMapDataType, cuuint32_t, void*, const cuuint64_t*, const cuuint64_t*,
                                  const cuuint32_t*, const cuuint32_t*, CUtensorMapInterleave, CUtensorMapSwizzle,
                                  CUtensorMapL2promotion, CUtensorMapFloatOOBfill);

bool make_maps(EncodeTiledFn fn, Maps* maps, void* x, void* wqkv, void* wo) {
    const cuuint64_t pix2 = 2 * kPixBytes, row = (cuuint64_t)kHW * kPixBytes;
    const cuuint32_t estr[5] = {1, 1, 1, 1, 1};
    bool ok = true;
    for (int tr = 0; tr < 2; tr++)
        for (int b = 0; b < 2; b++) {
            const cuuint64_t su = tr ? 2 * row : pix2, sv = tr ? pix2 : 2 * row;
            const cuuint64_t dims[5] = {2 * kC, 2, 105, 2, 112};
            const cuuint64_t strides[4] = {7 * su, su, row, sv};
            const cuuint32_t box[5] = {64, 2, 7, 1, b ? 2u : 6u};
            ok = ok && fn(&maps->m[2 * tr + b], CU_TENSOR_MAP_DATA_TYPE_BFLOAT16, 5, x, dims, strides, box, estr,
                          CU_TENSOR_MAP_INTERLEAVE_NONE, CU_TENSOR_MAP_SWIZZLE_128B, CU_TENSOR_MAP_L2_PROMOTION_L2_128B,
                          CU_TENSOR_MAP_FLOAT_OOB_FILL_NONE) == CUDA_SUCCESS;
        }
    for (int b = 0; b < 2; b++) {
        const cuuint64_t dims[3] = {b ? 64u : 48u, kC, b ? 9u : 4u}, strides[2] = {(b ? 3u : 1u) * kPixBytes, b ? 128u : 96u};
        const cuuint32_t box[3] = {b ? 64u : 48u, b ? 16u : 192u, b ? 3u : 1u};
        ok = ok && fn(b ? &maps->wv : &maps->wo, CU_TENSOR_MAP_DATA_TYPE_BFLOAT16, 3, b ? wqkv : wo, dims, strides, box, estr,
                      CU_TENSOR_MAP_INTERLEAVE_NONE, b ? CU_TENSOR_MAP_SWIZZLE_128B : CU_TENSOR_MAP_SWIZZLE_NONE, CU_TENSOR_MAP_L2_PROMOTION_L2_128B,
                      CU_TENSOR_MAP_FLOAT_OOB_FILL_NONE) == CUDA_SUCCESS;
    }
    return ok;
}

}

extern "C" void kernel_launch(void* const* d_in, const int* in_sizes, int n_in, void* d_out, int out_size) {
    static EncodeTiledFn encode = nullptr;
    static Scratch* scratch = nullptr;
    static Tables* tables = nullptr;
    if (!encode) {
        int dev = 0, reserved = 0;
        cudaFuncAttributes attr;
        cudaGetDevice(&dev);
        cudaDeviceGetAttribute(&reserved, cudaDevAttrReservedSharedMemoryPerBlock, dev);
        cudaFuncGetAttributes(&attr, nat_fused_kernel);
        if (reserved != (int)kSmemBase || attr.sharedSizeBytes != 0) return;
        cudaGetSymbolAddress((void**)&scratch, g_scratch);
        cudaGetSymbolAddress((void**)&tables, g_tables);
        void* fn = nullptr;
        cudaDriverEntryPointQueryResult st;
        cudaGetDriverEntryPoint("cuTensorMapEncodeTiled", &fn, cudaEnableDefault, &st);
        encode = (EncodeTiledFn)fn;
        cudaFuncSetAttribute(nat_fused_kernel, cudaFuncAttributeMaxDynamicSharedMemorySize, kSmemBytes);
    }
    Maps maps;
    maps.tables = tables;
    if (!encode || !make_maps(encode, &maps, d_in[0], d_in[1], d_in[2])) return;
    nat_fused_kernel<<<kGrid, kThreads, kSmemBytes>>>((const uint8_t*)d_in[0], (const uint8_t*)d_in[1], (uint8_t*)d_out, scratch, (const uint8_t*)d_in[2],
                                                      kDescRing, maps);
}
```

```cpp
#include <cuda_runtime.h>
#include <cuda_bf16.h>
#include <cuda.h>
#include <stdint.h>
#include <type_traits>
#include <stdlib.h>
#include <stdio.h>
#include <stddef.h>

#define KEEPFA 1
#define ASLOTS 0x3800
#define BSLOTS 0x6
#define QSLOTS 0x78a
#define OSPLIT 2
#define NAP 40
#define SPEC 1
#define EARLY 2
#define PFROM 24
#define PNAP 160
#define INLOOP 3

namespace {

constexpr int kC          = 192;
constexpr int kHW         = 224;
constexpr int kPixBytes   = kC * 2;
constexpr int kSlotBytes  = 84 * 128;
constexpr int kMidBytes   = 28 * 128;
constexpr int kOffMid     = 88 * 128;
constexpr int kSlotStride = 120 * 128;
constexpr int kRingChunk  = 208 * 128;
constexpr int kWChunk     = 192 * 128;
constexpr int kWBytes     = 3 * kWChunk;
constexpr uint32_t kSmemBase = 1024;
constexpr uint32_t s_ring = kSmemBase, s_m = s_ring + 3 * kRingChunk, s_wv = s_m + kWBytes, s_bar = s_wv + kWBytes;
constexpr uint32_t bar_b = s_bar, bar_img = s_bar + 24, bar_redo = s_bar + 72, bar_wop = s_bar + 96, bar_a = s_bar + 104,
                   bar_ok = s_bar + 112, bar_use = s_bar + 144, bar_free = s_bar + 160;
constexpr uint32_t s_par = s_bar + 192, s_late = s_bar + 196, s_again = s_bar + 200, s_tab = s_bar + 256, s_trace = s_tab + 2048;
constexpr int kSmemBytes  = s_trace + 2048 - kSmemBase;
constexpr int kThreads    = 384;
constexpr int kGrid       = 132;
constexpr int kTimeM = 2750, kTimeW = 5100;
constexpr float kScaleLog2e = 0.07216878364870322f * 1.4426950408889634f;

struct Maps {
    CUtensorMap m[4];
    CUtensorMap wo, wv;
    const struct Tables* tables;
};
#define TN(i, dflt) (dflt)
#define START_TIME (wg ? 850 + 500 * order : 250 + 560 * order)

struct Scratch {
    uint8_t img[2][2][kWBytes];
    uint32_t launches;
};
__device__ __align__(1024) Scratch g_scratch;

struct Table {
    uint32_t route[32][4];
    uint32_t u[8][4][4];
    uint32_t v[16][4][4];
};
struct Tables { Table t[2]; };
constexpr Tables make_tables() {
    Tables r = {};
    for (int rev = 0; rev < 2; rev++)
        for (int j = 0; j < 4; j++) {
            Table& t = r.t[rev];
            for (int q = 0; q < 8; q++) {
                uint32_t* e = t.route[4 * q + j];
                e[0] = 4 * q + 2 * (j & 1) + (j >> 1); e[1] = e[0] ^ 1;
                e[2] = j < 2 ? 0x5410u : 0x1054u; e[3] = e[2] + 0x2222u;
                e = t.u[q][j];
                for (int n = 0; n < 7; n++) e[0] |= ((n + j) % 7 < q ? 1u : 0u) << n;
                e[3] = e[0];
                for (int k = 0; k < 2; k++) {
                    const int step = 2 * k + (j >> 1), p0 = (step < 3 ? 16 * step : 40) + 8 * (j & 1);
                    uint32_t m = 0x8888u;
                    for (int n = 0; n < 8; n++) m |= ((p0 + n) % 7 < q ? 1u : 0u) << (2 * n);
                    e[1 + k] = m * 0x10001u;
                }
            }
            for (int sum = 0; sum < 15; sum++) {
                uint32_t* e = t.v[sum][j];
                for (int row = 0; row < 2; row++)
                    for (int b = 0; b < 14; b++) {
                        const int off = (sum + row) / 2, p = 4 * b + j;
                        const uint32_t bit = 1u << (2 * b + row);
                        if (p < 42 && p >= 7 * off) e[rev] |= bit;
                        if (p < 7 * off - 7) e[1 - rev] |= bit;
                        if (p >= 42 && p >= 7 * off && p < 7 * off + 49) e[2] |= bit;
                    }
                for (int n = 0; n < 6; n++)
                    if (8 * n + 2 * j < 42) e[3] |= 1u << (n + ((8 * n + 2 * j >= 7 * (sum / 2 & ~1)) != rev ? 0 : 8));
            }
        }
    return r;
}
__device__ __align__(128) const Tables g_tables = make_tables();

#define WO4(i) "=f"(d[i]), "=f"(d[i + 1]), "=f"(d[i + 2]), "=f"(d[i + 3])
#define RW4(i) "+f"(d[i]), "+f"(d[i + 1]), "+f"(d[i + 2]), "+f"(d[i + 3])

template <bool FIRST>
__device__ __forceinline__ void wgmma_n192(float (&d)[96], uint32_t a0, uint32_t a1, uint32_t a2, uint32_t a3, uint64_t descb) {
    if constexpr (FIRST) {
        asm volatile(
            "wgmma.mma_async.sync.aligned.m64n192k16.f32.bf16.bf16 "
            "{%0, %1, %2, %3, %4, %5, %6, %7, %8, %9, %10, %11, %12, %13, %14, %15, %16, %17, %18, %19, %20, %21, %22, %23, "
            "%24, %25, %26, %27, %28, %29, %30, %31, %32, %33, %34, %35, %36, %37, %38, %39, %40, %41, %42, %43, %44, %45, %46, %47, "
            "%48, %49, %50, %51, %52, %53, %54, %55, %56, %57, %58, %59, %60, %61, %62, %63, %64, %65, %66, %67, %68, %69, %70, %71, "
            "%72, %73, %74, %75, %76, %77, %78, %79, %80, %81, %82, %83, %84, %85, %86, %87, %88, %89, %90, %91, %92, %93, %94, %95}, "
            "{%96, %97, %98, %99}, %100, 0, 1, 1, 0;"
            : WO4(0), WO4(4), WO4(8), WO4(12), WO4(16), WO4(20), WO4(24), WO4(28), WO4(32), WO4(36), WO4(40), WO4(44),
              WO4(48), WO4(52), WO4(56), WO4(60), WO4(64), WO4(68), WO4(72), WO4(76), WO4(80), WO4(84), WO4(88), WO4(92)
            : "r"(a0), "r"(a1), "r"(a2), "r"(a3), "l"(descb));
    } else {
        asm volatile(
            "wgmma.mma_async.sync.aligned.m64n192k16.f32.bf16.bf16 "
            "{%0, %1, %2, %3, %4, %5, %6, %7, %8, %9, %10, %11, %12, %13, %14, %15, %16, %17, %18, %19, %20, %21, %22, %23, "
            "%24, %25, %26, %27, %28, %29, %30, %31, %32, %33, %34, %35, %36, %37, %38, %39, %40, %41, %42, %43, %44, %45, %46, %47, "
            "%48, %49, %50, %51, %52, %53, %54, %55, %56, %57, %58, %59, %60, %61, %62, %63, %64, %65, %66, %67, %68, %69, %70, %71, "
            "%72, %73, %74, %75, %76, %77, %78, %79, %80, %81, %82, %83, %84, %85, %86, %87, %88, %89, %90, %91, %92, %93, %94, %95}, "
            "{%96, %97, %98, %99}, %100, 1, 1, 1, 0;"
            : RW4(0), RW4(4), RW4(8), RW4(12), RW4(16), RW4(20), RW4(24), RW4(28), RW4(32), RW4(36), RW4(40), RW4(44),
              RW4(48), RW4(52), RW4(56), RW4(60), RW4(64), RW4(68), RW4(72), RW4(76), RW4(80), RW4(84), RW4(88), RW4(92)
            : "r"(a0), "r"(a1), "r"(a2), "r"(a3), "l"(descb));
    }
}

template <bool FIRST>
__device__ __forceinline__ void wgmma_n88(float (&d)[44], uint32_t a0, uint32_t a1, uint32_t a2, uint32_t a3, uint64_t descb) {
    if constexpr (FIRST) {
        asm volatile(
            "wgmma.mma_async.sync.aligned.m64n88k16.f32.bf16.bf16 "
            "{%0, %1, %2, %3, %4, %5, %6, %7, %8, %9, %10, %11, %12, %13, %14, %15, %16, %17, %18, %19, %20, %21, %22, %23, "
            "%24, %25, %26, %27, %28, %29, %30, %31, %32, %33, %34, %35, %36, %37, %38, %39, %40, %41, %42, %43}, "
            "{%44, %45, %46, %47}, %48, 0, 1, 1, 0;"
            : WO4(0), WO4(4), WO4(8), WO4(12), WO4(16), WO4(20), WO4(24), WO4(28), WO4(32), WO4(36), WO4(40)
            : "r"(a0), "r"(a1), "r"(a2), "r"(a3), "l"(descb));
    } else {
        asm volatile(
            "wgmma.mma_async.sync.aligned.m64n88k16.f32.bf16.bf16 "
            "{%0, %1, %2, %3, %4, %5, %6, %7, %8, %9, %10, %11, %12, %13, %14, %15, %16, %17, %18, %19, %20, %21, %22, %23, "
            "%24, %25, %26, %27, %28, %29, %30, %31, %32, %33, %34, %35, %36, %37, %38, %39, %40, %41, %42, %43}, "
            "{%44, %45, %46, %47}, %48, 1, 1, 1, 0;"
            : RW4(0), RW4(4), RW4(8), RW4(12), RW4(16), RW4(20), RW4(24), RW4(28), RW4(32), RW4(36), RW4(40)
            : "r"(a0), "r"(a1), "r"(a2), "r"(a3), "l"(descb));
    }
}

template <bool FIRST>
__device__ __forceinline__ void wgmma_n32(float (&d)[16], uint32_t a0, uint32_t a1, uint32_t a2, uint32_t a3, uint64_t descb) {
    if constexpr (FIRST) {
        asm volatile(
            "wgmma.mma_async.sync.aligned.m64n32k16.f32.bf16.bf16 "
            "{%0, %1, %2, %3, %4, %5, %6, %7, %8, %9, %10, %11, %12, %13, %14, %15}, "
            "{%16, %17, %18, %19}, %20, 0, 1, 1, 0;"
            : WO4(0), WO4(4), WO4(8), WO4(12)
            : "r"(a0), "r"(a1), "r"(a2), "r"(a3), "l"(descb));
    } else {
        asm volatile(
            "wgmma.mma_async.sync.aligned.m64n32k16.f32.bf16.bf16 "
            "{%0, %1, %2, %3, %4, %5, %6, %7, %8, %9, %10, %11, %12, %13, %14, %15}, "
            "{%16, %17, %18, %19}, %20, 1, 1, 1, 0;"
            : RW4(0), RW4(4), RW4(8), RW4(12)
            : "r"(a0), "r"(a1), "r"(a2), "r"(a3), "l"(descb));
    }
}

template <bool FIRST, int SEL>
__device__ __forceinline__ void wgmma_sp_n192_tb(float (&d)[96], uint32_t a0, uint32_t a1, uint32_t a2, uint32_t a3, uint64_t descb, uint32_t meta) {
    if constexpr (FIRST) {
        asm volatile(
            "wgmma.mma_async.sp.sync.aligned.m64n192k32.f32.bf16.bf16 "
            "{%0, %1, %2, %3, %4, %5, %6, %7, %8, %9, %10, %11, %12, %13, %14, %15, %16, %17, %18, %19, %20, %21, %22, %23, "
            "%24, %25, %26, %27, %28, %29, %30, %31, %32, %33, %34, %35, %36, %37, %38, %39, %40, %41, %42, %43, %44, %45, %46, %47, "
            "%48, %49, %50, %51, %52, %53, %54, %55, %56, %57, %58, %59, %60, %61, %62, %63, %64, %65, %66, %67, %68, %69, %70, %71, "
            "%72, %73, %74, %75, %76, %77, %78, %79, %80, %81, %82, %83, %84, %85, %86, %87, %88, %89, %90, %91, %92, %93, %94, %95}, "
            "{%96, %97, %98, %99}, %100, %101, %102, 0, 1, 1, 1;"
            : WO4(0), WO4(4), WO4(8), WO4(12), WO4(16), WO4(20), WO4(24), WO4(28), WO4(32), WO4(36), WO4(40), WO4(44),
              WO4(48), WO4(52), WO4(56), WO4(60), WO4(64), WO4(68), WO4(72), WO4(76), WO4(80), WO4(84), WO4(88), WO4(92)
            : "r"(a0), "r"(a1), "r"(a2), "r"(a3), "l"(descb), "r"(meta), "n"(SEL));
    } else {
        asm volatile(
            "wgmma.mma_async.sp.sync.aligned.m64n192k32.f32.bf16.bf16 "
            "{%0, %1, %2, %3, %4, %5, %6, %7, %8, %9, %10, %11, %12, %13, %14, %15, %16, %17, %18, %19, %20, %21, %22, %23, "
            "%24, %25, %26, %27, %28, %29, %30, %31, %32, %33, %34, %35, %36, %37, %38, %39, %40, %41, %42, %43, %44, %45, %46, %47, "
            "%48, %49, %50, %51, %52, %53, %54, %55, %56, %57, %58, %59, %60, %61, %62, %63, %64, %65, %66, %67, %68, %69, %70, %71, "
            "%72, %73, %74, %75, %76, %77, %78, %79, %80, %81, %82, %83, %84, %85, %86, %87, %88, %89, %90, %91, %92, %93, %94, %95}, "
            "{%96, %97, %98, %99}, %100, %101, %102, 1, 1, 1, 1;"
            : RW4(0), RW4(4), RW4(8), RW4(12), RW4(16), RW4(20), RW4(24), RW4(28), RW4(32), RW4(36), RW4(40), RW4(44),
              RW4(48), RW4(52), RW4(56), RW4(60), RW4(64), RW4(68), RW4(72), RW4(76), RW4(80), RW4(84), RW4(88), RW4(92)
            : "r"(a0), "r"(a1), "r"(a2), "r"(a3), "l"(descb), "r"(meta), "n"(SEL));
    }
}

#define TR(slot)
#define TRX(slot)
#define TRE(slot)
#define TRT(slot)
#define TRF(slot)
#define TRW(slot)
#define TRG(slot)
#define TRDUMP()

__device__ __forceinline__ void wg_fence() { asm volatile("wgmma.fence.sync.aligned;" ::: "memory"); }
__device__ __forceinline__ void wg_commit() { asm volatile("wgmma.commit_group.sync.aligned;" ::: "memory"); }
template <int N>
__device__ __forceinline__ void wg_wait() { asm volatile("wgmma.wait_group.sync.aligned %0;" ::"n"(N) : "memory"); }

template <int N>
__device__ __forceinline__ void pin(float (&d)[N]) {
#pragma unroll
    for (int i = 0; i < N; i++) asm volatile("" : "+f"(d[i])::"memory");
}
template <int N>
__device__ __forceinline__ void pin(uint32_t (&d)[N]) {
#pragma unroll
    for (int i = 0; i < N; i++) asm volatile("" : "+r"(d[i])::"memory");
}

constexpr uint64_t kDescRing = ((uint64_t)((1u << 30) | (1024u >> 4)) << 32) | (1u << 16) | (s_ring >> 4);
constexpr uint32_t kToV = ((kRingChunk >> 4) - 1) << 20;
__device__ __forceinline__ uint64_t desc_at(uint64_t base, uint32_t byte_off) {
    uint64_t d;
    asm volatile("add.s64 %0, %1, %2;" : "=l"(d) : "l"(base), "l"((uint64_t)(byte_off >> 4)));
    return d;
}

__device__ __forceinline__ void mbar_init(uint32_t bar, uint32_t count) {
    asm volatile("mbarrier.init.shared::cta.b64 [%0], %1;" ::"r"(bar), "r"(count) : "memory");
}
__device__ __forceinline__ void mbar_expect_tx(uint32_t bar, uint32_t bytes) {
    asm volatile("mbarrier.arrive.expect_tx.shared::cta.b64 _, [%0], %1;" ::"r"(bar), "r"(bytes) : "memory");
}
__device__ __forceinline__ void expect_tx_only(uint32_t bar, uint32_t bytes) {
    asm volatile("mbarrier.expect_tx.relaxed.cta.shared::cta.b64 [%0], %1;" ::"r"(bar), "r"(bytes) : "memory");
}
__device__ __forceinline__ void mbar_arrive(uint32_t bar) {
    asm volatile("mbarrier.arrive.shared::cta.b64 _, [%0];" ::"r"(bar) : "memory");
}
__device__ __forceinline__ void mbar_wait(uint32_t bar, uint32_t parity) {
    asm volatile(
        "{\n.reg .pred p;\n"
        "W: mbarrier.try_wait.parity.shared::cta.b64 p, [%0], %1;\n"
        "@!p bra W;\n}\n"
        ::"r"(bar), "r"(parity) : "memory");
}
__device__ __forceinline__ uint32_t clock_now() {
    uint32_t c;
    asm volatile("mov.u32 %0, %%clock;" : "=r"(c)::"memory");
    return c;
}
__device__ __forceinline__ void wait_until(uint32_t t0, int t) {
    if (t == 0) return;
    while ((int)(clock_now() - t0) < t) {}
}
__device__ __forceinline__ bool elect() {
    uint32_t ok;
    asm volatile("{\n.reg .pred p;\nelect.sync _|p, 0xffffffff;\nselp.u32 %0, 1, 0, p;\n}\n" : "=r"(ok));
    return ok != 0;
}
__device__ __forceinline__ void turn_wait(int wg) { asm volatile("bar.sync %0, 256;" ::"r"(1 + wg) : "memory"); }
__device__ __forceinline__ void turn_pass(int wg) { asm volatile("bar.arrive %0, 256;" ::"r"(2 - wg) : "memory"); }

__device__ __forceinline__ void tma_box(uint32_t dst, const CUtensorMap* map, uint32_t bar, int c0, int c2, int c3, int c4) {
    asm volatile(
        "cp.async.bulk.tensor.5d.shared::cluster.global.mbarrier::complete_tx::bytes [%0], [%1, {%3, %4, %5, %6, %7}], [%2];"
        ::"r"(dst), "l"(map), "r"(bar), "r"(c0), "r"(0), "r"(c2), "r"(c3), "r"(c4)
        : "memory");
}
__device__ __forceinline__ void tma_3d(uint32_t dst, const CUtensorMap* map, uint32_t bar, int c1, int c2) {
    asm volatile("cp.async.bulk.tensor.3d.shared::cluster.global.mbarrier::complete_tx::bytes [%0], [%1, {%3, %4, %5}], [%2];"
                 ::"r"(dst), "l"(map), "r"(bar), "r"(0), "r"(c1), "r"(c2)
                 : "memory");
}
__device__ __forceinline__ void prefetch_map(const CUtensorMap* map) {
    asm volatile("prefetch.tensormap [%0];" ::"l"(map) : "memory");
}
__device__ __forceinline__ uint4 ldg(const void* p) {
    uint4 v;
    asm volatile("ld.global.v4.u32 {%0, %1, %2, %3}, [%4];" : "=r"(v.x), "=r"(v.y), "=r"(v.z), "=r"(v.w) : "l"(p) : "memory");
    return v;
}
__device__ __forceinline__ uint32_t pack_bf16(float lo, float hi) {
    uint32_t r;
    asm("cvt.rn.bf16x2.f32 %0, %1, %2;" : "=r"(r) : "f"(hi), "f"(lo));
    return r;
}
__device__ __forceinline__ float ex2(float x) {
    float y;
    asm("ex2.approx.ftz.f32 %0, %1;" : "=f"(y) : "f"(x));
    return y;
}
__device__ __forceinline__ float rcp(float x) {
    float y;
    asm("rcp.approx.ftz.f32 %0, %1;" : "=f"(y) : "f"(x));
    return y;
}
__device__ __forceinline__ void mma16816(float (&d)[4], uint32_t a0, uint32_t a1, uint32_t a2, uint32_t a3, uint32_t b0, uint32_t b1) {
    asm volatile("mma.sync.aligned.m16n8k16.row.col.f32.bf16.bf16.f32 {%0, %1, %2, %3}, {%4, %5, %6, %7}, {%8, %9}, {%0, %1, %2, %3};"
                 : "+f"(d[0]), "+f"(d[1]), "+f"(d[2]), "+f"(d[3])
                 : "r"(a0), "r"(a1), "r"(a2), "r"(a3), "r"(b0), "r"(b1));
}
__device__ __forceinline__ uint4 lds128(uint32_t addr) {
    uint4 v;
    asm volatile("ld.volatile.shared.v4.u32 {%0, %1, %2, %3}, [%4];" : "=r"(v.x), "=r"(v.y), "=r"(v.z), "=r"(v.w) : "r"(addr) : "memory");
    return v;
}
__device__ __forceinline__ uint32_t lds_volatile(uint32_t addr) {
    uint32_t v;
    asm volatile("ld.volatile.shared.u32 %0, [%1];" : "=r"(v) : "r"(addr) : "memory");
    return v;
}

__device__ __forceinline__ int window_start(int n) { return min(max(n, 0), 105); }
__device__ __forceinline__ int origin_u(int u) { return min(max(u, 0), 98); }

struct Work {
    int u, v;
    int step;
    uint32_t su, sv;
    uint32_t base;
    bool corner;
    int ntiles;
    __device__ __forceinline__ void pixel_offsets(int qu, int qv, int j, uint32_t& o0, uint32_t& o1) const {
        const uint32_t b = (qu + window_start(qu)) * su + j * 16 + base;
        o0 = b + (qv + window_start(qv)) * sv;
        o1 = b + (qv + 1 + window_start(qv + 1)) * sv;
    }
};

__device__ __forceinline__ Work decode_work(int c) {
    Work w;
    const bool transposed = (c >> 4) == 7;
    const int px = 6 * (c & 1), py = 3 * (c & 2);
    w.corner = c >= 128;
    w.step = 8 - 4 * (c & 4);
    w.u = (c < 112 ? c & ~7 : 96 + (c & 8)) + (transposed ? py : px) - 6;
    w.v = (w.corner ? 96 : 48 - 2 * (c & 4)) + (transposed ? px : py) - 6;
    w.su = transposed ? kHW * kPixBytes : kPixBytes;
    w.sv = transposed ? kPixBytes : kHW * kPixBytes;
    w.base = px * (kPixBytes / 6) + py * (kHW * kPixBytes / 6) + 6 * (kHW + 1) * kPixBytes;
    w.ntiles = w.corner ? 4 : 6;
    return w;
}

struct RawX { uint4 a[6], b[6]; };
__device__ __forceinline__ void load_raw(RawX& r, const uint8_t* base, uint32_t o0, uint32_t o1) {
    __syncwarp();
#pragma unroll
    for (int c = 0; c < 6; c++) { r.a[c] = ldg(base + o0 + c * 64); r.b[c] = ldg(base + o1 + c * 64); }
    __syncwarp();
}
__device__ __forceinline__ void raw_to_frags(const RawX& r, uint32_t zero, uint32_t (&f)[48]) {
#pragma unroll
    for (int c = 0; c < 6; c++) {
        asm volatile("{\n.reg .b32 t, u;\nadd.u32 t, %4, %8;\nadd.u32 u, %5, %8;\nxor.b32 %0, %6, %8;\nxor.b32 %1, %7, %8;\n"
                     "xor.b32 %2, t, %8;\nxor.b32 %3, u, %8;\n}\n"
                     : "=&r"(f[8 * c + 1]), "=&r"(f[8 * c + 3]), "=&r"(f[8 * c + 4]), "=&r"(f[8 * c + 6])
                     : "r"(r.a[c].y), "r"(r.a[c].w), "r"(r.b[c].x), "r"(r.b[c].z), "r"(zero));
        f[8 * c + 0] = r.a[c].x; f[8 * c + 2] = r.a[c].z; f[8 * c + 5] = r.b[c].y; f[8 * c + 7] = r.b[c].w;
    }
}
__device__ __forceinline__ void acc_to_frags(const float (&d)[96], uint32_t (&f)[48]) {
#pragma unroll
    for (int i = 0; i < 48; i++) f[i] = pack_bf16(d[2 * i], d[2 * i + 1]);
}

template <class F>
__device__ __forceinline__ void proj_gemm(float (&d)[96], const uint32_t (&a)[48], uint64_t dsc, uint32_t img, F after) {
#pragma unroll
    for (int s = 0; s < 12; s++) {
        if (s == 0) wgmma_n192<true>(d, a[4 * s], a[4 * s + 1], a[4 * s + 2], a[4 * s + 3], desc_at(dsc, img - s_ring + (s >> 2) * kWChunk + (s & 3) * 32));
        else wgmma_n192<false>(d, a[4 * s], a[4 * s + 1], a[4 * s + 2], a[4 * s + 3], desc_at(dsc, img - s_ring + (s >> 2) * kWChunk + (s & 3) * 32));
        if (s == 11) wg_commit();
        after(s);
    }
}
__device__ __forceinline__ void pack_out(const float (&acc)[96], uint32_t (&po)[48]) {
#pragma unroll
    for (int g = 0; g < 6; g++)
#pragma unroll
        for (int q = 0; q < 4; q++) {
            po[8 * g + q] = pack_bf16(acc[16 * g + 4 * q], acc[16 * g + 4 * q + 1]);
            po[8 * g + 4 + q] = pack_bf16(acc[16 * g + 4 * q + 2], acc[16 * g + 4 * q + 3]);
        }
}
template <bool PINNED = true>
__device__ __forceinline__ void store_one(bool on, uint8_t* p0, uint8_t* p1, const uint32_t (&po)[48], int n) {
    if (PINNED) __syncwarp();
    asm volatile("{\n.reg .pred p;\nsetp.ne.u32 p, %5, 0;\n@p st.global.v4.u32 [%0], {%1, %2, %3, %4};\n}\n"
                 ::"l"(((n & 1) ? p1 : p0) + (n >> 1) * 64), "r"(po[4 * n]), "r"(po[4 * n + 1]), "r"(po[4 * n + 2]), "r"(po[4 * n + 3]), "r"((uint32_t)on) : "memory");
}

template <int N>
__device__ __forceinline__ float tree_max(const float (&v)[N]) {
    float t[N];
#pragma unroll
    for (int i = 0; i < N; i++) t[i] = v[i];
#pragma unroll
    for (int w = 1; w < N; w *= 2)
#pragma unroll
        for (int i = 0; i + w < N; i += 2 * w) t[i] = fmaxf(t[i], t[i + w]);
    return t[0];
}
template <int N>
__device__ __forceinline__ float tree_sum(const float (&v)[N]) {
    float t[N];
#pragma unroll
    for (int i = 0; i < N; i++) t[i] = v[i];
#pragma unroll
    for (int w = 1; w < N; w *= 2)
#pragma unroll
        for (int i = 0; i + w < N; i += 2 * w) t[i] += t[i + w];
    return t[0];
}

template <int B>
__device__ __forceinline__ void pick(uint32_t h, uint32_t ok, const float* s, float& v0, float& v1) {
    asm("{\n.reg .pred p, q0, q1;\n.reg .b32 t;\nand.b32 t, %6, %7;\nsetp.ne.u32 p, t, 0;\n"
        "and.b32 t, %8, %9;\nsetp.ne.u32 q0, t, 0;\nand.b32 t, %8, %10;\nsetp.ne.u32 q1, t, 0;\n"
        "@q0 selp.f32 %0, %3, %2, p;\n@q1 selp.f32 %1, %5, %4, p;\n}\n"
        : "+f"(v0), "+f"(v1)
        : "f"(s[0]), "f"(s[1]), "f"(s[2]), "f"(s[3]), "r"(h), "n"(1 << ((4 * B) % 7)), "r"(ok), "n"(1 << (2 * B)), "n"(2 << (2 * B)));
}
template <int B, class F>
__device__ __forceinline__ void for_blocks(F f) {
    if constexpr (B > 0) { for_blocks<B - 1>(f); f(std::integral_constant<int, B - 1>{}); }
}
__device__ __forceinline__ void gather_outer(const float (&s)[44], uint32_t h, uint32_t ok, float (&v0)[14], float (&v1)[14]) {
    for_blocks<11>([&](auto B) {
        constexpr int b = B.value < 8 ? (B.value >> 1) + 7 * (B.value & 1) : B.value - 4;
        pick<b>(h, ok, &s[4 * b], v0[b], v1[b]);
    });
}
__device__ __forceinline__ void gather_mid(const float (&sE)[16], uint32_t h, uint32_t ok, float (&v0)[14], float (&v1)[14]) {
    for_blocks<4>([&](auto B) { pick<10 + B.value>(h, ok, &sE[4 * B.value], v0[10 + B.value], v1[10 + B.value]); });
}
__device__ __forceinline__ float quad_max(float m) {
    m = fmaxf(m, __shfl_xor_sync(0xffffffffu, m, 1));
    return fmaxf(m, __shfl_xor_sync(0xffffffffu, m, 2));
}
__device__ __forceinline__ float quad_sum(float s) {
    s += __shfl_xor_sync(0xffffffffu, s, 1);
    return s + __shfl_xor_sync(0xffffffffu, s, 2);
}
template <int B0, int B1>
__device__ __forceinline__ void exp_route(float (&v0)[14], float (&v1)[14], float m0, float m1, const uint4& r, bool even, uint32_t (&y)[14]) {
#pragma unroll
    for (int b = B0; b < B1; b++) { v0[b] = ex2(v0[b] - m0); v1[b] = ex2(v1[b] - m1); }
#pragma unroll
    for (int b = B0; b < B1; b += 2) {
        const uint32_t x0 = pack_bf16(v0[b], v1[b]), x1 = pack_bf16(v0[b + 1], v1[b + 1]);
        const uint32_t u = __shfl_sync(0xffffffffu, even ? x0 : x1, r.x);
        const uint32_t w = __shfl_sync(0xffffffffu, even ? x1 : x0, r.y);
        y[b] = __byte_perm(u, w, r.z); y[b + 1] = __byte_perm(u, w, r.w);
    }
}
template <int BIT0, int N0, int N1>
__device__ __forceinline__ void unfold(const uint32_t (&y)[14], uint32_t fold, uint32_t (&p)[12]) {
    for_blocks<N1 - N0>([&](auto N) {
        constexpr int n = N0 + N.value;
        asm("{\n.reg .pred p;\n.reg .b32 t;\nand.b32 t, %4, %5;\nsetp.ne.u32 p, t, 0;\nselp.b32 %0, %2, 0, p;\nselp.b32 %1, %3, 0, p;\n}\n"
            : "=r"(p[2 * n]), "=r"(p[2 * n + 1]) : "r"(y[2 * n]), "r"(y[2 * n + 1]), "r"(fold), "n"(1 << (BIT0 + n)));
    });
}
__device__ __forceinline__ void keep(bool never, uint32_t a, uint32_t b, uint32_t c, uint32_t d) {
    asm volatile("{\n.reg .pred p;\nsetp.ne.u32 p, %4, 0;\n@p st.volatile.shared.v4.u32 [%5], {%0, %1, %2, %3};\n}\n"
                 ::"r"(a), "r"(b), "r"(c), "r"(d), "r"((uint32_t)never), "r"(s_trace) : "memory");
}

__device__ __forceinline__ uint32_t wimg_offset(uint32_t row, uint32_t s, uint32_t j) {
    return (s >> 2) * kWChunk + row * 128 + (((2 * (s & 3) + (j >> 1)) ^ (row & 7)) << 4) + (j & 1) * 8;
}

__device__ __forceinline__ void ldsm4(uint32_t (&r)[4], uint32_t addr) {
    asm volatile("ldmatrix.sync.aligned.m8n8.x4.shared.b16 {%0, %1, %2, %3}, [%4];" : "=r"(r[0]), "=r"(r[1]), "=r"(r[2]), "=r"(r[3]) : "r"(addr) : "memory");
}
__device__ __forceinline__ void ldsm4_t(uint32_t (&r)[4], uint32_t addr) {
    asm volatile("ldmatrix.sync.aligned.m8n8.x4.trans.shared.b16 {%0, %1, %2, %3}, [%4];" : "=r"(r[0]), "=r"(r[1]), "=r"(r[2]), "=r"(r[3]) : "r"(addr) : "memory");
}
__device__ __forceinline__ void m_partial(const uint8_t* wqkv, uint32_t mt, uint32_t s, uint32_t q, uint32_t lane, uint32_t zero) {
    const uint32_t r8 = lane >> 2, col = q * 128 + (lane & 3) * 16;
    const uint8_t* pa = wqkv + (16 * mt + r8) * 1152 + col;
    const uint8_t* pb = wqkv + (16 * s + 8 * (r8 & 2) + (r8 & 5)) * 1152 + col;
    uint4 A[2][2], B[4][2];
#pragma unroll
    for (int c = 0; c < 2; c++) {
#pragma unroll
        for (int h = 0; h < 2; h++) A[h][c] = ldg(pa + 384 + h * 8 * 1152 + c * 64);
#pragma unroll
        for (int n = 0; n < 4; n++) B[n][c] = ldg(pb + ((n & 1) * 8 + (n & 2)) * 1152 + c * 64);
    }
#pragma unroll
    for (int i = 0; i < 4; i++) { uint4& a = A[i >> 1][i & 1]; a.x ^= zero; a.y ^= zero; a.z ^= zero; a.w ^= zero; }
#pragma unroll
    for (int n = 0; n < 4; n++) {
        float d[4] = {0.f, 0.f, 0.f, 0.f};
#pragma unroll
        for (int c = 0; c < 2; c++) {
            mma16816(d, A[0][c].x, A[1][c].x, A[0][c].y, A[1][c].y, B[n][c].x, B[n][c].y);
            mma16816(d, A[0][c].z, A[1][c].z, A[0][c].w, A[1][c].w, B[n][c].z, B[n][c].w);
        }
        asm volatile("st.shared.v4.f32 [%0], {%1, %2, %3, %4};" ::"r"(s_wv + q * 2048 + n * 512 + lane * 16), "f"(d[0]), "f"(d[1]), "f"(d[2]), "f"(d[3]) : "memory");
    }
}
__device__ __forceinline__ void m_reduce(uint32_t e, uint32_t lane, float (&d)[2][4]) {
#pragma unroll
    for (int n = 0; n < 2; n++) {
        float t[3][4];
#pragma unroll
        for (int q = 0; q < 3; q++)
            asm volatile("ld.shared.v4.f32 {%0, %1, %2, %3}, [%4];" : "=f"(t[q][0]), "=f"(t[q][1]), "=f"(t[q][2]), "=f"(t[q][3]) : "r"(s_wv + q * 2048 + e * 1024 + n * 512 + lane * 16) : "memory");
#pragma unroll
        for (int i = 0; i < 4; i++) d[n][i] = (t[0][i] + t[1][i] + t[2][i]) * kScaleLog2e;
    }
}
__device__ __forceinline__ void w_piece(uint32_t q, uint32_t lane, float (&d)[2][4]) {
    const uint32_t rr = lane & 7, mi = lane >> 3, kr = 4 * (rr >> 1) + (mi & 2) + (rr & 1);
    const uint32_t pa = s_wv + q * 32 + (4 * (mi & 2) + rr) * 96 + ((mi & 1) << 4);
    const uint32_t pb = s_wv + 3 * 6144 + kr * 128 + (((mi & 1) ^ (kr & 7)) << 4);
    float e[2][4];
#pragma unroll
    for (int i = 0; i < 8; i++) (&d[0][0])[i] = (&e[0][0])[i] = 0.f;
#pragma unroll
    for (int k = 0; k < 12; k++) {
        uint32_t aq[4], bq[4];
        ldsm4_t(aq, pa + k * 1536);
        ldsm4(bq, (pb ^ ((k & 3) << 5)) + (k >> 2) * 2048);
        mma16816(k & 1 ? e[0] : d[0], aq[0], aq[1], aq[2], aq[3], bq[0], bq[1]);
        mma16816(k & 1 ? e[1] : d[1], aq[0], aq[1], aq[2], aq[3], bq[2], bq[3]);
    }
#pragma unroll
    for (int i = 0; i < 8; i++) (&d[0][0])[i] += (&e[0][0])[i];
}
__device__ __forceinline__ uint32_t piece_offset(uint32_t which, uint32_t s, uint32_t mt, uint32_t lane) {
    const uint32_t r8 = lane >> 2;
    return which * kWBytes + wimg_offset(which ? 32 * (mt >> 1) + 8 * (r8 >> 1) + 4 * (mt & 1) + (r8 & 1) : 16 * mt + r8, s, lane & 3);
}
__device__ __forceinline__ void piece_store(Scratch* g, uint32_t par, uint32_t off0, uint32_t which, const float (&d)[2][4]) {
#pragma unroll
    for (int hf = 0; hf < 2; hf++) {
        const uint32_t off = off0 ^ (hf ? which ? 288 : 1024 : 0);
        const uint32_t a = pack_bf16(d[0][2 * hf], d[0][2 * hf + 1]), b = pack_bf16(d[1][2 * hf], d[1][2 * hf + 1]);
        asm volatile("st.relaxed.gpu.global.v2.u32 [%0], {%1, %2};" ::"l"(g->img[0][0] + (par + off)), "r"(a ? a : 0x8000u), "r"(b) : "memory");
    }
}
__device__ __forceinline__ void piece_clear(Scratch* g, uint32_t par, uint32_t off0, uint32_t which) {
#pragma unroll
    for (int hf = 0; hf < 2; hf++)
        asm volatile("st.relaxed.gpu.global.v2.u32 [%0], {%1, %1};" ::"l"(g->img[0][0] + (par + (off0 ^ (hf ? which ? 288 : 1024 : 0)))), "r"(0) : "memory");
}

__device__ __forceinline__ uint32_t ld_relaxed(const uint32_t* p) {
    uint32_t v;
    asm volatile("ld.relaxed.gpu.global.u32 %0, [%1];" : "=r"(v) : "l"(p) : "memory");
    return v;
}
__device__ __forceinline__ void count_up(uint32_t* p) {
    asm volatile("red.relaxed.gpu.global.add.u32 [%0], %1;" ::"l"(p), "r"(1) : "memory");
}
__device__ __forceinline__ void bulk_g2s(uint32_t dst, const void* src, uint32_t bytes, uint32_t bar) {
    asm volatile("cp.async.bulk.shared::cluster.global.mbarrier::complete_tx::bytes [%0], [%1], %2, [%3];"
                 ::"r"(dst), "l"(src), "r"(bytes), "r"(bar)
                 : "memory");
}

__global__ void __launch_bounds__(kThreads, 1)
nat_fused_kernel(const uint8_t* __restrict__ x, const uint8_t* __restrict__ wqkv, uint8_t* __restrict__ out, Scratch* g,
                 const uint8_t* wo, uint64_t dsc, const __grid_constant__ Maps maps) {
    const int tid = threadIdx.x, lane = tid & 31;
    const int warp = __shfl_sync(0xffffffffu, tid >> 5, 0);
    const int wg = warp >> 2, wq = warp & 3, r8 = lane >> 2, j = lane & 3;
    const int cta = blockIdx.x;
    const Work w = decode_work(cta);
    const uint32_t jq = (cta < 124 ? cta + 8 : cta - 124) / 11u, jr = (cta < 124 ? cta + 8 : cta - 124) - 11 * jq;
    const uint32_t which = jr >= 6, jhi = which ? jr - 6 : jq, jlo = which ? jq : 2 * jr;
    const bool has_job = jr < 10;
    if (wg == 2 && wq < 3) {
#pragma unroll
        for (int r = 0; r < 3; r++)
            asm volatile("st.shared.v4.u32 [%0], {%1, %1, %1, %1};" ::"r"(s_ring + wq * kRingChunk + (r == 0 ? 84 : r == 1 ? 88 : 204) * 128 + lane * 16), "r"(0) : "memory");
        asm volatile("fence.proxy.async.shared::cta;" ::: "memory");
    }
    if (x == nullptr) return;
    const uint32_t t_start = clock_now();
    if (wg == 2) {
        asm volatile("setmaxnreg.dec.sync.aligned.u32 24;");
        if (wq < 3) {
            if (lane < 3 && cta < 128) {
                const uint32_t row = 3 * (cta >> 1) + wq;
                asm volatile("prefetch.global.L2 [%0];" ::"l"((cta & 1 ? wo + row * 384 : wqkv + row * 1152 + 768) + lane * 128));
            }
            asm volatile("bar.sync 7, 192;" ::: "memory");
            const uint32_t par = lds_volatile(s_par);
            uint32_t phase = 0;
#pragma unroll 1
            for (uint32_t c = 0; c < 6; c++) {
                const uint32_t part = c * kWChunk + wq * (kWChunk / 3), img = 8 * min(c, 3u);
                mbar_wait(bar_img + 8 * c, 0);
                if (SPEC && c == 0 && lane == 0) mbar_arrive(bar_ok);
                if (wq == 0) TRW(10 + c);
#pragma unroll 1
                while (true) {
                    uint32_t lo = ~0u;
#pragma unroll
                    for (int q = 0; q < 8; q++) lo = min(lo, lds_volatile(s_m + part + lane * 32 + (lane & 12) * 2 + q * 1024));
                    if (__all_sync(0xffffffffu, lo) || phase > 65535) break;
                    if (elect()) {
                        mbar_expect_tx(bar_redo + 8 * wq, kWChunk / 3);
                        bulk_g2s(s_m + part, g->img[0][0] + par + part, kWChunk / 3, bar_redo + 8 * wq);
                    }
                    mbar_wait(bar_redo + 8 * wq, phase++ & 1);
                }
                if (c == 2 && phase) asm volatile("st.shared.u32 [%0], %1;" ::"r"(s_again), "r"(1) : "memory");
                if ((c == 2 || c == 5) && lane == 0) mbar_arrive(bar_ok + img);
            }
            if (PFROM && wq == 0 && !w.corner) {
#pragma unroll 1
                for (int n = PFROM; n < 48; n++) {
                    uint32_t o0, o1;
                    w.pixel_offsets(w.u + r8, w.step < 0 ? w.v + 7 - n : w.v + n, 8 * j, o0, o1);
                    if (j < 3) asm volatile("prefetch.global.L2 [%0];" ::"l"(x + o0));
                    __nanosleep(PNAP);
                }
            }
        } else {
            uint32_t launch = ld_relaxed(&g->launches);
            const CUtensorMap* map = &maps.m[w.sv == kPixBytes ? 2 : 0];
            if (elect()) {
#pragma unroll
                for (int i = 0; i < 20 + 3 * !!EARLY; i++) mbar_init(s_bar + 8 * i, i < 13 ? 1 : i < 18 ? 3 : 4);
                asm volatile("fence.mbarrier_init.release.cluster;" ::: "memory");
                prefetch_map(map + 1);
                expect_tx_only(bar_a, sizeof(Table));
                bulk_g2s(s_tab, &maps.tables->t[w.step < 0], sizeof(Table), bar_a);
            }
            if (which && has_job && elect()) {
                mbar_expect_tx(bar_wop, 4 * 6144);
                tma_3d(s_wv, &maps.wo, bar_wop, 0, jhi);
                tma_3d(s_wv + 3 * 6144, &maps.wv, bar_wop, 16 * jlo, 6);
            }
            int u = w.u, v = w.v;
            uint32_t wait_bar = bar_use, wait_par = 1, slot = 0;
#pragma unroll 1
            for (int step = 0; step < 7 - w.corner; step++) {
                const bool first = step == 0 || (w.corner && step == 4);
                const int row = v + 4 + (first ? -w.step : w.step) / 2, ou = origin_u(u);
                const bool final = EARLY && step == 6 - w.corner;
                uint32_t dst = final ? s_m : s_ring + (first ? 0 : slot), mid = (final ? s_m : s_ring) + kOffMid + 512, bar = first ? bar_a : bar_b;
                if (final) { wait_bar = bar_free; wait_par = 0; }
                if (!EARLY) mbar_wait(wait_bar, wait_par);
                if (!EARLY) TRW(24 + step);
#pragma unroll 1
                for (int ch = (cta & 1) * kC, n = 0; n < 3; n++, ch += 64, dst += kRingChunk, mid += kRingChunk) {
                    if (EARLY) mbar_wait(wait_bar, wait_par);
                    if (EARLY && n == 0) TRW(24 + step);
                    if (final && EARLY == 2) wait_bar += 8;
                    if (elect()) {
                        mbar_expect_tx(bar, first ? kSlotBytes : kSlotBytes + kMidBytes);
                        tma_box(dst, map, bar, ch, ou, (cta >> 1) & 1, row);
                    }
                    if (!first) {
                        if (elect()) tma_box(mid, map + 1, bar, ch, ou, (cta >> 1) & 1, v + 6);
                        bar += 8;
                    }
                }
                if (step == 0) {
                    launch /= kGrid;
                    asm volatile("st.shared.v4.u32 [%0], {%1, %2, %2, %2};" ::"r"(s_par), "r"((launch & 1) * 2 * kWBytes), "r"(0) : "memory");
                    asm volatile("bar.arrive 5, 128;\nbar.arrive 3, 160;\nbar.arrive 4, 160;" ::: "memory");
                }
                if (step < 2) {
                    if (step) {
                        if (lane == 0) count_up(&g->launches);
                        asm volatile("bar.sync 6, 128;" ::: "memory");
                    }
                    wait_until(t_start, step ? TN(5, kTimeW) : TN(6, kTimeM));
                    TRW(5 + 4 * step);
#pragma unroll 1
                    for (int c = 3 * step; c < 3 + 3 * step; c++)
                        if (elect()) {
                            mbar_expect_tx(bar_img + 8 * c, kWChunk);
                            bulk_g2s(s_m + c * kWChunk, g->img[launch & 1][0] + c * kWChunk, kWChunk, bar_img + 8 * c);
                        }
                }
                const bool again = w.corner && step == 3;
                wait_bar = step == 0 ? bar_img + 8 * TN(1, 1) : again ? bar_use + 8 : bar_use;
                if (!again) {
                    wait_par = slot ? 0 : step != 0;
                    slot ^= kSlotStride;
                    if (w.corner && step == 2) { u += 8; v -= 8; } else if (step) v += w.step;
                }
            }
        }
        TRDUMP();
        return;
    }
    if (wg == 1 && wq < 3) {
        if (!which) m_partial(wqkv, jhi, jlo, wq, lane, (uint32_t)dsc & 1);
        const uint32_t off = piece_offset(which, which ? jlo : jlo + wq, which ? 3 * jhi + wq : jhi, lane);
        asm volatile("bar.sync %0, 128;" ::"r"(5 + (off >> 31)) : "memory");
        const uint32_t par = lds_volatile(s_par);
        if (has_job && wq < 2 + which) {
            float d[2][4];
            if (wq == 0) TRX(which ? 1 : 18);
            if (which) {
                mbar_wait(bar_wop, 0);
                if (wq == 0) TRX(2);
                w_piece(wq, lane, d);
            } else {
                m_reduce(wq, lane, d);
            }
            piece_store(g, par, off, which, d);
            __syncwarp();
            piece_clear(g, 2 * kWBytes - par, off, which);
            if (wq == 0) TRX(which ? 3 : 0);
        }
        asm volatile("bar.arrive 7, 192;\nbar.arrive 6, 128;" ::: "memory");
    }
    const int order = w.step < 0 ? warp ^ 3 : warp;
    int tu = w.u, tv = w.v + w.step * wg;
    const int du2 = w.corner ? 8 : 0, dv2 = w.corner ? 0 : 2 * w.step;
    uint32_t o0, o1;
    wait_until(t_start, START_TIME);
    asm volatile("setmaxnreg.inc.sync.aligned.u32 240;");
    w.pixel_offsets(tu + r8, tv + 2 * wq, j, o0, o1);
    uint32_t fa[48];
    {
        RawX raw;
        load_raw(raw, x, o0, o1);
        asm volatile("bar.sync %0, 160;" ::"r"(3 + wg) : "memory");
        raw_to_frags(raw, 0, fa);
        pin(fa);
    }
    mbar_wait(bar_ok, 0);
    const uint64_t dA = dsc + wg * (kSlotStride >> 4), dB = dsc + (wg ^ 1) * (kSlotStride >> 4);

    float acc[96];
    uint32_t po[48];
    uint32_t c0, c1;
    asm volatile("" : "=r"(c0), "=r"(c1));
#pragma unroll
    for (int q = 0; q < 48; q++) asm volatile("" : "=r"(po[q]));
#pragma unroll 1
    for (int i = wg; i < w.ntiles; i += 2) {
        const bool first = i == 0, last = i == w.ntiles - 1;

        TRF(8 + 16 * k);
        uint8_t *p0 = out + c0, *p1 = out + c1;
#pragma unroll 1
        for (uint32_t seen = 0;;) {
        wg_fence();
        if (!first) turn_wait(wg);
        proj_gemm(acc, fa, dsc, s_m, [&](int s) {
            if (s == 11 && !first) turn_pass(wg);
            const int n = __builtin_popcount(QSLOTS & ((1 << s) - 1));
            if (((QSLOTS >> s) & 1) && n < 12) store_one(i >= 2, out + c0, out + c1, po, n);
            if (s == 3 || s == 7) { if (EARLY == 2) wg_commit(); mbar_wait((SPEC ? bar_img : bar_ok) + 2 * s + 2, 0); wg_fence(); }
        });
        __syncwarp();
        TRF(9 + 16 * k);
            if (!first) break;
            mbar_wait(bar_ok + 16, 0);
            if (lds_volatile(s_again) == seen) break;
            wg_wait<0>();
            seen = 1;
        }
        c0 = o0; c1 = o1;
        w.pixel_offsets(tu + du2 + r8, tv + dv2 + 2 * wq, j, o0, o1);
        if (i + 2 >= w.ntiles) o0 = o1 = 0;
        mbar_wait(bar_a, w.corner ? i >> 1 : 0);
        if (EARLY == 2) {
            wg_wait<2>();
            if (last && lane == 0) mbar_arrive(bar_free);
            wg_wait<1>();
            if (last && lane == 0) mbar_arrive(bar_free + 8);
        }
        wg_wait<0>();
        if (EARLY && last && lane == 0) mbar_arrive(bar_free + (EARLY == 2 ? 16 : 0));
        const uint64_t dE = EARLY && last ? dsc + ((s_m - s_ring) >> 4) : dsc, dN = EARLY && last ? dE : dB;
        pin(acc);
        TR(11 + 16 * k);
        TRT(80 + k);
#pragma unroll
        for (int n = __builtin_popcount(QSLOTS); n < 12 - __builtin_popcount(ASLOTS) - __builtin_popcount(BSLOTS); n++) store_one(i >= 2, p0, p1, po, n);
        acc_to_frags(acc, fa);
        pin(fa);

        float sA[44], sE[16], sB[44];
        RawX nxt;
        if (!first) turn_wait(wg);
        wg_fence();
#pragma unroll
        for (int s = 0; s < 12; s++) {
            if (s == 0) wgmma_n88<true>(sA, fa[4 * s], fa[4 * s + 1], fa[4 * s + 2], fa[4 * s + 3], desc_at(dA, (s >> 2) * kRingChunk + (s & 3) * 32));
            else wgmma_n88<false>(sA, fa[4 * s], fa[4 * s + 1], fa[4 * s + 2], fa[4 * s + 3], desc_at(dA, (s >> 2) * kRingChunk + (s & 3) * 32));
            if (s == 11) { wg_commit(); if (!first) turn_pass(wg); }
            if ((ASLOTS >> s) & 1) store_one(i >= 2, p0, p1, po, 12 - __builtin_popcount(BSLOTS) - __builtin_popcount(ASLOTS >> s));
        }
#pragma unroll
        for (int s = 12; s < 16; s++)
            if ((ASLOTS >> s) & 1) store_one(i >= 2, p0, p1, po, 12 - __builtin_popcount(BSLOTS) - __builtin_popcount(ASLOTS >> s));
        TRF(12 + 16 * k);
        const int vq = tv + 2 * wq;
        const uint4 tabu = lds128(s_tab + offsetof(Table, u) + (window_start(tu + r8) - origin_u(tu)) * 64 + j * 16);
        const uint4 tabv = lds128(s_tab + offsetof(Table, v) + (window_start(vq) + window_start(vq + 1) - 2 * tv) * 64 + j * 16);
        const uint4 route = lds128(s_tab + lane * 16);
        load_raw(nxt, x, o0, o1);
        float v0[14], v1[14];
#pragma unroll
        for (int b = 0; b < 14; b++) v0[b] = v1[b] = __int_as_float(0xff800000);
        wg_wait<0>();
        pin(sA);
        gather_outer(sA, tabu.x, tabv.x, v0, v1);
        pin(v0); pin(v1);
        if (!first) turn_wait(wg);
#pragma unroll
        for (int c = 0; c < 3; c++) {
            mbar_wait(bar_b + 8 * c, wg);
            TRF(64 + 4 * k + c);
            wg_fence();
#pragma unroll
            for (int s = 4 * c; s < 4 * c + 4; s++) {
                if (s == 0) wgmma_n88<true>(sB, fa[4 * s], fa[4 * s + 1], fa[4 * s + 2], fa[4 * s + 3], desc_at(dN, c * kRingChunk + (s & 3) * 32));
                else wgmma_n88<false>(sB, fa[4 * s], fa[4 * s + 1], fa[4 * s + 2], fa[4 * s + 3], desc_at(dN, c * kRingChunk + (s & 3) * 32));
                if ((BSLOTS >> s) & 1) store_one(i >= 2, p0, p1, po, 12 - __builtin_popcount(BSLOTS >> s));
            }
        }
        wg_commit();
#pragma unroll
        for (int s = 0; s < 12; s++)
            if (s == 0) wgmma_n32<true>(sE, fa[4 * s], fa[4 * s + 1], fa[4 * s + 2], fa[4 * s + 3], desc_at(dE, kOffMid + (s >> 2) * kRingChunk + (s & 3) * 32));
            else wgmma_n32<false>(sE, fa[4 * s], fa[4 * s + 1], fa[4 * s + 2], fa[4 * s + 3], desc_at(dE, kOffMid + (s >> 2) * kRingChunk + (s & 3) * 32));
        wg_commit();
        if (OSPLIT || !last) turn_pass(wg);
        TRF(13 + 16 * k);
        wg_wait<1>();
        pin(sB);
        gather_outer(sB, tabu.w, tabv.y, v0, v1);
        wg_wait<0>();
        pin(sE);
        TRF(14 + 16 * k);
        gather_mid(sE, tabu.w, tabv.z, v0, v1);
        const float m0 = quad_max(tree_max(v0)), m1 = quad_max(tree_max(v1));

        uint32_t y[14], pa[12], pb[12];
        exp_route<0, 14>(v0, v1, m0, m1, route, (j & 1) == 0, y);
        float s0 = tree_sum(v0), s1 = tree_sum(v1);
        asm volatile("" : "+f"(s0), "+f"(s1));
        unfold<0, 0, 6>(y, tabv.w, pa);
        if (OSPLIT || !last) turn_wait(wg + (y[0] >> 31));
        TRF(15 + 16 * k + (y[13] >> 31));
        wg_fence();
        wgmma_sp_n192_tb<true, 0>(acc, pa[0], pa[1], pa[2], pa[3], desc_at(dA, kToV), tabu.y);
        wgmma_sp_n192_tb<false, 1>(acc, pa[4], pa[5], pa[6], pa[7], desc_at(dA, kToV + 4096), tabu.y);
        wgmma_sp_n192_tb<false, 0>(acc, pa[8], pa[9], pa[10], pa[11], desc_at(dA, kToV + 8192), tabu.z);
        wgmma_sp_n192_tb<false, 1>(acc, EARLY && j == 0 ? 0u : y[10], EARLY && j == 0 ? 0u : y[11], y[12], y[13], desc_at(dE, kToV + kOffMid), tabu.z);
        wg_commit();
        unfold<8, 0, 6>(y, tabv.w, pb);
        wg_fence();
        wgmma_sp_n192_tb<false, 0>(acc, pb[0], pb[1], pb[2], pb[3], desc_at(dN, kToV), tabu.y);
        wgmma_sp_n192_tb<false, 1>(acc, pb[4], pb[5], pb[6], pb[7], desc_at(dN, kToV + 4096), tabu.y);
        wgmma_sp_n192_tb<false, 0>(acc, pb[8], pb[9], pb[10], pb[11], desc_at(dN, kToV + 8192), tabu.z);
        wg_commit();
        if (!last) turn_pass(wg);
        TRF(16 + 16 * k);
        wg_wait<1>();
        if (lane == 0) mbar_arrive(bar_use);
        TRF(17 + 16 * k);
        mbar_wait(bar_ok + 24, 0);
        wg_wait<0>();
        if (lane == 0) mbar_arrive(bar_use + 8);
        pin(acc);
        TR(18 + 16 * k);

        acc_to_frags(acc, po);
        pin(po);
        if (!last) turn_wait(wg);
        wg_fence();
        proj_gemm(acc, po, dsc, s_wv, [&](int s) {
            if (s + 1 == OSPLIT && i + 2 == w.ntiles) { turn_pass(wg); turn_wait(wg); }
        });
        if (!last) turn_pass(wg);
        TRF(19 + 16 * k);
        const uint32_t zero = lds_volatile(s_late);
        const float inv0 = rcp(quad_sum(s0 + __uint_as_float(zero))), inv1 = rcp(quad_sum(s1 + __uint_as_float(zero)));
        raw_to_frags(nxt, zero, fa);
        pin(fa);
#pragma unroll
        for (int q = 0; q < 48; q += 4) keep(wqkv == nullptr, fa[q], fa[q + 1], fa[q + 2], fa[q + 3]);
        keep(wqkv == nullptr, __float_as_uint(inv0), __float_as_uint(inv1), zero, lane);
        TRF(20 + 16 * k);
        tu += du2; tv += dv2;
        wg_wait<0>();
        pin(acc);
        TR(21 + 16 * k);
#pragma unroll
        for (int q = 0; q < 96; q++) acc[q] *= q & 2 ? inv1 : inv0;
        pack_out(acc, po);
#pragma unroll
        for (int n = 0; n < INLOOP; n++) store_one<false>(last, out + c0, out + c1, po, n);
        pin(po);
    }
#pragma unroll
    for (int n = 0; n < 12; n++) {
        if (NAP) asm volatile("{\n.reg .pred p;\nsetp.eq.u32 p, %0, 0;\n@p nanosleep.u32 %1;\n}\n" ::"r"(wg), "n"(NAP) : "memory");
        store_one<false>(n >= INLOOP || wg == 0, out + c0, out + c1, po, n);
    }
    TRE(7);
    TRG(1);
    TRDUMP();
}

typedef CUresult (*EncodeTiledFn)(CUtensorMap*, CUtensorMapDataType, cuuint32_t, void*, const cuuint64_t*, const cuuint64_t*,
                                  const cuuint32_t*, const cuuint32_t*, CUtensorMapInterleave, CUtensorMapSwizzle,
                                  CUtensorMapL2promotion, CUtensorMapFloatOOBfill);

bool make_maps(EncodeTiledFn fn, Maps* maps, void* x, void* wqkv, void* wo) {
    const cuuint64_t pix2 = 2 * kPixBytes, row = (cuuint64_t)kHW * kPixBytes;
    const cuuint32_t estr[5] = {1, 1, 1, 1, 1};
    bool ok = true;
    for (int tr = 0; tr < 2; tr++)
        for (int b = 0; b < 2; b++) {
            const cuuint64_t su = tr ? 2 * row : pix2, sv = tr ? pix2 : 2 * row;
            const cuuint64_t dims[5] = {2 * kC, 2, 105, 2, 112};
            const cuuint64_t strides[4] = {7 * su, su, row, sv};
            const cuuint32_t box[5] = {64, 2, 7, 1, b ? 2u : 6u};
            ok = ok && fn(&maps->m[2 * tr + b], CU_TENSOR_MAP_DATA_TYPE_BFLOAT16, 5, x, dims, strides, box, estr,
                          CU_TENSOR_MAP_INTERLEAVE_NONE, CU_TENSOR_MAP_SWIZZLE_128B, CU_TENSOR_MAP_L2_PROMOTION_L2_128B,
                          CU_TENSOR_MAP_FLOAT_OOB_FILL_NONE) == CUDA_SUCCESS;
        }
    for (int b = 0; b < 2; b++) {
        const cuuint64_t dims[3] = {b ? 64u : 48u, kC, b ? 9u : 4u}, strides[2] = {(b ? 3u : 1u) * kPixBytes, b ? 128u : 96u};
        const cuuint32_t box[3] = {b ? 64u : 48u, b ? 16u : 192u, b ? 3u : 1u};
        ok = ok && fn(b ? &maps->wv : &maps->wo, CU_TENSOR_MAP_DATA_TYPE_BFLOAT16, 3, b ? wqkv : wo, dims, strides, box, estr,
                      CU_TENSOR_MAP_INTERLEAVE_NONE, b ? CU_TENSOR_MAP_SWIZZLE_128B : CU_TENSOR_MAP_SWIZZLE_NONE, CU_TENSOR_MAP_L2_PROMOTION_L2_128B,
                      CU_TENSOR_MAP_FLOAT_OOB_FILL_NONE) == CUDA_SUCCESS;
    }
    return ok;
}

}

extern "C" void kernel_launch(void* const* d_in, const int* in_sizes, int n_in, void* d_out, int out_size) {
    static EncodeTiledFn encode = nullptr;
    static Scratch* scratch = nullptr;
    static Tables* tables = nullptr;
    if (!encode) {
        int dev = 0, reserved = 0;
        cudaFuncAttributes attr;
        cudaGetDevice(&dev);
        cudaDeviceGetAttribute(&reserved, cudaDevAttrReservedSharedMemoryPerBlock, dev);
        cudaFuncGetAttributes(&attr, nat_fused_kernel);
        if (reserved != (int)kSmemBase || attr.sharedSizeBytes != 0) return;
        cudaGetSymbolAddress((void**)&scratch, g_scratch);
        cudaGetSymbolAddress((void**)&tables, g_tables);
        void* fn = nullptr;
        cudaDriverEntryPointQueryResult st;
        cudaGetDriverEntryPoint("cuTensorMapEncodeTiled", &fn, cudaEnableDefault, &st);
        encode = (EncodeTiledFn)fn;
        cudaFuncSetAttribute(nat_fused_kernel, cudaFuncAttributeMaxDynamicSharedMemorySize, kSmemBytes);
    }
    Maps maps;
    maps.tables = tables;
    if (!encode || !make_maps(encode, &maps, d_in[0], d_in[1], d_in[2])) return;
    nat_fused_kernel<<<kGrid, kThreads, kSmemBytes>>>((const uint8_t*)d_in[0], (const uint8_t*)d_in[1], (uint8_t*)d_out, scratch, (const uint8_t*)d_in[2],
                                                      kDescRing, maps);
}
```

```cpp
#include <cuda_runtime.h>
#include <cuda_bf16.h>
#include <cuda.h>
#include <stdint.h>
#include <type_traits>
#include <stdlib.h>
#include <stdio.h>
#include <stddef.h>

#define KEEPFA 1
#define ASLOTS 0x3800
#define BSLOTS 0x6
#define QSLOTS 0x78a
#define OSPLIT 2
#define NAP 40
#define SPEC 1
#define EARLY 2
#define PFROM 24
#define PNAP 160
#define INLOOP 3

namespace {

constexpr int kC          = 192;
constexpr int kHW         = 224;
constexpr int kPixBytes   = kC * 2;
constexpr int kSlotBytes  = 84 * 128;
constexpr int kMidBytes   = 28 * 128;
constexpr int kOffMid     = 88 * 128;
constexpr int kSlotStride = 120 * 128;
constexpr int kRingChunk  = 208 * 128;
constexpr int kWChunk     = 192 * 128;
constexpr int kWBytes     = 3 * kWChunk;
constexpr uint32_t kSmemBase = 1024;
constexpr uint32_t s_ring = kSmemBase, s_m = s_ring + 3 * kRingChunk, s_wv = s_m + kWBytes, s_bar = s_wv + kWBytes;
constexpr uint32_t bar_b = s_bar, bar_img = s_bar + 24, bar_redo = s_bar + 72, bar_wop = s_bar + 96, bar_a = s_bar + 104,
                   bar_ok = s_bar + 112, bar_use = s_bar + 144, bar_free = s_bar + 160;
constexpr uint32_t s_par = s_bar + 192, s_late = s_bar + 200, s_again = s_bar + 204, s_tab = s_bar + 256, s_trace = s_tab + 2048;
constexpr int kSmemBytes  = s_trace + 2048 - kSmemBase;
constexpr int kThreads    = 384;
constexpr int kGrid       = 132;
constexpr int kTimeM = 2500, kTimeW = 5100;
constexpr float kScaleLog2e = 0.07216878364870322f * 1.4426950408889634f;

struct Maps {
    CUtensorMap m[4];
    CUtensorMap wo, wv;
    const struct Tables* tables;
};
#define TN(i, dflt) (dflt)
#define START_TIME (wg ? 850 + 500 * order : 250 + 560 * order)

struct Scratch {
    uint8_t img[2][2][kWBytes];
    uint32_t launches[kGrid][32];
};
__device__ __align__(1024) Scratch g_scratch;

struct Table {
    uint32_t route[32][4];
    uint32_t u[8][4][4];
    uint32_t v[16][4][4];
};
struct Tables { Table t[2]; };
constexpr Tables make_tables() {
    Tables r = {};
    for (int rev = 0; rev < 2; rev++)
        for (int j = 0; j < 4; j++) {
            Table& t = r.t[rev];
            for (int q = 0; q < 8; q++) {
                uint32_t* e = t.route[4 * q + j];
                e[0] = 4 * q + 2 * (j & 1) + (j >> 1); e[1] = e[0] ^ 1;
                e[2] = j < 2 ? 0x5410u : 0x1054u; e[3] = e[2] + 0x2222u;
                e = t.u[q][j];
                for (int n = 0; n < 7; n++) e[0] |= ((n + j) % 7 < q ? 1u : 0u) << n;
                e[3] = e[0];
                for (int k = 0; k < 2; k++) {
                    const int step = 2 * k + (j >> 1), p0 = (step < 3 ? 16 * step : 40) + 8 * (j & 1);
                    uint32_t m = 0x8888u;
                    for (int n = 0; n < 8; n++) m |= ((p0 + n) % 7 < q ? 1u : 0u) << (2 * n);
                    e[1 + k] = m * 0x10001u;
                }
            }
            for (int sum = 0; sum < 15; sum++) {
                uint32_t* e = t.v[sum][j];
                for (int row = 0; row < 2; row++)
                    for (int b = 0; b < 14; b++) {
                        const int off = (sum + row) / 2, p = 4 * b + j;
                        const uint32_t bit = 1u << (2 * b + row);
                        if (p < 42 && p >= 7 * off) e[rev] |= bit;
                        if (p < 7 * off - 7) e[1 - rev] |= bit;
                        if (p >= 42 && p >= 7 * off && p < 7 * off + 49) e[2] |= bit;
                    }
                for (int n = 0; n < 6; n++)
                    if (8 * n + 2 * j < 42) e[3] |= 1u << (n + ((8 * n + 2 * j >= 7 * (sum / 2 & ~1)) != rev ? 0 : 8));
            }
        }
    return r;
}
__device__ __align__(128) const Tables g_tables = make_tables();

#define WO4(i) "=f"(d[i]), "=f"(d[i + 1]), "=f"(d[i + 2]), "=f"(d[i + 3])
#define RW4(i) "+f"(d[i]), "+f"(d[i + 1]), "+f"(d[i + 2]), "+f"(d[i + 3])

template <bool FIRST>
__device__ __forceinline__ void wgmma_n192(float (&d)[96], uint32_t a0, uint32_t a1, uint32_t a2, uint32_t a3, uint64_t descb) {
    if constexpr (FIRST) {
        asm volatile(
            "wgmma.mma_async.sync.aligned.m64n192k16.f32.bf16.bf16 "
            "{%0, %1, %2, %3, %4, %5, %6, %7, %8, %9, %10, %11, %12, %13, %14, %15, %16, %17, %18, %19, %20, %21, %22, %23, "
            "%24, %25, %26, %27, %28, %29, %30, %31, %32, %33, %34, %35, %36, %37, %38, %39, %40, %41, %42, %43, %44, %45, %46, %47, "
            "%48, %49, %50, %51, %52, %53, %54, %55, %56, %57, %58, %59, %60, %61, %62, %63, %64, %65, %66, %67, %68, %69, %70, %71, "
            "%72, %73, %74, %75, %76, %77, %78, %79, %80, %81, %82, %83, %84, %85, %86, %87, %88, %89, %90, %91, %92, %93, %94, %95}, "
            "{%96, %97, %98, %99}, %100, 0, 1, 1, 0;"
            : WO4(0), WO4(4), WO4(8), WO4(12), WO4(16), WO4(20), WO4(24), WO4(28), WO4(32), WO4(36), WO4(40), WO4(44),
              WO4(48), WO4(52), WO4(56), WO4(60), WO4(64), WO4(68), WO4(72), WO4(76), WO4(80), WO4(84), WO4(88), WO4(92)
            : "r"(a0), "r"(a1), "r"(a2), "r"(a3), "l"(descb));
    } else {
        asm volatile(
            "wgmma.mma_async.sync.aligned.m64n192k16.f32.bf16.bf16 "
            "{%0, %1, %2, %3, %4, %5, %6, %7, %8, %9, %10, %11, %12, %13, %14, %15, %16, %17, %18, %19, %20, %21, %22, %23, "
            "%24, %25, %26, %27, %28, %29, %30, %31, %32, %33, %34, %35, %36, %37, %38, %39, %40, %41, %42, %43, %44, %45, %46, %47, "
            "%48, %49, %50, %51, %52, %53, %54, %55, %56, %57, %58, %59, %60, %61, %62, %63, %64, %65, %66, %67, %68, %69, %70, %71, "
            "%72, %73, %74, %75, %76, %77, %78, %79, %80, %81, %82, %83, %84, %85, %86, %87, %88, %89, %90, %91, %92, %93, %94, %95}, "
            "{%96, %97, %98, %99}, %100, 1, 1, 1, 0;"
            : RW4(0), RW4(4), RW4(8), RW4(12), RW4(16), RW4(20), RW4(24), RW4(28), RW4(32), RW4(36), RW4(40), RW4(44),
              RW4(48), RW4(52), RW4(56), RW4(60), RW4(64), RW4(68), RW4(72), RW4(76), RW4(80), RW4(84), RW4(88), RW4(92)
            : "r"(a0), "r"(a1), "r"(a2), "r"(a3), "l"(descb));
    }
}

template <bool FIRST>
__device__ __forceinline__ void wgmma_n88(float (&d)[44], uint32_t a0, uint32_t a1, uint32_t a2, uint32_t a3, uint64_t descb) {
    if constexpr (FIRST) {
        asm volatile(
            "wgmma.mma_async.sync.aligned.m64n88k16.f32.bf16.bf16 "
            "{%0, %1, %2, %3, %4, %5, %6, %7, %8, %9, %10, %11, %12, %13, %14, %15, %16, %17, %18, %19, %20, %21, %22, %23, "
            "%24, %25, %26, %27, %28, %29, %30, %31, %32, %33, %34, %35, %36, %37, %38, %39, %40, %41, %42, %43}, "
            "{%44, %45, %46, %47}, %48, 0, 1, 1, 0;"
            : WO4(0), WO4(4), WO4(8), WO4(12), WO4(16), WO4(20), WO4(24), WO4(28), WO4(32), WO4(36), WO4(40)
            : "r"(a0), "r"(a1), "r"(a2), "r"(a3), "l"(descb));
    } else {
        asm volatile(
            "wgmma.mma_async.sync.aligned.m64n88k16.f32.bf16.bf16 "
            "{%0, %1, %2, %3, %4, %5, %6, %7, %8, %9, %10, %11, %12, %13, %14, %15, %16, %17, %18, %19, %20, %21, %22, %23, "
            "%24, %25, %26, %27, %28, %29, %30, %31, %32, %33, %34, %35, %36, %37, %38, %39, %40, %41, %42, %43}, "
            "{%44, %45, %46, %47}, %48, 1, 1, 1, 0;"
            : RW4(0), RW4(4), RW4(8), RW4(12), RW4(16), RW4(20), RW4(24), RW4(28), RW4(32), RW4(36), RW4(40)
            : "r"(a0), "r"(a1), "r"(a2), "r"(a3), "l"(descb));
    }
}

template <bool FIRST>
__device__ __forceinline__ void wgmma_n32(float (&d)[16], uint32_t a0, uint32_t a1, uint32_t a2, uint32_t a3, uint64_t descb) {
    if constexpr (FIRST) {
        asm volatile(
            "wgmma.mma_async.sync.aligned.m64n32k16.f32.bf16.bf16 "
            "{%0, %1, %2, %3, %4, %5, %6, %7, %8, %9, %10, %11, %12, %13, %14, %15}, "
            "{%16, %17, %18, %19}, %20, 0, 1, 1, 0;"
            : WO4(0), WO4(4), WO4(8), WO4(12)
            : "r"(a0), "r"(a1), "r"(a2), "r"(a3), "l"(descb));
    } else {
        asm volatile(
            "wgmma.mma_async.sync.aligned.m64n32k16.f32.bf16.bf16 "
            "{%0, %1, %2, %3, %4, %5, %6, %7, %8, %9, %10, %11, %12, %13, %14, %15}, "
            "{%16, %17, %18, %19}, %20, 1, 1, 1, 0;"
            : RW4(0), RW4(4), RW4(8), RW4(12)
            : "r"(a0), "r"(a1), "r"(a2), "r"(a3), "l"(descb));
    }
}

template <bool FIRST, int SEL>
__device__ __forceinline__ void wgmma_sp_n192_tb(float (&d)[96], uint32_t a0, uint32_t a1, uint32_t a2, uint32_t a3, uint64_t descb, uint32_t meta) {
    if constexpr (FIRST) {
        asm volatile(
            "wgmma.mma_async.sp.sync.aligned.m64n192k32.f32.bf16.bf16 "
            "{%0, %1, %2, %3, %4, %5, %6, %7, %8, %9, %10, %11, %12, %13, %14, %15, %16, %17, %18, %19, %20, %21, %22, %23, "
            "%24, %25, %26, %27, %28, %29, %30, %31, %32, %33, %34, %35, %36, %37, %38, %39, %40, %41, %42, %43, %44, %45, %46, %47, "
            "%48, %49, %50, %51, %52, %53, %54, %55, %56, %57, %58, %59, %60, %61, %62, %63, %64, %65, %66, %67, %68, %69, %70, %71, "
            "%72, %73, %74, %75, %76, %77, %78, %79, %80, %81, %82, %83, %84, %85, %86, %87, %88, %89, %90, %91, %92, %93, %94, %95}, "
            "{%96, %97, %98, %99}, %100, %101, %102, 0, 1, 1, 1;"
            : WO4(0), WO4(4), WO4(8), WO4(12), WO4(16), WO4(20), WO4(24), WO4(28), WO4(32), WO4(36), WO4(40), WO4(44),
              WO4(48), WO4(52), WO4(56), WO4(60), WO4(64), WO4(68), WO4(72), WO4(76), WO4(80), WO4(84), WO4(88), WO4(92)
            : "r"(a0), "r"(a1), "r"(a2), "r"(a3), "l"(descb), "r"(meta), "n"(SEL));
    } else {
        asm volatile(
            "wgmma.mma_async.sp.sync.aligned.m64n192k32.f32.bf16.bf16 "
            "{%0, %1, %2, %3, %4, %5, %6, %7, %8, %9, %10, %11, %12, %13, %14, %15, %16, %17, %18, %19, %20, %21, %22, %23, "
            "%24, %25, %26, %27, %28, %29, %30, %31, %32, %33, %34, %35, %36, %37, %38, %39, %40, %41, %42, %43, %44, %45, %46, %47, "
            "%48, %49, %50, %51, %52, %53, %54, %55, %56, %57, %58, %59, %60, %61, %62, %63, %64, %65, %66, %67, %68, %69, %70, %71, "
            "%72, %73, %74, %75, %76, %77, %78, %79, %80, %81, %82, %83, %84, %85, %86, %87, %88, %89, %90, %91, %92, %93, %94, %95}, "
            "{%96, %97, %98, %99}, %100, %101, %102, 1, 1, 1, 1;"
            : RW4(0), RW4(4), RW4(8), RW4(12), RW4(16), RW4(20), RW4(24), RW4(28), RW4(32), RW4(36), RW4(40), RW4(44),
              RW4(48), RW4(52), RW4(56), RW4(60), RW4(64), RW4(68), RW4(72), RW4(76), RW4(80), RW4(84), RW4(88), RW4(92)
            : "r"(a0), "r"(a1), "r"(a2), "r"(a3), "l"(descb), "r"(meta), "n"(SEL));
    }
}

#define TR(slot)
#define TRX(slot)
#define TRE(slot)
#define TRT(slot)
#define TRF(slot)
#define TRW(slot)
#define TRG(slot)
#define TRDUMP()

__device__ __forceinline__ void wg_fence() { asm volatile("wgmma.fence.sync.aligned;" ::: "memory"); }
__device__ __forceinline__ void wg_commit() { asm volatile("wgmma.commit_group.sync.aligned;" ::: "memory"); }
template <int N>
__device__ __forceinline__ void wg_wait() { asm volatile("wgmma.wait_group.sync.aligned %0;" ::"n"(N) : "memory"); }

template <int N>
__device__ __forceinline__ void pin(float (&d)[N]) {
#pragma unroll
    for (int i = 0; i < N; i++) asm volatile("" : "+f"(d[i])::"memory");
}
template <int N>
__device__ __forceinline__ void pin(uint32_t (&d)[N]) {
#pragma unroll
    for (int i = 0; i < N; i++) asm volatile("" : "+r"(d[i])::"memory");
}

constexpr uint64_t kDescRing = ((uint64_t)((1u << 30) | (1024u >> 4)) << 32) | (1u << 16) | (s_ring >> 4);
constexpr uint32_t kToV = ((kRingChunk >> 4) - 1) << 20;
__device__ __forceinline__ uint64_t desc_at(uint64_t base, uint32_t byte_off) {
    uint64_t d;
    asm volatile("add.s64 %0, %1, %2;" : "=l"(d) : "l"(base), "l"((uint64_t)(byte_off >> 4)));
    return d;
}

__device__ __forceinline__ void mbar_init(uint32_t bar, uint32_t count) {
    asm volatile("mbarrier.init.shared::cta.b64 [%0], %1;" ::"r"(bar), "r"(count) : "memory");
}
__device__ __forceinline__ void mbar_expect_tx(uint32_t bar, uint32_t bytes) {
    asm volatile("mbarrier.arrive.expect_tx.shared::cta.b64 _, [%0], %1;" ::"r"(bar), "r"(bytes) : "memory");
}
__device__ __forceinline__ void expect_tx_only(uint32_t bar, uint32_t bytes) {
    asm volatile("mbarrier.expect_tx.relaxed.cta.shared::cta.b64 [%0], %1;" ::"r"(bar), "r"(bytes) : "memory");
}
__device__ __forceinline__ void mbar_arrive(uint32_t bar) {
    asm volatile("mbarrier.arrive.shared::cta.b64 _, [%0];" ::"r"(bar) : "memory");
}
__device__ __forceinline__ void mbar_wait(uint32_t bar, uint32_t parity) {
    asm volatile(
        "{\n.reg .pred p;\n"
        "W: mbarrier.try_wait.parity.shared::cta.b64 p, [%0], %1;\n"
        "@!p bra W;\n}\n"
        ::"r"(bar), "r"(parity) : "memory");
}
__device__ __forceinline__ uint32_t clock_now() {
    uint32_t c;
    asm volatile("mov.u32 %0, %%clock;" : "=r"(c)::"memory");
    return c;
}
__device__ __forceinline__ void wait_until(uint32_t t0, int t) {
    if (t == 0) return;
    while ((int)(clock_now() - t0) < t) {}
}
__device__ __forceinline__ bool elect() {
    uint32_t ok;
    asm volatile("{\n.reg .pred p;\nelect.sync _|p, 0xffffffff;\nselp.u32 %0, 1, 0, p;\n}\n" : "=r"(ok));
    return ok != 0;
}
__device__ __forceinline__ void turn_wait(int wg) { asm volatile("bar.sync %0, 256;" ::"r"(1 + wg) : "memory"); }
__device__ __forceinline__ void turn_pass(int wg) { asm volatile("bar.arrive %0, 256;" ::"r"(2 - wg) : "memory"); }

__device__ __forceinline__ void tma_box(uint32_t dst, const CUtensorMap* map, uint32_t bar, int c0, int c2, int c3, int c4) {
    asm volatile(
        "cp.async.bulk.tensor.5d.shared::cluster.global.mbarrier::complete_tx::bytes [%0], [%1, {%3, %4, %5, %6, %7}], [%2];"
        ::"r"(dst), "l"(map), "r"(bar), "r"(c0), "r"(0), "r"(c2), "r"(c3), "r"(c4)
        : "memory");
}
__device__ __forceinline__ void tma_3d(uint32_t dst, const CUtensorMap* map, uint32_t bar, int c1, int c2) {
    asm volatile("cp.async.bulk.tensor.3d.shared::cluster.global.mbarrier::complete_tx::bytes [%0], [%1, {%3, %4, %5}], [%2];"
                 ::"r"(dst), "l"(map), "r"(bar), "r"(0), "r"(c1), "r"(c2)
                 : "memory");
}
__device__ __forceinline__ void prefetch_map(const CUtensorMap* map) {
    asm volatile("prefetch.tensormap [%0];" ::"l"(map) : "memory");
}
__device__ __forceinline__ uint4 ldg(const void* p) {
    uint4 v;
    asm volatile("ld.global.v4.u32 {%0, %1, %2, %3}, [%4];" : "=r"(v.x), "=r"(v.y), "=r"(v.z), "=r"(v.w) : "l"(p) : "memory");
    return v;
}
__device__ __forceinline__ uint32_t pack_bf16(float lo, float hi) {
    uint32_t r;
    asm("cvt.rn.bf16x2.f32 %0, %1, %2;" : "=r"(r) : "f"(hi), "f"(lo));
    return r;
}
__device__ __forceinline__ float ex2(float x) {
    float y;
    asm("ex2.approx.ftz.f32 %0, %1;" : "=f"(y) : "f"(x));
    return y;
}
__device__ __forceinline__ float rcp(float x) {
    float y;
    asm("rcp.approx.ftz.f32 %0, %1;" : "=f"(y) : "f"(x));
    return y;
}
__device__ __forceinline__ void mma16816(float (&d)[4], uint32_t a0, uint32_t a1, uint32_t a2, uint32_t a3, uint32_t b0, uint32_t b1) {
    asm volatile("mma.sync.aligned.m16n8k16.row.col.f32.bf16.bf16.f32 {%0, %1, %2, %3}, {%4, %5, %6, %7}, {%8, %9}, {%0, %1, %2, %3};"
                 : "+f"(d[0]), "+f"(d[1]), "+f"(d[2]), "+f"(d[3])
                 : "r"(a0), "r"(a1), "r"(a2), "r"(a3), "r"(b0), "r"(b1));
}
__device__ __forceinline__ uint4 lds128(uint32_t addr) {
    uint4 v;
    asm volatile("ld.volatile.shared.v4.u32 {%0, %1, %2, %3}, [%4];" : "=r"(v.x), "=r"(v.y), "=r"(v.z), "=r"(v.w) : "r"(addr) : "memory");
    return v;
}
__device__ __forceinline__ uint32_t lds_volatile(uint32_t addr) {
    uint32_t v;
    asm volatile("ld.volatile.shared.u32 %0, [%1];" : "=r"(v) : "r"(addr) : "memory");
    return v;
}

__device__ __forceinline__ int window_start(int n) { return min(max(n, 0), 105); }
__device__ __forceinline__ int origin_u(int u) { return min(max(u, 0), 98); }

struct Work {
    int u, v;
    int step;
    uint32_t su, sv;
    uint32_t base;
    bool corner;
    int ntiles;
    __device__ __forceinline__ void pixel_offsets(int qu, int qv, int j, uint32_t& o0, uint32_t& o1) const {
        const uint32_t b = (qu + window_start(qu)) * su + j * 16 + base;
        o0 = b + (qv + window_start(qv)) * sv;
        o1 = b + (qv + 1 + window_start(qv + 1)) * sv;
    }
};

__device__ __forceinline__ Work decode_work(int c) {
    Work w;
    const bool transposed = (c >> 4) == 7;
    const int px = 6 * (c & 1), py = 3 * (c & 2);
    w.corner = c >= 128;
    w.step = 8 - 4 * (c & 4);
    w.u = (c < 112 ? c & ~7 : 96 + (c & 8)) + (transposed ? py : px) - 6;
    w.v = (w.corner ? 96 : 48 - 2 * (c & 4)) + (transposed ? px : py) - 6;
    w.su = transposed ? kHW * kPixBytes : kPixBytes;
    w.sv = transposed ? kPixBytes : kHW * kPixBytes;
    w.base = px * (kPixBytes / 6) + py * (kHW * kPixBytes / 6) + 6 * (kHW + 1) * kPixBytes;
    w.ntiles = w.corner ? 4 : 6;
    return w;
}

struct RawX { uint4 a[6], b[6]; };
__device__ __forceinline__ void load_raw(RawX& r, const uint8_t* base, uint32_t o0, uint32_t o1) {
    __syncwarp();
#pragma unroll
    for (int c = 0; c < 6; c++) { r.a[c] = ldg(base + o0 + c * 64); r.b[c] = ldg(base + o1 + c * 64); }
    __syncwarp();
}
__device__ __forceinline__ void raw_to_frags(const RawX& r, uint32_t zero, uint32_t (&f)[48]) {
#pragma unroll
    for (int c = 0; c < 6; c++) {
        asm volatile("{\n.reg .b32 t, u;\nadd.u32 t, %4, %8;\nadd.u32 u, %5, %8;\nxor.b32 %0, %6, %8;\nxor.b32 %1, %7, %8;\n"
                     "xor.b32 %2, t, %8;\nxor.b32 %3, u, %8;\n}\n"
                     : "=&r"(f[8 * c + 1]), "=&r"(f[8 * c + 3]), "=&r"(f[8 * c + 4]), "=&r"(f[8 * c + 6])
                     : "r"(r.a[c].y), "r"(r.a[c].w), "r"(r.b[c].x), "r"(r.b[c].z), "r"(zero));
        f[8 * c + 0] = r.a[c].x; f[8 * c + 2] = r.a[c].z; f[8 * c + 5] = r.b[c].y; f[8 * c + 7] = r.b[c].w;
    }
}
__device__ __forceinline__ void acc_to_frags(const float (&d)[96], uint32_t (&f)[48]) {
#pragma unroll
    for (int i = 0; i < 48; i++) f[i] = pack_bf16(d[2 * i], d[2 * i + 1]);
}

template <class F>
__device__ __forceinline__ void proj_gemm(float (&d)[96], const uint32_t (&a)[48], uint64_t dsc, uint32_t img, F after) {
#pragma unroll
    for (int s = 0; s < 12; s++) {
        if (s == 0) wgmma_n192<true>(d, a[4 * s], a[4 * s + 1], a[4 * s + 2], a[4 * s + 3], desc_at(dsc, img - s_ring + (s >> 2) * kWChunk + (s & 3) * 32));
        else wgmma_n192<false>(d, a[4 * s], a[4 * s + 1], a[4 * s + 2], a[4 * s + 3], desc_at(dsc, img - s_ring + (s >> 2) * kWChunk + (s & 3) * 32));
        if (s == 11) wg_commit();
        after(s);
    }
}
__device__ __forceinline__ void pack_out(const float (&acc)[96], uint32_t (&po)[48]) {
#pragma unroll
    for (int g = 0; g < 6; g++)
#pragma unroll
        for (int q = 0; q < 4; q++) {
            po[8 * g + q] = pack_bf16(acc[16 * g + 4 * q], acc[16 * g + 4 * q + 1]);
            po[8 * g + 4 + q] = pack_bf16(acc[16 * g + 4 * q + 2], acc[16 * g + 4 * q + 3]);
        }
}
template <bool PINNED = true>
__device__ __forceinline__ void store_one(bool on, uint8_t* p0, uint8_t* p1, const uint32_t (&po)[48], int n) {
    if (PINNED) __syncwarp();
    asm volatile("{\n.reg .pred p;\nsetp.ne.u32 p, %5, 0;\n@p st.global.v4.u32 [%0], {%1, %2, %3, %4};\n}\n"
                 ::"l"(((n & 1) ? p1 : p0) + (n >> 1) * 64), "r"(po[4 * n]), "r"(po[4 * n + 1]), "r"(po[4 * n + 2]), "r"(po[4 * n + 3]), "r"((uint32_t)on) : "memory");
}

template <int N>
__device__ __forceinline__ float tree_max(const float (&v)[N]) {
    float t[N];
#pragma unroll
    for (int i = 0; i < N; i++) t[i] = v[i];
#pragma unroll
    for (int w = 1; w < N; w *= 2)
#pragma unroll
        for (int i = 0; i + w < N; i += 2 * w) t[i] = fmaxf(t[i], t[i + w]);
    return t[0];
}
template <int N>
__device__ __forceinline__ float tree_sum(const float (&v)[N]) {
    float t[N];
#pragma unroll
    for (int i = 0; i < N; i++) t[i] = v[i];
#pragma unroll
    for (int w = 1; w < N; w *= 2)
#pragma unroll
        for (int i = 0; i + w < N; i += 2 * w) t[i] += t[i + w];
    return t[0];
}

template <int B>
__device__ __forceinline__ void pick(uint32_t h, uint32_t ok, const float* s, float& v0, float& v1) {
    asm("{\n.reg .pred p, q0, q1;\n.reg .b32 t;\nand.b32 t, %6, %7;\nsetp.ne.u32 p, t, 0;\n"
        "and.b32 t, %8, %9;\nsetp.ne.u32 q0, t, 0;\nand.b32 t, %8, %10;\nsetp.ne.u32 q1, t, 0;\n"
        "@q0 selp.f32 %0, %3, %2, p;\n@q1 selp.f32 %1, %5, %4, p;\n}\n"
        : "+f"(v0), "+f"(v1)
        : "f"(s[0]), "f"(s[1]), "f"(s[2]), "f"(s[3]), "r"(h), "n"(1 << ((4 * B) % 7)), "r"(ok), "n"(1 << (2 * B)), "n"(2 << (2 * B)));
}
template <int B, class F>
__device__ __forceinline__ void for_blocks(F f) {
    if constexpr (B > 0) { for_blocks<B - 1>(f); f(std::integral_constant<int, B - 1>{}); }
}
__device__ __forceinline__ void gather_outer(const float (&s)[44], uint32_t h, uint32_t ok, float (&v0)[14], float (&v1)[14]) {
    for_blocks<11>([&](auto B) {
        constexpr int b = B.value < 8 ? (B.value >> 1) + 7 * (B.value & 1) : B.value - 4;
        pick<b>(h, ok, &s[4 * b], v0[b], v1[b]);
    });
}
__device__ __forceinline__ void gather_mid(const float (&sE)[16], uint32_t h, uint32_t ok, float (&v0)[14], float (&v1)[14]) {
    for_blocks<4>([&](auto B) { pick<10 + B.value>(h, ok, &sE[4 * B.value], v0[10 + B.value], v1[10 + B.value]); });
}
__device__ __forceinline__ float quad_max(float m) {
    m = fmaxf(m, __shfl_xor_sync(0xffffffffu, m, 1));
    return fmaxf(m, __shfl_xor_sync(0xffffffffu, m, 2));
}
__device__ __forceinline__ float quad_sum(float s) {
    s += __shfl_xor_sync(0xffffffffu, s, 1);
    return s + __shfl_xor_sync(0xffffffffu, s, 2);
}
template <int B0, int B1>
__device__ __forceinline__ void exp_route(float (&v0)[14], float (&v1)[14], float m0, float m1, const uint4& r, bool even, uint32_t (&y)[14]) {
#pragma unroll
    for (int b = B0; b < B1; b++) { v0[b] = ex2(v0[b] - m0); v1[b] = ex2(v1[b] - m1); }
#pragma unroll
    for (int b = B0; b < B1; b += 2) {
        const uint32_t x0 = pack_bf16(v0[b], v1[b]), x1 = pack_bf16(v0[b + 1], v1[b + 1]);
        const uint32_t u = __shfl_sync(0xffffffffu, even ? x0 : x1, r.x);
        const uint32_t w = __shfl_sync(0xffffffffu, even ? x1 : x0, r.y);
        y[b] = __byte_perm(u, w, r.z); y[b + 1] = __byte_perm(u, w, r.w);
    }
}
template <int BIT0, int N0, int N1>
__device__ __forceinline__ void unfold(const uint32_t (&y)[14], uint32_t fold, uint32_t (&p)[12]) {
    for_blocks<N1 - N0>([&](auto N) {
        constexpr int n = N0 + N.value;
        asm("{\n.reg .pred p;\n.reg .b32 t;\nand.b32 t, %4, %5;\nsetp.ne.u32 p, t, 0;\nselp.b32 %0, %2, 0, p;\nselp.b32 %1, %3, 0, p;\n}\n"
            : "=r"(p[2 * n]), "=r"(p[2 * n + 1]) : "r"(y[2 * n]), "r"(y[2 * n + 1]), "r"(fold), "n"(1 << (BIT0 + n)));
    });
}
__device__ __forceinline__ void keep(bool never, uint32_t a, uint32_t b, uint32_t c, uint32_t d) {
    asm volatile("{\n.reg .pred p;\nsetp.ne.u32 p, %4, 0;\n@p st.volatile.shared.v4.u32 [%5], {%0, %1, %2, %3};\n}\n"
                 ::"r"(a), "r"(b), "r"(c), "r"(d), "r"((uint32_t)never), "r"(s_trace) : "memory");
}

__device__ __forceinline__ uint32_t wimg_offset(uint32_t row, uint32_t s, uint32_t j) {
    return (s >> 2) * kWChunk + row * 128 + (((2 * (s & 3) + (j >> 1)) ^ (row & 7)) << 4) + (j & 1) * 8;
}

__device__ __forceinline__ void ldsm4(uint32_t (&r)[4], uint32_t addr) {
    asm volatile("ldmatrix.sync.aligned.m8n8.x4.shared.b16 {%0, %1, %2, %3}, [%4];" : "=r"(r[0]), "=r"(r[1]), "=r"(r[2]), "=r"(r[3]) : "r"(addr) : "memory");
}
__device__ __forceinline__ void ldsm4_t(uint32_t (&r)[4], uint32_t addr) {
    asm volatile("ldmatrix.sync.aligned.m8n8.x4.trans.shared.b16 {%0, %1, %2, %3}, [%4];" : "=r"(r[0]), "=r"(r[1]), "=r"(r[2]), "=r"(r[3]) : "r"(addr) : "memory");
}
struct MOperands { uint4 A[2][2], B[4][2]; };
__device__ __forceinline__ void m_load(MOperands& m, const uint8_t* wqkv, uint32_t mt, uint32_t s, uint32_t q, uint32_t lane) {
    const uint32_t r8 = lane >> 2, col = q * 128 + (lane & 3) * 16;
    const uint8_t* pa = wqkv + (16 * mt + r8) * 1152 + col;
    const uint8_t* pb = wqkv + (16 * s + 8 * (r8 & 2) + (r8 & 5)) * 1152 + col;
#pragma unroll
    for (int c = 0; c < 2; c++) {
#pragma unroll
        for (int h = 0; h < 2; h++) m.A[h][c] = ldg(pa + 384 + h * 8 * 1152 + c * 64);
#pragma unroll
        for (int n = 0; n < 4; n++) m.B[n][c] = ldg(pb + ((n & 1) * 8 + (n & 2)) * 1152 + c * 64);
    }
}
__device__ __forceinline__ void m_partial(MOperands& m, uint32_t q, uint32_t lane, uint32_t zero) {
    auto& A = m.A;
    auto& B = m.B;
#pragma unroll
    for (int i = 0; i < 4; i++) { uint4& a = A[i >> 1][i & 1]; a.x ^= zero; a.y ^= zero; a.z ^= zero; a.w ^= zero; }
#pragma unroll
    for (int n = 0; n < 4; n++) {
        float d[4] = {0.f, 0.f, 0.f, 0.f};
#pragma unroll
        for (int c = 0; c < 2; c++) {
            mma16816(d, A[0][c].x, A[1][c].x, A[0][c].y, A[1][c].y, B[n][c].x, B[n][c].y);
            mma16816(d, A[0][c].z, A[1][c].z, A[0][c].w, A[1][c].w, B[n][c].z, B[n][c].w);
        }
        asm volatile("st.shared.v4.f32 [%0], {%1, %2, %3, %4};" ::"r"(s_wv + q * 2048 + n * 512 + lane * 16), "f"(d[0]), "f"(d[1]), "f"(d[2]), "f"(d[3]) : "memory");
    }
}
__device__ __forceinline__ void m_reduce(uint32_t e, uint32_t lane, float (&d)[2][4]) {
#pragma unroll
    for (int n = 0; n < 2; n++) {
        float t[3][4];
#pragma unroll
        for (int q = 0; q < 3; q++)
            asm volatile("ld.shared.v4.f32 {%0, %1, %2, %3}, [%4];" : "=f"(t[q][0]), "=f"(t[q][1]), "=f"(t[q][2]), "=f"(t[q][3]) : "r"(s_wv + q * 2048 + e * 1024 + n * 512 + lane * 16) : "memory");
#pragma unroll
        for (int i = 0; i < 4; i++) d[n][i] = (t[0][i] + t[1][i] + t[2][i]) * kScaleLog2e;
    }
}
__device__ __forceinline__ void w_piece(uint32_t q, uint32_t lane, float (&d)[2][4]) {
    const uint32_t rr = lane & 7, mi = lane >> 3, kr = 4 * (rr >> 1) + (mi & 2) + (rr & 1);
    const uint32_t pa = s_wv + q * 32 + (4 * (mi & 2) + rr) * 96 + ((mi & 1) << 4);
    const uint32_t pb = s_wv + 3 * 6144 + kr * 128 + (((mi & 1) ^ (kr & 7)) << 4);
    float e[2][4];
#pragma unroll
    for (int i = 0; i < 8; i++) (&d[0][0])[i] = (&e[0][0])[i] = 0.f;
#pragma unroll
    for (int k = 0; k < 12; k++) {
        uint32_t aq[4], bq[4];
        ldsm4_t(aq, pa + k * 1536);
        ldsm4(bq, (pb ^ ((k & 3) << 5)) + (k >> 2) * 2048);
        mma16816(k & 1 ? e[0] : d[0], aq[0], aq[1], aq[2], aq[3], bq[0], bq[1]);
        mma16816(k & 1 ? e[1] : d[1], aq[0], aq[1], aq[2], aq[3], bq[2], bq[3]);
    }
#pragma unroll
    for (int i = 0; i < 8; i++) (&d[0][0])[i] += (&e[0][0])[i];
}
__device__ __forceinline__ uint32_t piece_offset(uint32_t which, uint32_t s, uint32_t mt, uint32_t lane) {
    const uint32_t r8 = lane >> 2;
    return which * kWBytes + wimg_offset(which ? 32 * (mt >> 1) + 8 * (r8 >> 1) + 4 * (mt & 1) + (r8 & 1) : 16 * mt + r8, s, lane & 3);
}
__device__ __forceinline__ void piece_store(Scratch* g, uint32_t par, uint32_t off0, uint32_t which, const float (&d)[2][4]) {
#pragma unroll
    for (int hf = 0; hf < 2; hf++) {
        const uint32_t off = off0 ^ (hf ? which ? 288 : 1024 : 0);
        const uint32_t a = pack_bf16(d[0][2 * hf], d[0][2 * hf + 1]), b = pack_bf16(d[1][2 * hf], d[1][2 * hf + 1]);
        asm volatile("st.relaxed.gpu.global.v2.u32 [%0], {%1, %2};" ::"l"(g->img[0][0] + (par + off)), "r"(a ? a : 0x8000u), "r"(b) : "memory");
    }
}
__device__ __forceinline__ void piece_clear(Scratch* g, uint32_t par, uint32_t off0, uint32_t which) {
#pragma unroll
    for (int hf = 0; hf < 2; hf++)
        asm volatile("st.relaxed.gpu.global.v2.u32 [%0], {%1, %1};" ::"l"(g->img[0][0] + (par + (off0 ^ (hf ? which ? 288 : 1024 : 0)))), "r"(0) : "memory");
}

__device__ __forceinline__ uint32_t ld_relaxed(const uint32_t* p) {
    uint32_t v;
    asm volatile("ld.relaxed.gpu.global.u32 %0, [%1];" : "=r"(v) : "l"(p) : "memory");
    return v;
}
__device__ __forceinline__ void count_up(uint32_t* p) {
    asm volatile("red.relaxed.gpu.global.add.u32 [%0], %1;" ::"l"(p), "r"(1) : "memory");
}
__device__ __forceinline__ void bulk_g2s(uint32_t dst, const void* src, uint32_t bytes, uint32_t bar) {
    asm volatile("cp.async.bulk.shared::cluster.global.mbarrier::complete_tx::bytes [%0], [%1], %2, [%3];"
                 ::"r"(dst), "l"(src), "r"(bytes), "r"(bar)
                 : "memory");
}

__global__ void __launch_bounds__(kThreads, 1)
nat_fused_kernel(const uint8_t* __restrict__ x, const uint8_t* __restrict__ wqkv, uint8_t* __restrict__ out, Scratch* g,
                 const uint8_t* wo, uint64_t dsc, const __grid_constant__ Maps maps) {
    const int tid = threadIdx.x, lane = tid & 31;
    const int warp = __shfl_sync(0xffffffffu, tid >> 5, 0);
    const int wg = warp >> 2, wq = warp & 3, r8 = lane >> 2, j = lane & 3;
    const int cta = blockIdx.x;
    const Work w = decode_work(cta);
    const uint32_t jq = (cta < 124 ? cta + 8 : cta - 124) / 11u, jr = (cta < 124 ? cta + 8 : cta - 124) - 11 * jq;
    const uint32_t which = jr >= 6, jhi = which ? jr - 6 : jq, jlo = which ? jq : 2 * jr;
    const bool has_job = jr < 10;
    if (wg == 2 && wq < 3) {
#pragma unroll
        for (int r = 0; r < 3; r++)
            asm volatile("st.shared.v4.u32 [%0], {%1, %1, %1, %1};" ::"r"(s_ring + wq * kRingChunk + (r == 0 ? 84 : r == 1 ? 88 : 204) * 128 + lane * 16), "r"(0) : "memory");
        asm volatile("fence.proxy.async.shared::cta;" ::: "memory");
    }
    MOperands mo;
    uint32_t launch = 0;
    if (wg == 1 && wq < 3 && !which) m_load(mo, wqkv, jhi, jlo, wq, lane);
    if (warp == 7) launch = ld_relaxed(g->launches[cta]);
    if (x == nullptr) return;
    const uint32_t t_start = clock_now();
    if (wg == 2) {
        asm volatile("setmaxnreg.dec.sync.aligned.u32 24;");
        if (wq < 3) {
            if (lane < 3 && cta < 128) {
                const uint32_t row = 3 * (cta >> 1) + wq;
                asm volatile("prefetch.global.L2 [%0];" ::"l"((cta & 1 ? wo + row * 384 : wqkv + row * 1152 + 768) + lane * 128));
            }
            asm volatile("bar.sync 7, 192;" ::: "memory");
            const uint32_t par = lds_volatile(s_par);
            uint32_t phase = 0;
#pragma unroll 1
            for (uint32_t c = 0; c < 6; c++) {
                const uint32_t part = c * kWChunk + wq * (kWChunk / 3), img = 8 * min(c, 3u);
                mbar_wait(bar_img + 8 * c, 0);
                if (SPEC && c == 0 && lane == 0) mbar_arrive(bar_ok);
                if (wq == 0) TRW(10 + c);
#pragma unroll 1
                while (true) {
                    uint32_t lo = ~0u;
#pragma unroll
                    for (int q = 0; q < 8; q++) lo = min(lo, lds_volatile(s_m + part + lane * 32 + (lane & 12) * 2 + q * 1024));
                    if (__all_sync(0xffffffffu, lo) || phase > 65535) break;
                    if (elect()) {
                        mbar_expect_tx(bar_redo + 8 * wq, kWChunk / 3);
                        bulk_g2s(s_m + part, g->img[0][0] + par + part, kWChunk / 3, bar_redo + 8 * wq);
                    }
                    mbar_wait(bar_redo + 8 * wq, phase++ & 1);
                }
                if (c == 2 && phase) asm volatile("st.shared.u32 [%0], %1;" ::"r"(s_again), "r"(1) : "memory");
                if ((c == 2 || c == 5) && lane == 0) mbar_arrive(bar_ok + img);
            }
            if (PFROM && wq == 0 && !w.corner) {
#pragma unroll 1
                for (int n = PFROM; n < 48; n++) {
                    uint32_t o0, o1;
                    w.pixel_offsets(w.u + r8, w.step < 0 ? w.v + 7 - n : w.v + n, 8 * j, o0, o1);
                    if (j < 3) asm volatile("prefetch.global.L2 [%0];" ::"l"(x + o0));
                    __nanosleep(PNAP);
                }
            }
        } else {
            const CUtensorMap* map = &maps.m[w.sv == kPixBytes ? 2 : 0];
            if (elect()) {
#pragma unroll
                for (int i = 0; i < 20 + 3 * !!EARLY; i++) mbar_init(s_bar + 8 * i, i < 13 ? 1 : i < 18 ? 3 : 4);
                asm volatile("fence.mbarrier_init.release.cluster;" ::: "memory");
                prefetch_map(map + 1);
                expect_tx_only(bar_a, sizeof(Table));
                bulk_g2s(s_tab, &maps.tables->t[w.step < 0], sizeof(Table), bar_a);
            }
            if (which && has_job && elect()) {
                mbar_expect_tx(bar_wop, 4 * 6144);
                tma_3d(s_wv, &maps.wo, bar_wop, 0, jhi);
                tma_3d(s_wv + 3 * 6144, &maps.wv, bar_wop, 16 * jlo, 6);
            }
            int u = w.u, v = w.v;
            uint32_t wait_bar = bar_use, wait_par = 1, slot = 0;
#pragma unroll 1
            for (int step = 0; step < 7 - w.corner; step++) {
                const bool first = step == 0 || (w.corner && step == 4);
                const int row = v + 4 + (first ? -w.step : w.step) / 2, ou = origin_u(u);
                const bool final = EARLY && step == 6 - w.corner;
                uint32_t dst = final ? s_m : s_ring + (first ? 0 : slot), mid = (final ? s_m : s_ring) + kOffMid + 512, bar = first ? bar_a : bar_b;
                if (final) { wait_bar = bar_free; wait_par = 0; }
                if (!EARLY) mbar_wait(wait_bar, wait_par);
                if (!EARLY) TRW(24 + step);
#pragma unroll 1
                for (int ch = (cta & 1) * kC, n = 0; n < 3; n++, ch += 64, dst += kRingChunk, mid += kRingChunk) {
                    if (EARLY) mbar_wait(wait_bar, wait_par);
                    if (EARLY && n == 0) TRW(24 + step);
                    if (final && EARLY == 2) wait_bar += 8;
                    if (elect()) {
                        mbar_expect_tx(bar, first ? kSlotBytes : kSlotBytes + kMidBytes);
                        tma_box(dst, map, bar, ch, ou, (cta >> 1) & 1, row);
                    }
                    if (!first) {
                        if (elect()) tma_box(mid, map + 1, bar, ch, ou, (cta >> 1) & 1, v + 6);
                        bar += 8;
                    }
                }
                if (step == 0) {
                    asm volatile("st.shared.v2.u32 [%0], {%1, %1};" ::"r"(s_late), "r"(0) : "memory");
                    asm volatile("bar.arrive 3, 160;\nbar.arrive 4, 160;\nbar.arrive 8, 128;\nbar.sync 9, 64;" ::: "memory");
                }
                if (step < 2) {
                    if (step) {
                        asm volatile("bar.sync 6, 128;" ::: "memory");
                    }
                    const uint32_t par = __shfl_sync(0xffffffffu, lds_volatile(s_par), 0);
                    wait_until(t_start, step ? TN(5, kTimeW) : TN(6, kTimeM));
                    TRW(5 + 4 * step);
#pragma unroll 1
                    for (int c = 3 * step; c < 3 + 3 * step; c++)
                        if (elect()) {
                            mbar_expect_tx(bar_img + 8 * c, kWChunk);
                            bulk_g2s(s_m + c * kWChunk, g->img[0][0] + (par + c * kWChunk), kWChunk, bar_img + 8 * c);
                        }
                }
                const bool again = w.corner && step == 3;
                wait_bar = step == 0 ? bar_img + 8 * TN(1, 1) : again ? bar_use + 8 : bar_use;
                if (!again) {
                    wait_par = slot ? 0 : step != 0;
                    slot ^= kSlotStride;
                    if (w.corner && step == 2) { u += 8; v -= 8; } else if (step) v += w.step;
                }
            }
        }
        TRDUMP();
        return;
    }
    if (warp == 7) {
        asm volatile("st.shared.u32 [%0], %1;\nbar.arrive 9, 64;" ::"r"(s_par), "r"((launch & 1) * 2 * kWBytes) : "memory");
        g->launches[cta][lane] = launch + 1;
        asm volatile("bar.arrive 5, 128;" ::: "memory");
    }
    if (wg == 1 && wq < 3) {
        if (!which) m_partial(mo, wq, lane, (uint32_t)dsc & 1);
        const uint32_t off = piece_offset(which, which ? jlo : jlo + wq, which ? 3 * jhi + wq : jhi, lane);
        asm volatile("bar.sync %0, %1;" ::"r"(5 + (off >> 31)), "n"(128) : "memory");
        const uint32_t par = lds_volatile(s_par);
        if (which) asm volatile("bar.sync 8, 128;" ::: "memory");
        if (has_job && wq < 2 + which) {
            float d[2][4];
            if (wq == 0) TRX(which ? 1 : 18);
            if (which) {
                mbar_wait(bar_wop, 0);
                if (wq == 0) TRX(2);
                w_piece(wq, lane, d);
            } else {
                m_reduce(wq, lane, d);
            }
            piece_store(g, par, off, which, d);
            __syncwarp();
            piece_clear(g, 2 * kWBytes - par, off, which);
            if (wq == 0) TRX(which ? 3 : 0);
        }
        if (!which) asm volatile("bar.sync 8, 128;" ::: "memory");
        asm volatile("bar.arrive 7, 192;\nbar.arrive 6, 128;" ::: "memory");
    }
    const int order = w.step < 0 ? warp ^ 3 : warp;
    int tu = w.u, tv = w.v + w.step * wg;
    const int du2 = w.corner ? 8 : 0, dv2 = w.corner ? 0 : 2 * w.step;
    uint32_t o0, o1;
    wait_until(t_start, START_TIME);
    asm volatile("setmaxnreg.inc.sync.aligned.u32 240;");
    w.pixel_offsets(tu + r8, tv + 2 * wq, j, o0, o1);
    uint32_t fa[48];
    {
        RawX raw;
        load_raw(raw, x, o0, o1);
        asm volatile("bar.sync %0, 160;" ::"r"(3 + wg) : "memory");
        raw_to_frags(raw, 0, fa);
        pin(fa);
    }
    mbar_wait(bar_ok, 0);
    const uint64_t dA = dsc + wg * (kSlotStride >> 4), dB = dsc + (wg ^ 1) * (kSlotStride >> 4);

    float acc[96];
    uint32_t po[48];
    uint32_t c0, c1;
    asm volatile("" : "=r"(c0), "=r"(c1));
#pragma unroll
    for (int q = 0; q < 48; q++) asm volatile("" : "=r"(po[q]));
#pragma unroll 1
    for (int i = wg; i < w.ntiles; i += 2) {
        const bool first = i == 0, last = i == w.ntiles - 1;

        TRF(8 + 16 * k);
        uint8_t *p0 = out + c0, *p1 = out + c1;
#pragma unroll 1
        for (uint32_t seen = 0;;) {
        wg_fence();
        if (!first) turn_wait(wg);
        proj_gemm(acc, fa, dsc, s_m, [&](int s) {
            if (s == 11 && !first) turn_pass(wg);
            const int n = __builtin_popcount(QSLOTS & ((1 << s) - 1));
            if (((QSLOTS >> s) & 1) && n < 12) store_one(i >= 2, out + c0, out + c1, po, n);
            if (s == 3 || s == 7) { if (EARLY == 2) wg_commit(); mbar_wait((SPEC ? bar_img : bar_ok) + 2 * s + 2, 0); wg_fence(); }
        });
        __syncwarp();
        TRF(9 + 16 * k);
            if (!first) break;
            mbar_wait(bar_ok + 16, 0);
            if (lds_volatile(s_again) == seen) break;
            wg_wait<0>();
            seen = 1;
        }
        c0 = o0; c1 = o1;
        w.pixel_offsets(tu + du2 + r8, tv + dv2 + 2 * wq, j, o0, o1);
        if (i + 2 >= w.ntiles) o0 = o1 = 0;
        mbar_wait(bar_a, w.corner ? i >> 1 : 0);
        if (EARLY == 2) {
            wg_wait<2>();
            if (last && lane == 0) mbar_arrive(bar_free);
            wg_wait<1>();
            if (last && lane == 0) mbar_arrive(bar_free + 8);
        }
        wg_wait<0>();
        if (EARLY && last && lane == 0) mbar_arrive(bar_free + (EARLY == 2 ? 16 : 0));
        const uint64_t dE = EARLY && last ? dsc + ((s_m - s_ring) >> 4) : dsc, dN = EARLY && last ? dE : dB;
        pin(acc);
        TR(11 + 16 * k);
        TRT(80 + k);
#pragma unroll
        for (int n = __builtin_popcount(QSLOTS); n < 12 - __builtin_popcount(ASLOTS) - __builtin_popcount(BSLOTS); n++) store_one(i >= 2, p0, p1, po, n);
        acc_to_frags(acc, fa);
        pin(fa);

        float sA[44], sE[16], sB[44];
        RawX nxt;
        if (!first) turn_wait(wg);
        wg_fence();
#pragma unroll
        for (int s = 0; s < 12; s++) {
            if (s == 0) wgmma_n88<true>(sA, fa[4 * s], fa[4 * s + 1], fa[4 * s + 2], fa[4 * s + 3], desc_at(dA, (s >> 2) * kRingChunk + (s & 3) * 32));
            else wgmma_n88<false>(sA, fa[4 * s], fa[4 * s + 1], fa[4 * s + 2], fa[4 * s + 3], desc_at(dA, (s >> 2) * kRingChunk + (s & 3) * 32));
            if (s == 11) { wg_commit(); if (!first) turn_pass(wg); }
            if ((ASLOTS >> s) & 1) store_one(i >= 2, p0, p1, po, 12 - __builtin_popcount(BSLOTS) - __builtin_popcount(ASLOTS >> s));
        }
#pragma unroll
        for (int s = 12; s < 16; s++)
            if ((ASLOTS >> s) & 1) store_one(i >= 2, p0, p1, po, 12 - __builtin_popcount(BSLOTS) - __builtin_popcount(ASLOTS >> s));
        TRF(12 + 16 * k);
        const int vq = tv + 2 * wq;
        const uint4 tabu = lds128(s_tab + offsetof(Table, u) + (window_start(tu + r8) - origin_u(tu)) * 64 + j * 16);
        const uint4 tabv = lds128(s_tab + offsetof(Table, v) + (window_start(vq) + window_start(vq + 1) - 2 * tv) * 64 + j * 16);
        const uint4 route = lds128(s_tab + lane * 16);
        load_raw(nxt, x, o0, o1);
        float v0[14], v1[14];
#pragma unroll
        for (int b = 0; b < 14; b++) v0[b] = v1[b] = __int_as_float(0xff800000);
        wg_wait<0>();
        pin(sA);
        gather_outer(sA, tabu.x, tabv.x, v0, v1);
        pin(v0); pin(v1);
        if (!first) turn_wait(wg);
#pragma unroll
        for (int c = 0; c < 3; c++) {
            mbar_wait(bar_b + 8 * c, wg);
            TRF(64 + 4 * k + c);
            wg_fence();
#pragma unroll
            for (int s = 4 * c; s < 4 * c + 4; s++) {
                if (s == 0) wgmma_n88<true>(sB, fa[4 * s], fa[4 * s + 1], fa[4 * s + 2], fa[4 * s + 3], desc_at(dN, c * kRingChunk + (s & 3) * 32));
                else wgmma_n88<false>(sB, fa[4 * s], fa[4 * s + 1], fa[4 * s + 2], fa[4 * s + 3], desc_at(dN, c * kRingChunk + (s & 3) * 32));
                if ((BSLOTS >> s) & 1) store_one(i >= 2, p0, p1, po, 12 - __builtin_popcount(BSLOTS >> s));
            }
        }
        wg_commit();
#pragma unroll
        for (int s = 0; s < 12; s++)
            if (s == 0) wgmma_n32<true>(sE, fa[4 * s], fa[4 * s + 1], fa[4 * s + 2], fa[4 * s + 3], desc_at(dE, kOffMid + (s >> 2) * kRingChunk + (s & 3) * 32));
            else wgmma_n32<false>(sE, fa[4 * s], fa[4 * s + 1], fa[4 * s + 2], fa[4 * s + 3], desc_at(dE, kOffMid + (s >> 2) * kRingChunk + (s & 3) * 32));
        wg_commit();
        if (OSPLIT || !last) turn_pass(wg);
        TRF(13 + 16 * k);
        wg_wait<1>();
        pin(sB);
        gather_outer(sB, tabu.w, tabv.y, v0, v1);
        wg_wait<0>();
        pin(sE);
        TRF(14 + 16 * k);
        gather_mid(sE, tabu.w, tabv.z, v0, v1);
        const float m0 = quad_max(tree_max(v0)), m1 = quad_max(tree_max(v1));

        uint32_t y[14], pa[12], pb[12];
        exp_route<0, 14>(v0, v1, m0, m1, route, (j & 1) == 0, y);
        float s0 = tree_sum(v0), s1 = tree_sum(v1);
        asm volatile("" : "+f"(s0), "+f"(s1));
        unfold<0, 0, 6>(y, tabv.w, pa);
        if (OSPLIT || !last) turn_wait(wg + (y[0] >> 31));
        TRF(15 + 16 * k + (y[13] >> 31));
        wg_fence();
        wgmma_sp_n192_tb<true, 0>(acc, pa[0], pa[1], pa[2], pa[3], desc_at(dA, kToV), tabu.y);
        wgmma_sp_n192_tb<false, 1>(acc, pa[4], pa[5], pa[6], pa[7], desc_at(dA, kToV + 4096), tabu.y);
        wgmma_sp_n192_tb<false, 0>(acc, pa[8], pa[9], pa[10], pa[11], desc_at(dA, kToV + 8192), tabu.z);
        wgmma_sp_n192_tb<false, 1>(acc, EARLY && j == 0 ? 0u : y[10], EARLY && j == 0 ? 0u : y[11], y[12], y[13], desc_at(dE, kToV + kOffMid), tabu.z);
        wg_commit();
        unfold<8, 0, 6>(y, tabv.w, pb);
        wg_fence();
        wgmma_sp_n192_tb<false, 0>(acc, pb[0], pb[1], pb[2], pb[3], desc_at(dN, kToV), tabu.y);
        wgmma_sp_n192_tb<false, 1>(acc, pb[4], pb[5], pb[6], pb[7], desc_at(dN, kToV + 4096), tabu.y);
        wgmma_sp_n192_tb<false, 0>(acc, pb[8], pb[9], pb[10], pb[11], desc_at(dN, kToV + 8192), tabu.z);
        wg_commit();
        if (!last) turn_pass(wg);
        TRF(16 + 16 * k);
        wg_wait<1>();
        if (lane == 0) mbar_arrive(bar_use);
        TRF(17 + 16 * k);
        mbar_wait(bar_ok + 24, 0);
        wg_wait<0>();
        if (lane == 0) mbar_arrive(bar_use + 8);
        pin(acc);
        TR(18 + 16 * k);

        acc_to_frags(acc, po);
        pin(po);
        if (!last) turn_wait(wg);
        wg_fence();
        proj_gemm(acc, po, dsc, s_wv, [&](int s) {
            if (s + 1 == OSPLIT && i + 2 == w.ntiles) { turn_pass(wg); turn_wait(wg); }
        });
        if (!last) turn_pass(wg);
        TRF(19 + 16 * k);
        const uint32_t zero = lds_volatile(s_late);
        const float inv0 = rcp(quad_sum(s0 + __uint_as_float(zero))), inv1 = rcp(quad_sum(s1 + __uint_as_float(zero)));
        raw_to_frags(nxt, zero, fa);
        pin(fa);
#pragma unroll
        for (int q = 0; q < 48; q += 4) keep(wqkv == nullptr, fa[q], fa[q + 1], fa[q + 2], fa[q + 3]);
        keep(wqkv == nullptr, __float_as_uint(inv0), __float_as_uint(inv1), zero, lane);
        TRF(20 + 16 * k);
        tu += du2; tv += dv2;
        wg_wait<0>();
        pin(acc);
        TR(21 + 16 * k);
#pragma unroll
        for (int q = 0; q < 96; q++) acc[q] *= q & 2 ? inv1 : inv0;
        pack_out(acc, po);
#pragma unroll
        for (int n = 0; n < INLOOP; n++) store_one<false>(last, out + c0, out + c1, po, n);
        pin(po);
    }
#pragma unroll
    for (int n = 0; n < 12; n++) {
        if (NAP) asm volatile("{\n.reg .pred p;\nsetp.eq.u32 p, %0, 0;\n@p nanosleep.u32 %1;\n}\n" ::"r"(wg), "n"(NAP) : "memory");
        store_one<false>(n >= INLOOP || wg == 0, out + c0, out + c1, po, n);
    }
    TRE(7);
    TRG(1);
    TRDUMP();
}

typedef CUresult (*EncodeTiledFn)(CUtensorMap*, CUtensorMapDataType, cuuint32_t, void*, const cuuint64_t*, const cuuint64_t*,
                                  const cuuint32_t*, const cuuint32_t*, CUtensorMapInterleave, CUtensorMapSwizzle,
                                  CUtensorMapL2promotion, CUtensorMapFloatOOBfill);

bool make_maps(EncodeTiledFn fn, Maps* maps, void* x, void* wqkv, void* wo) {
    const cuuint64_t pix2 = 2 * kPixBytes, row = (cuuint64_t)kHW * kPixBytes;
    const cuuint32_t estr[5] = {1, 1, 1, 1, 1};
    bool ok = true;
    for (int tr = 0; tr < 2; tr++)
        for (int b = 0; b < 2; b++) {
            const cuuint64_t su = tr ? 2 * row : pix2, sv = tr ? pix2 : 2 * row;
            const cuuint64_t dims[5] = {2 * kC, 2, 105, 2, 112};
            const cuuint64_t strides[4] = {7 * su, su, row, sv};
            const cuuint32_t box[5] = {64, 2, 7, 1, b ? 2u : 6u};
            ok = ok && fn(&maps->m[2 * tr + b], CU_TENSOR_MAP_DATA_TYPE_BFLOAT16, 5, x, dims, strides, box, estr,
                          CU_TENSOR_MAP_INTERLEAVE_NONE, CU_TENSOR_MAP_SWIZZLE_128B, CU_TENSOR_MAP_L2_PROMOTION_L2_128B,
                          CU_TENSOR_MAP_FLOAT_OOB_FILL_NONE) == CUDA_SUCCESS;
        }
    for (int b = 0; b < 2; b++) {
        const cuuint64_t dims[3] = {b ? 64u : 48u, kC, b ? 9u : 4u}, strides[2] = {(b ? 3u : 1u) * kPixBytes, b ? 128u : 96u};
        const cuuint32_t box[3] = {b ? 64u : 48u, b ? 16u : 192u, b ? 3u : 1u};
        ok = ok && fn(b ? &maps->wv : &maps->wo, CU_TENSOR_MAP_DATA_TYPE_BFLOAT16, 3, b ? wqkv : wo, dims, strides, box, estr,
                      CU_TENSOR_MAP_INTERLEAVE_NONE, b ? CU_TENSOR_MAP_SWIZZLE_128B : CU_TENSOR_MAP_SWIZZLE_NONE, CU_TENSOR_MAP_L2_PROMOTION_L2_128B,
                      CU_TENSOR_MAP_FLOAT_OOB_FILL_NONE) == CUDA_SUCCESS;
    }
    return ok;
}

}

extern "C" void kernel_launch(void* const* d_in, const int* in_sizes, int n_in, void* d_out, int out_size) {
    static EncodeTiledFn encode = nullptr;
    static Scratch* scratch = nullptr;
    static Tables* tables = nullptr;
    if (!encode) {
        int dev = 0, reserved = 0;
        cudaFuncAttributes attr;
        cudaGetDevice(&dev);
        cudaDeviceGetAttribute(&reserved, cudaDevAttrReservedSharedMemoryPerBlock, dev);
        cudaFuncGetAttributes(&attr, nat_fused_kernel);
        if (reserved != (int)kSmemBase || attr.sharedSizeBytes != 0) return;
        cudaGetSymbolAddress((void**)&scratch, g_scratch);
        cudaGetSymbolAddress((void**)&tables, g_tables);
        void* fn = nullptr;
        cudaDriverEntryPointQueryResult st;
        cudaGetDriverEntryPoint("cuTensorMapEncodeTiled", &fn, cudaEnableDefault, &st);
        encode = (EncodeTiledFn)fn;
        cudaFuncSetAttribute(nat_fused_kernel, cudaFuncAttributeMaxDynamicSharedMemorySize, kSmemBytes);
    }
    Maps maps;
    maps.tables = tables;
    if (!encode || !make_maps(encode, &maps, d_in[0], d_in[1], d_in[2])) return;
    nat_fused_kernel<<<kGrid, kThreads, kSmemBytes>>>((const uint8_t*)d_in[0], (const uint8_t*)d_in[1], (uint8_t*)d_out, scratch, (const uint8_t*)d_in[2],
                                                      kDescRing, maps);
}
```

```cpp
#include <cuda_runtime.h>
#include <cuda_bf16.h>
#include <cuda.h>
#include <stdint.h>
#include <type_traits>
#include <stdlib.h>
#include <stdio.h>
#include <stddef.h>

#define ASLOTS 0x3800
#define BSLOTS 0x6
#define QSLOTS 0x78a
#define OSPLIT 2
#define NAP 40
#define PFROM 24
#define PNAP 160
#define INLOOP 3

namespace {

constexpr int kC          = 192;
constexpr int kHW         = 224;
constexpr int kPixBytes   = kC * 2;
constexpr int kSlotBytes  = 84 * 128;
constexpr int kMidBytes   = 28 * 128;
constexpr int kOffMid     = 88 * 128;
constexpr int kSlotStride = 120 * 128;
constexpr int kRingChunk  = 208 * 128;
constexpr int kWChunk     = 192 * 128;
constexpr int kWBytes     = 3 * kWChunk;
constexpr uint32_t kSmemBase = 1024;
constexpr uint32_t s_ring = kSmemBase, s_m = s_ring + 3 * kRingChunk, s_wv = s_m + kWBytes, s_bar = s_wv + kWBytes;
constexpr uint32_t bar_b = s_bar, bar_img = s_bar + 24, bar_redo = s_bar + 72, bar_wop = s_bar + 96, bar_a = s_bar + 104,
                   bar_ok = s_bar + 112, bar_use = s_bar + 144, bar_free = s_bar + 160;
constexpr uint32_t s_par = s_bar + 192, s_late = s_bar + 200, s_again = s_bar + 204, s_tab = s_bar + 256, s_trace = s_tab + 2048;
constexpr int kSmemBytes  = s_trace + 2048 - kSmemBase;
constexpr int kThreads    = 384;
constexpr int kGrid       = 132;
constexpr int kTimeM = 2500, kTimeW = 5100;
constexpr float kScaleLog2e = 0.07216878364870322f * 1.4426950408889634f;

struct Maps {
    CUtensorMap m[4];
    CUtensorMap wo, wv;
    const struct Tables* tables;
};
#define TN(i, dflt) (dflt)
#define START_TIME (wg ? 850 + 500 * order : 250 + 560 * order)

struct Scratch {
    uint8_t img[2][2][kWBytes];
    uint32_t launches[kGrid][32];
};
__device__ __align__(1024) Scratch g_scratch;

struct Table {
    uint32_t route[32][4];
    uint32_t u[8][4][4];
    uint32_t v[16][4][4];
};
struct Tables { Table t[2]; };
constexpr Tables make_tables() {
    Tables r = {};
    for (int rev = 0; rev < 2; rev++)
        for (int j = 0; j < 4; j++) {
            Table& t = r.t[rev];
            for (int q = 0; q < 8; q++) {
                uint32_t* e = t.route[4 * q + j];
                e[0] = 4 * q + 2 * (j & 1) + (j >> 1); e[1] = e[0] ^ 1;
                e[2] = j < 2 ? 0x5410u : 0x1054u; e[3] = e[2] + 0x2222u;
                e = t.u[q][j];
                for (int n = 0; n < 7; n++) e[0] |= ((n + j) % 7 < q ? 1u : 0u) << n;
                e[3] = e[0];
                for (int k = 0; k < 2; k++) {
                    const int step = 2 * k + (j >> 1), p0 = (step < 3 ? 16 * step : 40) + 8 * (j & 1);
                    uint32_t m = 0x8888u;
                    for (int n = 0; n < 8; n++) m |= ((p0 + n) % 7 < q ? 1u : 0u) << (2 * n);
                    e[1 + k] = m * 0x10001u;
                }
            }
            for (int sum = 0; sum < 15; sum++) {
                uint32_t* e = t.v[sum][j];
                for (int row = 0; row < 2; row++)
                    for (int b = 0; b < 14; b++) {
                        const int off = (sum + row) / 2, p = 4 * b + j;
                        const uint32_t bit = 1u << (2 * b + row);
                        if (p < 42 && p >= 7 * off) e[rev] |= bit;
                        if (p < 7 * off - 7) e[1 - rev] |= bit;
                        if (p >= 42 && p >= 7 * off && p < 7 * off + 49) e[2] |= bit;
                    }
                for (int n = 0; n < 6; n++)
                    if (8 * n + 2 * j < 42) e[3] |= 1u << (n + ((8 * n + 2 * j >= 7 * (sum / 2 & ~1)) != rev ? 0 : 8));
            }
        }
    return r;
}
__device__ __align__(128) const Tables g_tables = make_tables();

#define WO4(i) "=f"(d[i]), "=f"(d[i + 1]), "=f"(d[i + 2]), "=f"(d[i + 3])
#define RW4(i) "+f"(d[i]), "+f"(d[i + 1]), "+f"(d[i + 2]), "+f"(d[i + 3])

template <bool FIRST>
__device__ __forceinline__ void wgmma_n192(float (&d)[96], uint32_t a0, uint32_t a1, uint32_t a2, uint32_t a3, uint64_t descb) {
    if constexpr (FIRST) {
        asm volatile(
            "wgmma.mma_async.sync.aligned.m64n192k16.f32.bf16.bf16 "
            "{%0, %1, %2, %3, %4, %5, %6, %7, %8, %9, %10, %11, %12, %13, %14, %15, %16, %17, %18, %19, %20, %21, %22, %23, "
            "%24, %25, %26, %27, %28, %29, %30, %31, %32, %33, %34, %35, %36, %37, %38, %39, %40, %41, %42, %43, %44, %45, %46, %47, "
            "%48, %49, %50, %51, %52, %53, %54, %55, %56, %57, %58, %59, %60, %61, %62, %63, %64, %65, %66, %67, %68, %69, %70, %71, "
            "%72, %73, %74, %75, %76, %77, %78, %79, %80, %81, %82, %83, %84, %85, %86, %87, %88, %89, %90, %91, %92, %93, %94, %95}, "
            "{%96, %97, %98, %99}, %100, 0, 1, 1, 0;"
            : WO4(0), WO4(4), WO4(8), WO4(12), WO4(16), WO4(20), WO4(24), WO4(28), WO4(32), WO4(36), WO4(40), WO4(44),
              WO4(48), WO4(52), WO4(56), WO4(60), WO4(64), WO4(68), WO4(72), WO4(76), WO4(80), WO4(84), WO4(88), WO4(92)
            : "r"(a0), "r"(a1), "r"(a2), "r"(a3), "l"(descb));
    } else {
        asm volatile(
            "wgmma.mma_async.sync.aligned.m64n192k16.f32.bf16.bf16 "
            "{%0, %1, %2, %3, %4, %5, %6, %7, %8, %9, %10, %11, %12, %13, %14, %15, %16, %17, %18, %19, %20, %21, %22, %23, "
            "%24, %25, %26, %27, %28, %29, %30, %31, %32, %33, %34, %35, %36, %37, %38, %39, %40, %41, %42, %43, %44, %45, %46, %47, "
            "%48, %49, %50, %51, %52, %53, %54, %55, %56, %57, %58, %59, %60, %61, %62, %63, %64, %65, %66, %67, %68, %69, %70, %71, "
            "%72, %73, %74, %75, %76, %77, %78, %79, %80, %81, %82, %83, %84, %85, %86, %87, %88, %89, %90, %91, %92, %93, %94, %95}, "
            "{%96, %97, %98, %99}, %100, 1, 1, 1, 0;"
            : RW4(0), RW4(4), RW4(8), RW4(12), RW4(16), RW4(20), RW4(24), RW4(28), RW4(32), RW4(36), RW4(40), RW4(44),
              RW4(48), RW4(52), RW4(56), RW4(60), RW4(64), RW4(68), RW4(72), RW4(76), RW4(80), RW4(84), RW4(88), RW4(92)
            : "r"(a0), "r"(a1), "r"(a2), "r"(a3), "l"(descb));
    }
}

template <bool FIRST>
__device__ __forceinline__ void wgmma_n88(float (&d)[44], uint32_t a0, uint32_t a1, uint32_t a2, uint32_t a3, uint64_t descb) {
    if constexpr (FIRST) {
        asm volatile(
            "wgmma.mma_async.sync.aligned.m64n88k16.f32.bf16.bf16 "
            "{%0, %1, %2, %3, %4, %5, %6, %7, %8, %9, %10, %11, %12, %13, %14, %15, %16, %17, %18, %19, %20, %21, %22, %23, "
            "%24, %25, %26, %27, %28, %29, %30, %31, %32, %33, %34, %35, %36, %37, %38, %39, %40, %41, %42, %43}, "
            "{%44, %45, %46, %47}, %48, 0, 1, 1, 0;"
            : WO4(0), WO4(4), WO4(8), WO4(12), WO4(16), WO4(20), WO4(24), WO4(28), WO4(32), WO4(36), WO4(40)
            : "r"(a0), "r"(a1), "r"(a2), "r"(a3), "l"(descb));
    } else {
        asm volatile(
            "wgmma.mma_async.sync.aligned.m64n88k16.f32.bf16.bf16 "
            "{%0, %1, %2, %3, %4, %5, %6, %7, %8, %9, %10, %11, %12, %13, %14, %15, %16, %17, %18, %19, %20, %21, %22, %23, "
            "%24, %25, %26, %27, %28, %29, %30, %31, %32, %33, %34, %35, %36, %37, %38, %39, %40, %41, %42, %43}, "
            "{%44, %45, %46, %47}, %48, 1, 1, 1, 0;"
            : RW4(0), RW4(4), RW4(8), RW4(12), RW4(16), RW4(20), RW4(24), RW4(28), RW4(32), RW4(36), RW4(40)
            : "r"(a0), "r"(a1), "r"(a2), "r"(a3), "l"(descb));
    }
}

template <bool FIRST>
__device__ __forceinline__ void wgmma_n32(float (&d)[16], uint32_t a0, uint32_t a1, uint32_t a2, uint32_t a3, uint64_t descb) {
    if constexpr (FIRST) {
        asm volatile(
            "wgmma.mma_async.sync.aligned.m64n32k16.f32.bf16.bf16 "
            "{%0, %1, %2, %3, %4, %5, %6, %7, %8, %9, %10, %11, %12, %13, %14, %15}, "
            "{%16, %17, %18, %19}, %20, 0, 1, 1, 0;"
            : WO4(0), WO4(4), WO4(8), WO4(12)
            : "r"(a0), "r"(a1), "r"(a2), "r"(a3), "l"(descb));
    } else {
        asm volatile(
            "wgmma.mma_async.sync.aligned.m64n32k16.f32.bf16.bf16 "
            "{%0, %1, %2, %3, %4, %5, %6, %7, %8, %9, %10, %11, %12, %13, %14, %15}, "
            "{%16, %17, %18, %19}, %20, 1, 1, 1, 0;"
            : RW4(0), RW4(4), RW4(8), RW4(12)
            : "r"(a0), "r"(a1), "r"(a2), "r"(a3), "l"(descb));
    }
}

template <bool FIRST, int SEL>
__device__ __forceinline__ void wgmma_sp_n192_tb(float (&d)[96], uint32_t a0, uint32_t a1, uint32_t a2, uint32_t a3, uint64_t descb, uint32_t meta) {
    if constexpr (FIRST) {
        asm volatile(
            "wgmma.mma_async.sp.sync.aligned.m64n192k32.f32.bf16.bf16 "
            "{%0, %1, %2, %3, %4, %5, %6, %7, %8, %9, %10, %11, %12, %13, %14, %15, %16, %17, %18, %19, %20, %21, %22, %23, "
            "%24, %25, %26, %27, %28, %29, %30, %31, %32, %33, %34, %35, %36, %37, %38, %39, %40, %41, %42, %43, %44, %45, %46, %47, "
            "%48, %49, %50, %51, %52, %53, %54, %55, %56, %57, %58, %59, %60, %61, %62, %63, %64, %65, %66, %67, %68, %69, %70, %71, "
            "%72, %73, %74, %75, %76, %77, %78, %79, %80, %81, %82, %83, %84, %85, %86, %87, %88, %89, %90, %91, %92, %93, %94, %95}, "
            "{%96, %97, %98, %99}, %100, %101, %102, 0, 1, 1, 1;"
            : WO4(0), WO4(4), WO4(8), WO4(12), WO4(16), WO4(20), WO4(24), WO4(28), WO4(32), WO4(36), WO4(40), WO4(44),
              WO4(48), WO4(52), WO4(56), WO4(60), WO4(64), WO4(68), WO4(72), WO4(76), WO4(80), WO4(84), WO4(88), WO4(92)
            : "r"(a0), "r"(a1), "r"(a2), "r"(a3), "l"(descb), "r"(meta), "n"(SEL));
    } else {
        asm volatile(
            "wgmma.mma_async.sp.sync.aligned.m64n192k32.f32.bf16.bf16 "
            "{%0, %1, %2, %3, %4, %5, %6, %7, %8, %9, %10, %11, %12, %13, %14, %15, %16, %17, %18, %19, %20, %21, %22, %23, "
            "%24, %25, %26, %27, %28, %29, %30, %31, %32, %33, %34, %35, %36, %37, %38, %39, %40, %41, %42, %43, %44, %45, %46, %47, "
            "%48, %49, %50, %51, %52, %53, %54, %55, %56, %57, %58, %59, %60, %61, %62, %63, %64, %65, %66, %67, %68, %69, %70, %71, "
            "%72, %73, %74, %75, %76, %77, %78, %79, %80, %81, %82, %83, %84, %85, %86, %87, %88, %89, %90, %91, %92, %93, %94, %95}, "
            "{%96, %97, %98, %99}, %100, %101, %102, 1, 1, 1, 1;"
            : RW4(0), RW4(4), RW4(8), RW4(12), RW4(16), RW4(20), RW4(24), RW4(28), RW4(32), RW4(36), RW4(40), RW4(44),
              RW4(48), RW4(52), RW4(56), RW4(60), RW4(64), RW4(68), RW4(72), RW4(76), RW4(80), RW4(84), RW4(88), RW4(92)
            : "r"(a0), "r"(a1), "r"(a2), "r"(a3), "l"(descb), "r"(meta), "n"(SEL));
    }
}

#define TR(slot)
#define TRX(slot)
#define TRE(slot)
#define TRT(slot)
#define TRF(slot)
#define TRW(slot)
#define TRG(slot)
#define TRDUMP()

__device__ __forceinline__ void wg_fence() { asm volatile("wgmma.fence.sync.aligned;" ::: "memory"); }
__device__ __forceinline__ void wg_commit() { asm volatile("wgmma.commit_group.sync.aligned;" ::: "memory"); }
template <int N>
__device__ __forceinline__ void wg_wait() { asm volatile("wgmma.wait_group.sync.aligned %0;" ::"n"(N) : "memory"); }

template <int N>
__device__ __forceinline__ void pin(float (&d)[N]) {
#pragma unroll
    for (int i = 0; i < N; i++) asm volatile("" : "+f"(d[i])::"memory");
}
template <int N>
__device__ __forceinline__ void pin(uint32_t (&d)[N]) {
#pragma unroll
    for (int i = 0; i < N; i++) asm volatile("" : "+r"(d[i])::"memory");
}

constexpr uint64_t kDescRing = ((uint64_t)((1u << 30) | (1024u >> 4)) << 32) | (1u << 16) | (s_ring >> 4);
constexpr uint32_t kToV = ((kRingChunk >> 4) - 1) << 20;
__device__ __forceinline__ uint64_t desc_at(uint64_t base, uint32_t byte_off) {
    uint64_t d;
    asm volatile("add.s64 %0, %1, %2;" : "=l"(d) : "l"(base), "l"((uint64_t)(byte_off >> 4)));
    return d;
}

__device__ __forceinline__ void mbar_init(uint32_t bar, uint32_t count) {
    asm volatile("mbarrier.init.shared::cta.b64 [%0], %1;" ::"r"(bar), "r"(count) : "memory");
}
__device__ __forceinline__ void mbar_expect_tx(uint32_t bar, uint32_t bytes) {
    asm volatile("mbarrier.arrive.expect_tx.shared::cta.b64 _, [%0], %1;" ::"r"(bar), "r"(bytes) : "memory");
}
__device__ __forceinline__ void expect_tx_only(uint32_t bar, uint32_t bytes) {
    asm volatile("mbarrier.expect_tx.relaxed.cta.shared::cta.b64 [%0], %1;" ::"r"(bar), "r"(bytes) : "memory");
}
__device__ __forceinline__ void mbar_arrive(uint32_t bar) {
    asm volatile("mbarrier.arrive.shared::cta.b64 _, [%0];" ::"r"(bar) : "memory");
}
__device__ __forceinline__ void mbar_wait(uint32_t bar, uint32_t parity) {
    asm volatile(
        "{\n.reg .pred p;\n"
        "W: mbarrier.try_wait.parity.shared::cta.b64 p, [%0], %1;\n"
        "@!p bra W;\n}\n"
        ::"r"(bar), "r"(parity) : "memory");
}
__device__ __forceinline__ uint32_t clock_now() {
    uint32_t c;
    asm volatile("mov.u32 %0, %%clock;" : "=r"(c)::"memory");
    return c;
}
__device__ __forceinline__ void wait_until(uint32_t t0, int t) {
    if (t == 0) return;
    while ((int)(clock_now() - t0) < t) {}
}
__device__ __forceinline__ bool elect() {
    uint32_t ok;
    asm volatile("{\n.reg .pred p;\nelect.sync _|p, 0xffffffff;\nselp.u32 %0, 1, 0, p;\n}\n" : "=r"(ok));
    return ok != 0;
}
__device__ __forceinline__ void turn_wait(int wg) { asm volatile("bar.sync %0, 256;" ::"r"(1 + wg) : "memory"); }
__device__ __forceinline__ void turn_pass(int wg) { asm volatile("bar.arrive %0, 256;" ::"r"(2 - wg) : "memory"); }

__device__ __forceinline__ void tma_box(uint32_t dst, const CUtensorMap* map, uint32_t bar, int c0, int c2, int c3, int c4) {
    asm volatile(
        "cp.async.bulk.tensor.5d.shared::cluster.global.mbarrier::complete_tx::bytes [%0], [%1, {%3, %4, %5, %6, %7}], [%2];"
        ::"r"(dst), "l"(map), "r"(bar), "r"(c0), "r"(0), "r"(c2), "r"(c3), "r"(c4)
        : "memory");
}
__device__ __forceinline__ void tma_3d(uint32_t dst, const CUtensorMap* map, uint32_t bar, int c1, int c2) {
    asm volatile("cp.async.bulk.tensor.3d.shared::cluster.global.mbarrier::complete_tx::bytes [%0], [%1, {%3, %4, %5}], [%2];"
                 ::"r"(dst), "l"(map), "r"(bar), "r"(0), "r"(c1), "r"(c2)
                 : "memory");
}
__device__ __forceinline__ void prefetch_map(const CUtensorMap* map) {
    asm volatile("prefetch.tensormap [%0];" ::"l"(map) : "memory");
}
__device__ __forceinline__ uint4 ldg(const void* p) {
    uint4 v;
    asm volatile("ld.global.v4.u32 {%0, %1, %2, %3}, [%4];" : "=r"(v.x), "=r"(v.y), "=r"(v.z), "=r"(v.w) : "l"(p) : "memory");
    return v;
}
__device__ __forceinline__ uint32_t pack_bf16(float lo, float hi) {
    uint32_t r;
    asm("cvt.rn.bf16x2.f32 %0, %1, %2;" : "=r"(r) : "f"(hi), "f"(lo));
    return r;
}
__device__ __forceinline__ float ex2(float x) {
    float y;
    asm("ex2.approx.ftz.f32 %0, %1;" : "=f"(y) : "f"(x));
    return y;
}
__device__ __forceinline__ float rcp(float x) {
    float y;
    asm("rcp.approx.ftz.f32 %0, %1;" : "=f"(y) : "f"(x));
    return y;
}
__device__ __forceinline__ void mma16816(float (&d)[4], uint32_t a0, uint32_t a1, uint32_t a2, uint32_t a3, uint32_t b0, uint32_t b1) {
    asm volatile("mma.sync.aligned.m16n8k16.row.col.f32.bf16.bf16.f32 {%0, %1, %2, %3}, {%4, %5, %6, %7}, {%8, %9}, {%0, %1, %2, %3};"
                 : "+f"(d[0]), "+f"(d[1]), "+f"(d[2]), "+f"(d[3])
                 : "r"(a0), "r"(a1), "r"(a2), "r"(a3), "r"(b0), "r"(b1));
}
__device__ __forceinline__ uint4 lds128(uint32_t addr) {
    uint4 v;
    asm volatile("ld.volatile.shared.v4.u32 {%0, %1, %2, %3}, [%4];" : "=r"(v.x), "=r"(v.y), "=r"(v.z), "=r"(v.w) : "r"(addr) : "memory");
    return v;
}
__device__ __forceinline__ uint32_t lds_volatile(uint32_t addr) {
    uint32_t v;
    asm volatile("ld.volatile.shared.u32 %0, [%1];" : "=r"(v) : "r"(addr) : "memory");
    return v;
}

__device__ __forceinline__ int window_start(int n) { return min(max(n, 0), 105); }
__device__ __forceinline__ int origin_u(int u) { return min(max(u, 0), 98); }

struct Work {
    int u, v;
    int step;
    uint32_t su, sv;
    uint32_t base;
    bool corner;
    int ntiles;
    __device__ __forceinline__ void pixel_offsets(int qu, int qv, int j, uint32_t& o0, uint32_t& o1) const {
        const uint32_t b = (qu + window_start(qu)) * su + j * 16 + base;
        o0 = b + (qv + window_start(qv)) * sv;
        o1 = b + (qv + 1 + window_start(qv + 1)) * sv;
    }
};

__device__ __forceinline__ Work decode_work(int c) {
    Work w;
    const bool transposed = (c >> 4) == 7;
    const int px = 6 * (c & 1), py = 3 * (c & 2);
    w.corner = c >= 128;
    w.step = 8 - 4 * (c & 4);
    w.u = (c < 112 ? c & ~7 : 96 + (c & 8)) + (transposed ? py : px) - 6;
    w.v = (w.corner ? 96 : 48 - 2 * (c & 4)) + (transposed ? px : py) - 6;
    w.su = transposed ? kHW * kPixBytes : kPixBytes;
    w.sv = transposed ? kPixBytes : kHW * kPixBytes;
    w.base = px * (kPixBytes / 6) + py * (kHW * kPixBytes / 6) + 6 * (kHW + 1) * kPixBytes;
    w.ntiles = w.corner ? 4 : 6;
    return w;
}

struct RawX { uint4 a[6], b[6]; };
__device__ __forceinline__ void load_raw(RawX& r, const uint8_t* base, uint32_t o0, uint32_t o1) {
    __syncwarp();
#pragma unroll
    for (int c = 0; c < 6; c++) { r.a[c] = ldg(base + o0 + c * 64); r.b[c] = ldg(base + o1 + c * 64); }
    __syncwarp();
}
__device__ __forceinline__ void raw_to_frags(const RawX& r, uint32_t zero, uint32_t (&f)[48]) {
#pragma unroll
    for (int c = 0; c < 6; c++) {
        asm volatile("{\n.reg .b32 t, u;\nadd.u32 t, %4, %8;\nadd.u32 u, %5, %8;\nxor.b32 %0, %6, %8;\nxor.b32 %1, %7, %8;\n"
                     "xor.b32 %2, t, %8;\nxor.b32 %3, u, %8;\n}\n"
                     : "=&r"(f[8 * c + 1]), "=&r"(f[8 * c + 3]), "=&r"(f[8 * c + 4]), "=&r"(f[8 * c + 6])
                     : "r"(r.a[c].y), "r"(r.a[c].w), "r"(r.b[c].x), "r"(r.b[c].z), "r"(zero));
        f[8 * c + 0] = r.a[c].x; f[8 * c + 2] = r.a[c].z; f[8 * c + 5] = r.b[c].y; f[8 * c + 7] = r.b[c].w;
    }
}
__device__ __forceinline__ void acc_to_frags(const float (&d)[96], uint32_t (&f)[48]) {
#pragma unroll
    for (int i = 0; i < 48; i++) f[i] = pack_bf16(d[2 * i], d[2 * i + 1]);
}

template <class F>
__device__ __forceinline__ void proj_gemm(float (&d)[96], const uint32_t (&a)[48], uint64_t dsc, uint32_t img, F after) {
#pragma unroll
    for (int s = 0; s < 12; s++) {
        if (s == 0) wgmma_n192<true>(d, a[4 * s], a[4 * s + 1], a[4 * s + 2], a[4 * s + 3], desc_at(dsc, img - s_ring + (s >> 2) * kWChunk + (s & 3) * 32));
        else wgmma_n192<false>(d, a[4 * s], a[4 * s + 1], a[4 * s + 2], a[4 * s + 3], desc_at(dsc, img - s_ring + (s >> 2) * kWChunk + (s & 3) * 32));
        if (s == 11) wg_commit();
        after(s);
    }
}
__device__ __forceinline__ void pack_out(const float (&acc)[96], uint32_t (&po)[48]) {
#pragma unroll
    for (int g = 0; g < 6; g++)
#pragma unroll
        for (int q = 0; q < 4; q++) {
            po[8 * g + q] = pack_bf16(acc[16 * g + 4 * q], acc[16 * g + 4 * q + 1]);
            po[8 * g + 4 + q] = pack_bf16(acc[16 * g + 4 * q + 2], acc[16 * g + 4 * q + 3]);
        }
}
template <bool PINNED = true>
__device__ __forceinline__ void store_one(bool on, uint8_t* p0, uint8_t* p1, const uint32_t (&po)[48], int n) {
    if (PINNED) __syncwarp();
    asm volatile("{\n.reg .pred p;\nsetp.ne.u32 p, %5, 0;\n@p st.global.v4.u32 [%0], {%1, %2, %3, %4};\n}\n"
                 ::"l"(((n & 1) ? p1 : p0) + (n >> 1) * 64), "r"(po[4 * n]), "r"(po[4 * n + 1]), "r"(po[4 * n + 2]), "r"(po[4 * n + 3]), "r"((uint32_t)on) : "memory");
}

template <int N>
__device__ __forceinline__ float tree_max(const float (&v)[N]) {
    float t[N];
#pragma unroll
    for (int i = 0; i < N; i++) t[i] = v[i];
#pragma unroll
    for (int w = 1; w < N; w *= 2)
#pragma unroll
        for (int i = 0; i + w < N; i += 2 * w) t[i] = fmaxf(t[i], t[i + w]);
    return t[0];
}
template <int N>
__device__ __forceinline__ float tree_sum(const float (&v)[N]) {
    float t[N];
#pragma unroll
    for (int i = 0; i < N; i++) t[i] = v[i];
#pragma unroll
    for (int w = 1; w < N; w *= 2)
#pragma unroll
        for (int i = 0; i + w < N; i += 2 * w) t[i] += t[i + w];
    return t[0];
}

template <int B>
__device__ __forceinline__ void pick(uint32_t h, uint32_t ok, const float* s, float& v0, float& v1) {
    asm("{\n.reg .pred p, q0, q1;\n.reg .b32 t;\nand.b32 t, %6, %7;\nsetp.ne.u32 p, t, 0;\n"
        "and.b32 t, %8, %9;\nsetp.ne.u32 q0, t, 0;\nand.b32 t, %8, %10;\nsetp.ne.u32 q1, t, 0;\n"
        "@q0 selp.f32 %0, %3, %2, p;\n@q1 selp.f32 %1, %5, %4, p;\n}\n"
        : "+f"(v0), "+f"(v1)
        : "f"(s[0]), "f"(s[1]), "f"(s[2]), "f"(s[3]), "r"(h), "n"(1 << ((4 * B) % 7)), "r"(ok), "n"(1 << (2 * B)), "n"(2 << (2 * B)));
}
template <int B, class F>
__device__ __forceinline__ void for_blocks(F f) {
    if constexpr (B > 0) { for_blocks<B - 1>(f); f(std::integral_constant<int, B - 1>{}); }
}
__device__ __forceinline__ void gather_outer(const float (&s)[44], uint32_t h, uint32_t ok, float (&v0)[14], float (&v1)[14]) {
    for_blocks<11>([&](auto B) {
        constexpr int b = B.value < 8 ? (B.value >> 1) + 7 * (B.value & 1) : B.value - 4;
        pick<b>(h, ok, &s[4 * b], v0[b], v1[b]);
    });
}
__device__ __forceinline__ void gather_mid(const float (&sE)[16], uint32_t h, uint32_t ok, float (&v0)[14], float (&v1)[14]) {
    for_blocks<4>([&](auto B) { pick<10 + B.value>(h, ok, &sE[4 * B.value], v0[10 + B.value], v1[10 + B.value]); });
}
__device__ __forceinline__ float quad_max(float m) {
    m = fmaxf(m, __shfl_xor_sync(0xffffffffu, m, 1));
    return fmaxf(m, __shfl_xor_sync(0xffffffffu, m, 2));
}
__device__ __forceinline__ float quad_sum(float s) {
    s += __shfl_xor_sync(0xffffffffu, s, 1);
    return s + __shfl_xor_sync(0xffffffffu, s, 2);
}
template <int B0, int B1>
__device__ __forceinline__ void exp_route(float (&v0)[14], float (&v1)[14], float m0, float m1, const uint4& r, bool even, uint32_t (&y)[14]) {
#pragma unroll
    for (int b = B0; b < B1; b++) { v0[b] = ex2(v0[b] - m0); v1[b] = ex2(v1[b] - m1); }
#pragma unroll
    for (int b = B0; b < B1; b += 2) {
        const uint32_t x0 = pack_bf16(v0[b], v1[b]), x1 = pack_bf16(v0[b + 1], v1[b + 1]);
        const uint32_t u = __shfl_sync(0xffffffffu, even ? x0 : x1, r.x);
        const uint32_t w = __shfl_sync(0xffffffffu, even ? x1 : x0, r.y);
        y[b] = __byte_perm(u, w, r.z); y[b + 1] = __byte_perm(u, w, r.w);
    }
}
template <int BIT0, int N0, int N1>
__device__ __forceinline__ void unfold(const uint32_t (&y)[14], uint32_t fold, uint32_t (&p)[12]) {
    for_blocks<N1 - N0>([&](auto N) {
        constexpr int n = N0 + N.value;
        asm("{\n.reg .pred p;\n.reg .b32 t;\nand.b32 t, %4, %5;\nsetp.ne.u32 p, t, 0;\nselp.b32 %0, %2, 0, p;\nselp.b32 %1, %3, 0, p;\n}\n"
            : "=r"(p[2 * n]), "=r"(p[2 * n + 1]) : "r"(y[2 * n]), "r"(y[2 * n + 1]), "r"(fold), "n"(1 << (BIT0 + n)));
    });
}
__device__ __forceinline__ void keep(bool never, uint32_t a, uint32_t b, uint32_t c, uint32_t d) {
    asm volatile("{\n.reg .pred p;\nsetp.ne.u32 p, %4, 0;\n@p st.volatile.shared.v4.u32 [%5], {%0, %1, %2, %3};\n}\n"
                 ::"r"(a), "r"(b), "r"(c), "r"(d), "r"((uint32_t)never), "r"(s_trace) : "memory");
}

__device__ __forceinline__ uint32_t wimg_offset(uint32_t row, uint32_t s, uint32_t j) {
    return (s >> 2) * kWChunk + row * 128 + (((2 * (s & 3) + (j >> 1)) ^ (row & 7)) << 4) + (j & 1) * 8;
}

__device__ __forceinline__ void ldsm4(uint32_t (&r)[4], uint32_t addr) {
    asm volatile("ldmatrix.sync.aligned.m8n8.x4.shared.b16 {%0, %1, %2, %3}, [%4];" : "=r"(r[0]), "=r"(r[1]), "=r"(r[2]), "=r"(r[3]) : "r"(addr) : "memory");
}
__device__ __forceinline__ void ldsm4_t(uint32_t (&r)[4], uint32_t addr) {
    asm volatile("ldmatrix.sync.aligned.m8n8.x4.trans.shared.b16 {%0, %1, %2, %3}, [%4];" : "=r"(r[0]), "=r"(r[1]), "=r"(r[2]), "=r"(r[3]) : "r"(addr) : "memory");
}
struct MOperands { uint4 A[2][2], B[4][2]; };
__device__ __forceinline__ void m_load(MOperands& m, const uint8_t* wqkv, uint32_t mt, uint32_t s, uint32_t q, uint32_t lane) {
    const uint32_t r8 = lane >> 2, col = q * 128 + (lane & 3) * 16;
    const uint8_t* pa = wqkv + (16 * mt + r8) * 1152 + col;
    const uint8_t* pb = wqkv + (16 * s + 8 * (r8 & 2) + (r8 & 5)) * 1152 + col;
#pragma unroll
    for (int c = 0; c < 2; c++) {
#pragma unroll
        for (int h = 0; h < 2; h++) m.A[h][c] = ldg(pa + 384 + h * 8 * 1152 + c * 64);
#pragma unroll
        for (int n = 0; n < 4; n++) m.B[n][c] = ldg(pb + ((n & 1) * 8 + (n & 2)) * 1152 + c * 64);
    }
}
__device__ __forceinline__ void m_partial(MOperands& m, uint32_t q, uint32_t lane, uint32_t zero) {
    auto& A = m.A;
    auto& B = m.B;
#pragma unroll
    for (int i = 0; i < 4; i++) { uint4& a = A[i >> 1][i & 1]; a.x ^= zero; a.y ^= zero; a.z ^= zero; a.w ^= zero; }
#pragma unroll
    for (int n = 0; n < 4; n++) {
        float d[4] = {0.f, 0.f, 0.f, 0.f};
#pragma unroll
        for (int c = 0; c < 2; c++) {
            mma16816(d, A[0][c].x, A[1][c].x, A[0][c].y, A[1][c].y, B[n][c].x, B[n][c].y);
            mma16816(d, A[0][c].z, A[1][c].z, A[0][c].w, A[1][c].w, B[n][c].z, B[n][c].w);
        }
        asm volatile("st.shared.v4.f32 [%0], {%1, %2, %3, %4};" ::"r"(s_wv + q * 2048 + n * 512 + lane * 16), "f"(d[0]), "f"(d[1]), "f"(d[2]), "f"(d[3]) : "memory");
    }
}
__device__ __forceinline__ void m_reduce(uint32_t e, uint32_t lane, float (&d)[2][4]) {
#pragma unroll
    for (int n = 0; n < 2; n++) {
        float t[3][4];
#pragma unroll
        for (int q = 0; q < 3; q++)
            asm volatile("ld.shared.v4.f32 {%0, %1, %2, %3}, [%4];" : "=f"(t[q][0]), "=f"(t[q][1]), "=f"(t[q][2]), "=f"(t[q][3]) : "r"(s_wv + q * 2048 + e * 1024 + n * 512 + lane * 16) : "memory");
#pragma unroll
        for (int i = 0; i < 4; i++) d[n][i] = (t[0][i] + t[1][i] + t[2][i]) * kScaleLog2e;
    }
}
__device__ __forceinline__ void w_piece(uint32_t q, uint32_t lane, float (&d)[2][4]) {
    const uint32_t rr = lane & 7, mi = lane >> 3, kr = 4 * (rr >> 1) + (mi & 2) + (rr & 1);
    const uint32_t pa = s_wv + q * 32 + (4 * (mi & 2) + rr) * 96 + ((mi & 1) << 4);
    const uint32_t pb = s_wv + 3 * 6144 + kr * 128 + (((mi & 1) ^ (kr & 7)) << 4);
    float e[2][4];
#pragma unroll
    for (int i = 0; i < 8; i++) (&d[0][0])[i] = (&e[0][0])[i] = 0.f;
#pragma unroll
    for (int k = 0; k < 12; k++) {
        uint32_t aq[4], bq[4];
        ldsm4_t(aq, pa + k * 1536);
        ldsm4(bq, (pb ^ ((k & 3) << 5)) + (k >> 2) * 2048);
        mma16816(k & 1 ? e[0] : d[0], aq[0], aq[1], aq[2], aq[3], bq[0], bq[1]);
        mma16816(k & 1 ? e[1] : d[1], aq[0], aq[1], aq[2], aq[3], bq[2], bq[3]);
    }
#pragma unroll
    for (int i = 0; i < 8; i++) (&d[0][0])[i] += (&e[0][0])[i];
}
__device__ __forceinline__ uint32_t piece_offset(uint32_t which, uint32_t s, uint32_t mt, uint32_t lane) {
    const uint32_t r8 = lane >> 2;
    return which * kWBytes + wimg_offset(which ? 32 * (mt >> 1) + 8 * (r8 >> 1) + 4 * (mt & 1) + (r8 & 1) : 16 * mt + r8, s, lane & 3);
}
__device__ __forceinline__ void piece_store(Scratch* g, uint32_t par, uint32_t off0, uint32_t which, const float (&d)[2][4]) {
#pragma unroll
    for (int hf = 0; hf < 2; hf++) {
        const uint32_t off = off0 ^ (hf ? which ? 288 : 1024 : 0);
        const uint32_t a = pack_bf16(d[0][2 * hf], d[0][2 * hf + 1]), b = pack_bf16(d[1][2 * hf], d[1][2 * hf + 1]);
        asm volatile("st.relaxed.gpu.global.v2.u32 [%0], {%1, %2};" ::"l"(g->img[0][0] + (par + off)), "r"(a ? a : 0x8000u), "r"(b) : "memory");
    }
}
__device__ __forceinline__ void piece_clear(Scratch* g, uint32_t par, uint32_t off0, uint32_t which) {
#pragma unroll
    for (int hf = 0; hf < 2; hf++)
        asm volatile("st.relaxed.gpu.global.v2.u32 [%0], {%1, %1};" ::"l"(g->img[0][0] + (par + (off0 ^ (hf ? which ? 288 : 1024 : 0)))), "r"(0) : "memory");
}

__device__ __forceinline__ uint32_t ld_relaxed(const uint32_t* p) {
    uint32_t v;
    asm volatile("ld.relaxed.gpu.global.u32 %0, [%1];" : "=r"(v) : "l"(p) : "memory");
    return v;
}
__device__ __forceinline__ void count_up(uint32_t* p) {
    asm volatile("red.relaxed.gpu.global.add.u32 [%0], %1;" ::"l"(p), "r"(1) : "memory");
}
__device__ __forceinline__ void bulk_g2s(uint32_t dst, const void* src, uint32_t bytes, uint32_t bar) {
    asm volatile("cp.async.bulk.shared::cluster.global.mbarrier::complete_tx::bytes [%0], [%1], %2, [%3];"
                 ::"r"(dst), "l"(src), "r"(bytes), "r"(bar)
                 : "memory");
}

__global__ void __launch_bounds__(kThreads, 1)
nat_fused_kernel(const uint8_t* __restrict__ x, const uint8_t* __restrict__ wqkv, uint8_t* __restrict__ out, Scratch* g,
                 const uint8_t* wo, uint64_t dsc, const __grid_constant__ Maps maps) {
    const int tid = threadIdx.x, lane = tid & 31;
    const int warp = __shfl_sync(0xffffffffu, tid >> 5, 0);
    const int wg = warp >> 2, wq = warp & 3, r8 = lane >> 2, j = lane & 3;
    const int cta = blockIdx.x;
    const Work w = decode_work(cta);
    const uint32_t jq = (cta < 124 ? cta + 8 : cta - 124) / 11u, jr = (cta < 124 ? cta + 8 : cta - 124) - 11 * jq;
    const uint32_t which = jr >= 6, jhi = which ? jr - 6 : jq, jlo = which ? jq : 2 * jr;
    const bool has_job = jr < 10;
    if (wg == 2 && wq < 3) {
#pragma unroll
        for (int r = 0; r < 3; r++)
            asm volatile("st.shared.v4.u32 [%0], {%1, %1, %1, %1};" ::"r"(s_ring + wq * kRingChunk + (r == 0 ? 84 : r == 1 ? 88 : 204) * 128 + lane * 16), "r"(0) : "memory");
        asm volatile("fence.proxy.async.shared::cta;" ::: "memory");
    }
    MOperands mo;
    uint32_t launch = 0;
    if (wg == 1 && wq < 3 && !which) m_load(mo, wqkv, jhi, jlo, wq, lane);
    if (warp == 7) launch = ld_relaxed(g->launches[cta]);
    if (x == nullptr) return;
    const uint32_t t_start = clock_now();
    if (wg == 2) {
        asm volatile("setmaxnreg.dec.sync.aligned.u32 24;");
        if (wq < 3) {
            if (lane < 3 && cta < 128) {
                const uint32_t row = 3 * (cta >> 1) + wq;
                asm volatile("prefetch.global.L2 [%0];" ::"l"((cta & 1 ? wo + row * 384 : wqkv + row * 1152 + 768) + lane * 128));
            }
            asm volatile("bar.sync 7, 192;" ::: "memory");
            const uint32_t par = lds_volatile(s_par);
            uint32_t phase = 0;
#pragma unroll 1
            for (uint32_t c = 0; c < 6; c++) {
                const uint32_t part = c * kWChunk + wq * (kWChunk / 3), img = 8 * min(c, 3u);
                mbar_wait(bar_img + 8 * c, 0);
                if (c == 0 && lane == 0) mbar_arrive(bar_ok);
                if (wq == 0) TRW(10 + c);
#pragma unroll 1
                while (true) {
                    uint32_t lo = ~0u;
#pragma unroll
                    for (int q = 0; q < 8; q++) lo = min(lo, lds_volatile(s_m + part + lane * 32 + (lane & 12) * 2 + q * 1024));
                    if (__all_sync(0xffffffffu, lo) || phase > 65535) break;
                    if (elect()) {
                        mbar_expect_tx(bar_redo + 8 * wq, kWChunk / 3);
                        bulk_g2s(s_m + part, g->img[0][0] + par + part, kWChunk / 3, bar_redo + 8 * wq);
                    }
                    mbar_wait(bar_redo + 8 * wq, phase++ & 1);
                }
                if (c == 2 && phase) asm volatile("st.shared.u32 [%0], %1;" ::"r"(s_again), "r"(1) : "memory");
                if ((c == 2 || c == 5) && lane == 0) mbar_arrive(bar_ok + img);
            }
            if (wq == 0 && !w.corner) {
#pragma unroll 1
                for (int n = PFROM; n < 48; n++) {
                    uint32_t o0, o1;
                    w.pixel_offsets(w.u + r8, w.step < 0 ? w.v + 7 - n : w.v + n, 8 * j, o0, o1);
                    if (j < 3) asm volatile("prefetch.global.L2 [%0];" ::"l"(x + o0));
                    __nanosleep(PNAP);
                }
            }
        } else {
            const CUtensorMap* map = &maps.m[w.sv == kPixBytes ? 2 : 0];
            if (elect()) {
#pragma unroll
                for (int i = 0; i < 23; i++) mbar_init(s_bar + 8 * i, i < 13 ? 1 : i < 18 ? 3 : 4);
                asm volatile("fence.mbarrier_init.release.cluster;" ::: "memory");
                prefetch_map(map + 1);
                expect_tx_only(bar_a, sizeof(Table));
                bulk_g2s(s_tab, &maps.tables->t[w.step < 0], sizeof(Table), bar_a);
            }
            if (which && has_job && elect()) {
                mbar_expect_tx(bar_wop, 4 * 6144);
                tma_3d(s_wv, &maps.wo, bar_wop, 0, jhi);
                tma_3d(s_wv + 3 * 6144, &maps.wv, bar_wop, 16 * jlo, 6);
            }
            int u = w.u, v = w.v;
            uint32_t wait_bar = bar_use, wait_par = 1, slot = 0;
#pragma unroll 1
            for (int step = 0; step < 7 - w.corner; step++) {
                const bool first = step == 0 || (w.corner && step == 4);
                const int row = v + 4 + (first ? -w.step : w.step) / 2, ou = origin_u(u);
                const bool final = step == 6 - w.corner;
                uint32_t dst = final ? s_m : s_ring + (first ? 0 : slot), mid = (final ? s_m : s_ring) + kOffMid + 512, bar = first ? bar_a : bar_b;
                if (final) { wait_bar = bar_free; wait_par = 0; }
#pragma unroll 1
                for (int ch = (cta & 1) * kC, n = 0; n < 3; n++, ch += 64, dst += kRingChunk, mid += kRingChunk) {
                    mbar_wait(wait_bar, wait_par);
                    if (n == 0) TRW(24 + step);
                    if (final) wait_bar += 8;
                    if (elect()) {
                        mbar_expect_tx(bar, first ? kSlotBytes : kSlotBytes + kMidBytes);
                        tma_box(dst, map, bar, ch, ou, (cta >> 1) & 1, row);
                    }
                    if (!first) {
                        if (elect()) tma_box(mid, map + 1, bar, ch, ou, (cta >> 1) & 1, v + 6);
                        bar += 8;
                    }
                }
                if (step == 0) {
                    asm volatile("st.shared.v2.u32 [%0], {%1, %1};" ::"r"(s_late), "r"(0) : "memory");
                    asm volatile("bar.arrive 3, 160;\nbar.arrive 4, 160;\nbar.arrive 8, 128;\nbar.sync 9, 64;" ::: "memory");
                }
                if (step < 2) {
                    if (step) {
                        asm volatile("bar.sync 6, 128;" ::: "memory");
                    }
                    const uint32_t par = __shfl_sync(0xffffffffu, lds_volatile(s_par), 0);
                    wait_until(t_start, step ? TN(5, kTimeW) : TN(6, kTimeM));
                    TRW(5 + 4 * step);
#pragma unroll 1
                    for (int c = 3 * step; c < 3 + 3 * step; c++)
                        if (elect()) {
                            mbar_expect_tx(bar_img + 8 * c, kWChunk);
                            bulk_g2s(s_m + c * kWChunk, g->img[0][0] + (par + c * kWChunk), kWChunk, bar_img + 8 * c);
                        }
                }
                const bool again = w.corner && step == 3;
                wait_bar = step == 0 ? bar_img + 8 * TN(1, 1) : again ? bar_use + 8 : bar_use;
                if (!again) {
                    wait_par = slot ? 0 : step != 0;
                    slot ^= kSlotStride;
                    if (w.corner && step == 2) { u += 8; v -= 8; } else if (step) v += w.step;
                }
            }
        }
        TRDUMP();
        return;
    }
    if (warp == 7) {
        asm volatile("st.shared.u32 [%0], %1;\nbar.arrive 9, 64;" ::"r"(s_par), "r"((launch & 1) * 2 * kWBytes) : "memory");
        g->launches[cta][lane] = launch + 1;
        asm volatile("bar.arrive 5, 128;" ::: "memory");
    }
    if (wg == 1 && wq < 3) {
        if (!which) m_partial(mo, wq, lane, (uint32_t)dsc & 1);
        const uint32_t off = piece_offset(which, which ? jlo : jlo + wq, which ? 3 * jhi + wq : jhi, lane);
        asm volatile("bar.sync %0, %1;" ::"r"(5 + (off >> 31)), "n"(128) : "memory");
        const uint32_t par = lds_volatile(s_par);
        if (which) asm volatile("bar.sync 8, 128;" ::: "memory");
        if (has_job && wq < 2 + which) {
            float d[2][4];
            if (wq == 0) TRX(which ? 1 : 18);
            if (which) {
                mbar_wait(bar_wop, 0);
                if (wq == 0) TRX(2);
                w_piece(wq, lane, d);
            } else {
                m_reduce(wq, lane, d);
            }
            piece_store(g, par, off, which, d);
            __syncwarp();
            piece_clear(g, 2 * kWBytes - par, off, which);
            if (wq == 0) TRX(which ? 3 : 0);
        }
        if (!which) asm volatile("bar.sync 8, 128;" ::: "memory");
        asm volatile("bar.arrive 7, 192;\nbar.arrive 6, 128;" ::: "memory");
    }
    const int order = w.step < 0 ? warp ^ 3 : warp;
    int tu = w.u, tv = w.v + w.step * wg;
    const int du2 = w.corner ? 8 : 0, dv2 = w.corner ? 0 : 2 * w.step;
    uint32_t o0, o1;
    wait_until(t_start, START_TIME);
    asm volatile("setmaxnreg.inc.sync.aligned.u32 240;");
    w.pixel_offsets(tu + r8, tv + 2 * wq, j, o0, o1);
    uint32_t fa[48];
    {
        RawX raw;
        load_raw(raw, x, o0, o1);
        asm volatile("bar.sync %0, 160;" ::"r"(3 + wg) : "memory");
        raw_to_frags(raw, 0, fa);
        pin(fa);
    }
    mbar_wait(bar_ok, 0);
    const uint64_t dA = dsc + wg * (kSlotStride >> 4), dB = dsc + (wg ^ 1) * (kSlotStride >> 4);

    float acc[96];
    uint32_t po[48];
    uint32_t c0, c1;
    asm volatile("" : "=r"(c0), "=r"(c1));
#pragma unroll
    for (int q = 0; q < 48; q++) asm volatile("" : "=r"(po[q]));
#pragma unroll 1
    for (int i = wg; i < w.ntiles; i += 2) {
        const bool first = i == 0, last = i == w.ntiles - 1;

        TRF(8 + 16 * k);
        uint8_t *p0 = out + c0, *p1 = out + c1;
#pragma unroll 1
        for (uint32_t seen = 0;;) {
        wg_fence();
        if (!first) turn_wait(wg);
        proj_gemm(acc, fa, dsc, s_m, [&](int s) {
            if (s == 11 && !first) turn_pass(wg);
            const int n = __builtin_popcount(QSLOTS & ((1 << s) - 1));
            if (((QSLOTS >> s) & 1) && n < 12) store_one(i >= 2, out + c0, out + c1, po, n);
            if (s == 3 || s == 7) { wg_commit(); mbar_wait(bar_img + 2 * s + 2, 0); wg_fence(); }
        });
        __syncwarp();
        TRF(9 + 16 * k);
            if (!first) break;
            mbar_wait(bar_ok + 16, 0);
            if (lds_volatile(s_again) == seen) break;
            wg_wait<0>();
            seen = 1;
        }
        c0 = o0; c1 = o1;
        w.pixel_offsets(tu + du2 + r8, tv + dv2 + 2 * wq, j, o0, o1);
        if (i + 2 >= w.ntiles) o0 = o1 = 0;
        mbar_wait(bar_a, w.corner ? i >> 1 : 0);
        wg_wait<2>();
        if (last && lane == 0) mbar_arrive(bar_free);
        wg_wait<1>();
        if (last && lane == 0) mbar_arrive(bar_free + 8);
        wg_wait<0>();
        if (last && lane == 0) mbar_arrive(bar_free + 16);
        const uint64_t dE = last ? dsc + ((s_m - s_ring) >> 4) : dsc, dN = last ? dE : dB;
        pin(acc);
        TR(11 + 16 * k);
        TRT(80 + k);
#pragma unroll
        for (int n = __builtin_popcount(QSLOTS); n < 12 - __builtin_popcount(ASLOTS) - __builtin_popcount(BSLOTS); n++) store_one(i >= 2, p0, p1, po, n);
        acc_to_frags(acc, fa);
        pin(fa);

        float sA[44], sE[16], sB[44];
        RawX nxt;
        if (!first) turn_wait(wg);
        wg_fence();
#pragma unroll
        for (int s = 0; s < 12; s++) {
            if (s == 0) wgmma_n88<true>(sA, fa[4 * s], fa[4 * s + 1], fa[4 * s + 2], fa[4 * s + 3], desc_at(dA, (s >> 2) * kRingChunk + (s & 3) * 32));
            else wgmma_n88<false>(sA, fa[4 * s], fa[4 * s + 1], fa[4 * s + 2], fa[4 * s + 3], desc_at(dA, (s >> 2) * kRingChunk + (s & 3) * 32));
            if (s == 11) { wg_commit(); if (!first) turn_pass(wg); }
            if ((ASLOTS >> s) & 1) store_one(i >= 2, p0, p1, po, 12 - __builtin_popcount(BSLOTS) - __builtin_popcount(ASLOTS >> s));
        }
#pragma unroll
        for (int s = 12; s < 16; s++)
            if ((ASLOTS >> s) & 1) store_one(i >= 2, p0, p1, po, 12 - __builtin_popcount(BSLOTS) - __builtin_popcount(ASLOTS >> s));
        TRF(12 + 16 * k);
        const int vq = tv + 2 * wq;
        const uint4 tabu = lds128(s_tab + offsetof(Table, u) + (window_start(tu + r8) - origin_u(tu)) * 64 + j * 16);
        const uint4 tabv = lds128(s_tab + offsetof(Table, v) + (window_start(vq) + window_start(vq + 1) - 2 * tv) * 64 + j * 16);
        const uint4 route = lds128(s_tab + lane * 16);
        load_raw(nxt, x, o0, o1);
        float v0[14], v1[14];
#pragma unroll
        for (int b = 0; b < 14; b++) {
            v0[b] = __uint_as_float((b > 10 ? route.x >> (b + 2) : 0u) | 0xff800000u);
            v1[b] = __uint_as_float((b > 10 ? route.x >> (b + 5) : 0u) | 0xff800000u);
        }
        wg_wait<0>();
        pin(sA);
        gather_outer(sA, tabu.x, tabv.x, v0, v1);
        pin(v0); pin(v1);
        if (!first) turn_wait(wg);
#pragma unroll
        for (int c = 0; c < 3; c++) {
            mbar_wait(bar_b + 8 * c, wg);
            TRF(64 + 4 * k + c);
            wg_fence();
#pragma unroll
            for (int s = 4 * c; s < 4 * c + 4; s++) {
                if (s == 0) wgmma_n88<true>(sB, fa[4 * s], fa[4 * s + 1], fa[4 * s + 2], fa[4 * s + 3], desc_at(dN, c * kRingChunk + (s & 3) * 32));
                else wgmma_n88<false>(sB, fa[4 * s], fa[4 * s + 1], fa[4 * s + 2], fa[4 * s + 3], desc_at(dN, c * kRingChunk + (s & 3) * 32));
                if ((BSLOTS >> s) & 1) store_one(i >= 2, p0, p1, po, 12 - __builtin_popcount(BSLOTS >> s));
            }
        }
        wg_commit();
#pragma unroll
        for (int s = 0; s < 12; s++)
            if (s == 0) wgmma_n32<true>(sE, fa[4 * s], fa[4 * s + 1], fa[4 * s + 2], fa[4 * s + 3], desc_at(dE, kOffMid + (s >> 2) * kRingChunk + (s & 3) * 32));
            else wgmma_n32<false>(sE, fa[4 * s], fa[4 * s + 1], fa[4 * s + 2], fa[4 * s + 3], desc_at(dE, kOffMid + (s >> 2) * kRingChunk + (s & 3) * 32));
        wg_commit();
        turn_pass(wg);
        TRF(13 + 16 * k);
        wg_wait<1>();
        pin(sB);
        gather_outer(sB, tabu.w, tabv.y, v0, v1);
        wg_wait<0>();
        pin(sE);
        TRF(14 + 16 * k);
        gather_mid(sE, tabu.w, tabv.z, v0, v1);
        const float m0 = quad_max(tree_max(v0)), m1 = quad_max(tree_max(v1));

        uint32_t y[14], pa[12], pb[12];
        exp_route<0, 14>(v0, v1, m0, m1, route, (j & 1) == 0, y);
        float s0 = tree_sum(v0), s1 = tree_sum(v1);
        asm volatile("" : "+f"(s0), "+f"(s1));
        unfold<0, 0, 6>(y, tabv.w, pa);
        turn_wait(wg + (y[0] >> 31));
        TRF(15 + 16 * k + (y[13] >> 31));
        wg_fence();
        wgmma_sp_n192_tb<true, 0>(acc, pa[0], pa[1], pa[2], pa[3], desc_at(dA, kToV), tabu.y);
        wgmma_sp_n192_tb<false, 1>(acc, pa[4], pa[5], pa[6], pa[7], desc_at(dA, kToV + 4096), tabu.y);
        wgmma_sp_n192_tb<false, 0>(acc, pa[8], pa[9], pa[10], pa[11], desc_at(dA, kToV + 8192), tabu.z);
        wgmma_sp_n192_tb<false, 1>(acc, j == 0 ? 0u : y[10], j == 0 ? 0u : y[11], y[12], y[13], desc_at(dE, kToV + kOffMid), tabu.z);
        wg_commit();
        unfold<8, 0, 6>(y, tabv.w, pb);
        wg_fence();
        wgmma_sp_n192_tb<false, 0>(acc, pb[0], pb[1], pb[2], pb[3], desc_at(dN, kToV), tabu.y);
        wgmma_sp_n192_tb<false, 1>(acc, pb[4], pb[5], pb[6], pb[7], desc_at(dN, kToV + 4096), tabu.y);
        wgmma_sp_n192_tb<false, 0>(acc, pb[8], pb[9], pb[10], pb[11], desc_at(dN, kToV + 8192), tabu.z);
        wg_commit();
        if (!last) turn_pass(wg);
        TRF(16 + 16 * k);
        wg_wait<1>();
        if (lane == 0) mbar_arrive(bar_use);
        TRF(17 + 16 * k);
        mbar_wait(bar_ok + 24, 0);
        wg_wait<0>();
        if (lane == 0) mbar_arrive(bar_use + 8);
        pin(acc);
        TR(18 + 16 * k);

        acc_to_frags(acc, po);
        pin(po);
        if (!last) turn_wait(wg);
        wg_fence();
        proj_gemm(acc, po, dsc, s_wv, [&](int s) {
            if (s + 1 == OSPLIT && i + 2 == w.ntiles) { turn_pass(wg); turn_wait(wg); }
        });
        if (!last) turn_pass(wg);
        TRF(19 + 16 * k);
        const uint32_t zero = lds_volatile(s_late);
        const float inv0 = rcp(quad_sum(s0 + __uint_as_float(zero))), inv1 = rcp(quad_sum(s1 + __uint_as_float(zero)));
        raw_to_frags(nxt, zero, fa);
        pin(fa);
#pragma unroll
        for (int q = 0; q < 48; q += 4) keep(wqkv == nullptr, fa[q], fa[q + 1], fa[q + 2], fa[q + 3]);
        keep(wqkv == nullptr, __float_as_uint(inv0), __float_as_uint(inv1), zero, lane);
        TRF(20 + 16 * k);
        tu += du2; tv += dv2;
        wg_wait<0>();
        pin(acc);
        TR(21 + 16 * k);
#pragma unroll
        for (int q = 0; q < 96; q++) acc[q] *= q & 2 ? inv1 : inv0;
        pack_out(acc, po);
#pragma unroll
        for (int n = 0; n < INLOOP; n++) store_one<false>(last, out + c0, out + c1, po, n);
        pin(po);
    }
#pragma unroll
    for (int n = 0; n < 12; n++) {
        asm volatile("{\n.reg .pred p;\nsetp.eq.u32 p, %0, 0;\n@p nanosleep.u32 %1;\n}\n" ::"r"(wg), "n"(NAP) : "memory");
        store_one<false>(n >= INLOOP || wg == 0, out + c0, out + c1, po, n);
    }
    TRE(7);
    TRG(1);
    TRDUMP();
}

typedef CUresult (*EncodeTiledFn)(CUtensorMap*, CUtensorMapDataType, cuuint32_t, void*, const cuuint64_t*, const cuuint64_t*,
                                  const cuuint32_t*, const cuuint32_t*, CUtensorMapInterleave, CUtensorMapSwizzle,
                                  CUtensorMapL2promotion, CUtensorMapFloatOOBfill);

bool make_maps(EncodeTiledFn fn, Maps* maps, void* x, void* wqkv, void* wo) {
    const cuuint64_t pix2 = 2 * kPixBytes, row = (cuuint64_t)kHW * kPixBytes;
    const cuuint32_t estr[5] = {1, 1, 1, 1, 1};
    bool ok = true;
    for (int tr = 0; tr < 2; tr++)
        for (int b = 0; b < 2; b++) {
            const cuuint64_t su = tr ? 2 * row : pix2, sv = tr ? pix2 : 2 * row;
            const cuuint64_t dims[5] = {2 * kC, 2, 105, 2, 112};
            const cuuint64_t strides[4] = {7 * su, su, row, sv};
            const cuuint32_t box[5] = {64, 2, 7, 1, b ? 2u : 6u};
            ok = ok && fn(&maps->m[2 * tr + b], CU_TENSOR_MAP_DATA_TYPE_BFLOAT16, 5, x, dims, strides, box, estr,
                          CU_TENSOR_MAP_INTERLEAVE_NONE, CU_TENSOR_MAP_SWIZZLE_128B, CU_TENSOR_MAP_L2_PROMOTION_L2_128B,
                          CU_TENSOR_MAP_FLOAT_OOB_FILL_NONE) == CUDA_SUCCESS;
        }
    for (int b = 0; b < 2; b++) {
        const cuuint64_t dims[3] = {b ? 64u : 48u, kC, b ? 9u : 4u}, strides[2] = {(b ? 3u : 1u) * kPixBytes, b ? 128u : 96u};
        const cuuint32_t box[3] = {b ? 64u : 48u, b ? 16u : 192u, b ? 3u : 1u};
        ok = ok && fn(b ? &maps->wv : &maps->wo, CU_TENSOR_MAP_DATA_TYPE_BFLOAT16, 3, b ? wqkv : wo, dims, strides, box, estr,
                      CU_TENSOR_MAP_INTERLEAVE_NONE, b ? CU_TENSOR_MAP_SWIZZLE_128B : CU_TENSOR_MAP_SWIZZLE_NONE, CU_TENSOR_MAP_L2_PROMOTION_L2_128B,
                      CU_TENSOR_MAP_FLOAT_OOB_FILL_NONE) == CUDA_SUCCESS;
    }
    return ok;
}

}

extern "C" void kernel_launch(void* const* d_in, const int* in_sizes, int n_in, void* d_out, int out_size) {
    static EncodeTiledFn encode = nullptr;
    static Scratch* scratch = nullptr;
    static Tables* tables = nullptr;
    if (!encode) {
        int dev = 0, reserved = 0;
        cudaFuncAttributes attr;
        cudaGetDevice(&dev);
        cudaDeviceGetAttribute(&reserved, cudaDevAttrReservedSharedMemoryPerBlock, dev);
        cudaFuncGetAttributes(&attr, nat_fused_kernel);
        if (reserved != (int)kSmemBase || attr.sharedSizeBytes != 0) return;
        cudaGetSymbolAddress((void**)&scratch, g_scratch);
        cudaGetSymbolAddress((void**)&tables, g_tables);
        void* fn = nullptr;
        cudaDriverEntryPointQueryResult st;
        cudaGetDriverEntryPoint("cuTensorMapEncodeTiled", &fn, cudaEnableDefault, &st);
        encode = (EncodeTiledFn)fn;
        cudaFuncSetAttribute(nat_fused_kernel, cudaFuncAttributeMaxDynamicSharedMemorySize, kSmemBytes);
    }
    Maps maps;
    maps.tables = tables;
    if (!encode || !make_maps(encode, &maps, d_in[0], d_in[1], d_in[2])) return;
    nat_fused_kernel<<<kGrid, kThreads, kSmemBytes>>>((const uint8_t*)d_in[0], (const uint8_t*)d_in[1], (uint8_t*)d_out, scratch, (const uint8_t*)d_in[2],
                                                      kDescRing, maps);
}
```

```cpp
#include <cuda_runtime.h>
#include <cuda_bf16.h>
#include <cuda.h>
#include <stdint.h>
#include <type_traits>
#include <stdlib.h>
#include <stdio.h>
#include <stddef.h>

#define ASLOTS 0x3800
#define BSLOTS 0x6
#define QSLOTS 0x78a
#define OSPLIT 2
#define NAP 40
#define INLOOP 3

namespace {

constexpr int kC          = 192;
constexpr int kHW         = 224;
constexpr int kPixBytes   = kC * 2;
constexpr int kSlotBytes  = 84 * 128;
constexpr int kMidBytes   = 28 * 128;
constexpr int kOffMid     = 88 * 128;
constexpr int kSlotStride = 120 * 128;
constexpr int kRingChunk  = 208 * 128;
constexpr int kWChunk     = 192 * 128;
constexpr int kWBytes     = 3 * kWChunk;
constexpr uint32_t kSmemBase = 1024;
constexpr uint32_t s_ring = kSmemBase, s_m = s_ring + 3 * kRingChunk, s_wv = s_m + kWBytes, s_bar = s_wv + kWBytes;
constexpr uint32_t bar_b = s_bar, bar_img = s_bar + 24, bar_redo = s_bar + 72, bar_wop = s_bar + 96, bar_a = s_bar + 104,
                   bar_ok = s_bar + 112, bar_use = s_bar + 144, bar_free = s_bar + 160;
constexpr uint32_t s_par = s_bar + 192, s_late = s_bar + 200, s_again = s_bar + 204, s_tab = s_bar + 256, s_trace = s_tab + 2048;
constexpr int kSmemBytes  = s_trace + 2048 - kSmemBase;
constexpr int kThreads    = 384;
constexpr int kGrid       = 132;
constexpr int kTimeM = 2500, kTimeW = 5100;
constexpr float kScaleLog2e = 0.07216878364870322f * 1.4426950408889634f;

struct Maps {
    CUtensorMap m[4];
    CUtensorMap wo, wv;
    const struct Tables* tables;
};
#define TN(i, dflt) (dflt)
#define START_TIME (wg ? 850 + 500 * order : 250 + 560 * order)

struct Scratch {
    uint8_t img[2][2][kWBytes];
    uint32_t launches[kGrid][32];
};
__device__ __align__(1024) Scratch g_scratch;

struct Table {
    uint32_t route[32][4];
    uint32_t u[8][4][4];
    uint32_t v[16][4][4];
};
struct Tables { Table t[2]; };
constexpr Tables make_tables() {
    Tables r = {};
    for (int rev = 0; rev < 2; rev++)
        for (int j = 0; j < 4; j++) {
            Table& t = r.t[rev];
            for (int q = 0; q < 8; q++) {
                uint32_t* e = t.route[4 * q + j];
                e[0] = 4 * q + 2 * (j & 1) + (j >> 1); e[1] = e[0] ^ 1;
                e[2] = j < 2 ? 0x5410u : 0x1054u; e[3] = e[2] + 0x2222u;
                e = t.u[q][j];
                for (int n = 0; n < 7; n++) e[0] |= ((n + j) % 7 < q ? 1u : 0u) << n;
                e[3] = e[0];
                for (int k = 0; k < 2; k++) {
                    const int step = 2 * k + (j >> 1), p0 = (step < 3 ? 16 * step : 40) + 8 * (j & 1);
                    uint32_t m = 0x8888u;
                    for (int n = 0; n < 8; n++) m |= ((p0 + n) % 7 < q ? 1u : 0u) << (2 * n);
                    e[1 + k] = m * 0x10001u;
                }
            }
            for (int sum = 0; sum < 15; sum++) {
                uint32_t* e = t.v[sum][j];
                for (int row = 0; row < 2; row++)
                    for (int b = 0; b < 14; b++) {
                        const int off = (sum + row) / 2, p = 4 * b + j;
                        const uint32_t bit = 1u << (2 * b + row);
                        if (p < 42 && p >= 7 * off) e[rev] |= bit;
                        if (p < 7 * off - 7) e[1 - rev] |= bit;
                        if (p >= 42 && p >= 7 * off && p < 7 * off + 49) e[2] |= bit;
                    }
                for (int n = 0; n < 6; n++)
                    if (8 * n + 2 * j < 42) e[3] |= 1u << (n + ((8 * n + 2 * j >= 7 * (sum / 2 & ~1)) != rev ? 0 : 8));
            }
        }
    return r;
}
__device__ __align__(128) const Tables g_tables = make_tables();

#define WO4(i) "=f"(d[i]), "=f"(d[i + 1]), "=f"(d[i + 2]), "=f"(d[i + 3])
#define RW4(i) "+f"(d[i]), "+f"(d[i + 1]), "+f"(d[i + 2]), "+f"(d[i + 3])

template <bool FIRST>
__device__ __forceinline__ void wgmma_n192(float (&d)[96], uint32_t a0, uint32_t a1, uint32_t a2, uint32_t a3, uint64_t descb) {
    if constexpr (FIRST) {
        asm volatile(
            "wgmma.mma_async.sync.aligned.m64n192k16.f32.bf16.bf16 "
            "{%0, %1, %2, %3, %4, %5, %6, %7, %8, %9, %10, %11, %12, %13, %14, %15, %16, %17, %18, %19, %20, %21, %22, %23, "
            "%24, %25, %26, %27, %28, %29, %30, %31, %32, %33, %34, %35, %36, %37, %38, %39, %40, %41, %42, %43, %44, %45, %46, %47, "
            "%48, %49, %50, %51, %52, %53, %54, %55, %56, %57, %58, %59, %60, %61, %62, %63, %64, %65, %66, %67, %68, %69, %70, %71, "
            "%72, %73, %74, %75, %76, %77, %78, %79, %80, %81, %82, %83, %84, %85, %86, %87, %88, %89, %90, %91, %92, %93, %94, %95}, "
            "{%96, %97, %98, %99}, %100, 0, 1, 1, 0;"
            : WO4(0), WO4(4), WO4(8), WO4(12), WO4(16), WO4(20), WO4(24), WO4(28), WO4(32), WO4(36), WO4(40), WO4(44),
              WO4(48), WO4(52), WO4(56), WO4(60), WO4(64), WO4(68), WO4(72), WO4(76), WO4(80), WO4(84), WO4(88), WO4(92)
            : "r"(a0), "r"(a1), "r"(a2), "r"(a3), "l"(descb));
    } else {
        asm volatile(
            "wgmma.mma_async.sync.aligned.m64n192k16.f32.bf16.bf16 "
            "{%0, %1, %2, %3, %4, %5, %6, %7, %8, %9, %10, %11, %12, %13, %14, %15, %16, %17, %18, %19, %20, %21, %22, %23, "
            "%24, %25, %26, %27, %28, %29, %30, %31, %32, %33, %34, %35, %36, %37, %38, %39, %40, %41, %42, %43, %44, %45, %46, %47, "
            "%48, %49, %50, %51, %52, %53, %54, %55, %56, %57, %58, %59, %60, %61, %62, %63, %64, %65, %66, %67, %68, %69, %70, %71, "
            "%72, %73, %74, %75, %76, %77, %78, %79, %80, %81, %82, %83, %84, %85, %86, %87, %88, %89, %90, %91, %92, %93, %94, %95}, "
            "{%96, %97, %98, %99}, %100, 1, 1, 1, 0;"
            : RW4(0), RW4(4), RW4(8), RW4(12), RW4(16), RW4(20), RW4(24), RW4(28), RW4(32), RW4(36), RW4(40), RW4(44),
              RW4(48), RW4(52), RW4(56), RW4(60), RW4(64), RW4(68), RW4(72), RW4(76), RW4(80), RW4(84), RW4(88), RW4(92)
            : "r"(a0), "r"(a1), "r"(a2), "r"(a3), "l"(descb));
    }
}

template <bool FIRST>
__device__ __forceinline__ void wgmma_n88(float (&d)[44], uint32_t a0, uint32_t a1, uint32_t a2, uint32_t a3, uint64_t descb) {
    if constexpr (FIRST) {
        asm volatile(
            "wgmma.mma_async.sync.aligned.m64n88k16.f32.bf16.bf16 "
            "{%0, %1, %2, %3, %4, %5, %6, %7, %8, %9, %10, %11, %12, %13, %14, %15, %16, %17, %18, %19, %20, %21, %22, %23, "
            "%24, %25, %26, %27, %28, %29, %30, %31, %32, %33, %34, %35, %36, %37, %38, %39, %40, %41, %42, %43}, "
            "{%44, %45, %46, %47}, %48, 0, 1, 1, 0;"
            : WO4(0), WO4(4), WO4(8), WO4(12), WO4(16), WO4(20), WO4(24), WO4(28), WO4(32), WO4(36), WO4(40)
            : "r"(a0), "r"(a1), "r"(a2), "r"(a3), "l"(descb));
    } else {
        asm volatile(
            "wgmma.mma_async.sync.aligned.m64n88k16.f32.bf16.bf16 "
            "{%0, %1, %2, %3, %4, %5, %6, %7, %8, %9, %10, %11, %12, %13, %14, %15, %16, %17, %18, %19, %20, %21, %22, %23, "
            "%24, %25, %26, %27, %28, %29, %30, %31, %32, %33, %34, %35, %36, %37, %38, %39, %40, %41, %42, %43}, "
            "{%44, %45, %46, %47}, %48, 1, 1, 1, 0;"
            : RW4(0), RW4(4), RW4(8), RW4(12), RW4(16), RW4(20), RW4(24), RW4(28), RW4(32), RW4(36), RW4(40)
            : "r"(a0), "r"(a1), "r"(a2), "r"(a3), "l"(descb));
    }
}

template <bool FIRST>
__device__ __forceinline__ void wgmma_n32(float (&d)[16], uint32_t a0, uint32_t a1, uint32_t a2, uint32_t a3, uint64_t descb) {
    if constexpr (FIRST) {
        asm volatile(
            "wgmma.mma_async.sync.aligned.m64n32k16.f32.bf16.bf16 "
            "{%0, %1, %2, %3, %4, %5, %6, %7, %8, %9, %10, %11, %12, %13, %14, %15}, "
            "{%16, %17, %18, %19}, %20, 0, 1, 1, 0;"
            : WO4(0), WO4(4), WO4(8), WO4(12)
            : "r"(a0), "r"(a1), "r"(a2), "r"(a3), "l"(descb));
    } else {
        asm volatile(
            "wgmma.mma_async.sync.aligned.m64n32k16.f32.bf16.bf16 "
            "{%0, %1, %2, %3, %4, %5, %6, %7, %8, %9, %10, %11, %12, %13, %14, %15}, "
            "{%16, %17, %18, %19}, %20, 1, 1, 1, 0;"
            : RW4(0), RW4(4), RW4(8), RW4(12)
            : "r"(a0), "r"(a1), "r"(a2), "r"(a3), "l"(descb));
    }
}

template <bool FIRST, int SEL>
__device__ __forceinline__ void wgmma_sp_n192_tb(float (&d)[96], uint32_t a0, uint32_t a1, uint32_t a2, uint32_t a3, uint64_t descb, uint32_t meta) {
    if constexpr (FIRST) {
        asm volatile(
            "wgmma.mma_async.sp.sync.aligned.m64n192k32.f32.bf16.bf16 "
            "{%0, %1, %2, %3, %4, %5, %6, %7, %8, %9, %10, %11, %12, %13, %14, %15, %16, %17, %18, %19, %20, %21, %22, %23, "
            "%24, %25, %26, %27, %28, %29, %30, %31, %32, %33, %34, %35, %36, %37, %38, %39, %40, %41, %42, %43, %44, %45, %46, %47, "
            "%48, %49, %50, %51, %52, %53, %54, %55, %56, %57, %58, %59, %60, %61, %62, %63, %64, %65, %66, %67, %68, %69, %70, %71, "
            "%72, %73, %74, %75, %76, %77, %78, %79, %80, %81, %82, %83, %84, %85, %86, %87, %88, %89, %90, %91, %92, %93, %94, %95}, "
            "{%96, %97, %98, %99}, %100, %101, %102, 0, 1, 1, 1;"
            : WO4(0), WO4(4), WO4(8), WO4(12), WO4(16), WO4(20), WO4(24), WO4(28), WO4(32), WO4(36), WO4(40), WO4(44),
              WO4(48), WO4(52), WO4(56), WO4(60), WO4(64), WO4(68), WO4(72), WO4(76), WO4(80), WO4(84), WO4(88), WO4(92)
            : "r"(a0), "r"(a1), "r"(a2), "r"(a3), "l"(descb), "r"(meta), "n"(SEL));
    } else {
        asm volatile(
            "wgmma.mma_async.sp.sync.aligned.m64n192k32.f32.bf16.bf16 "
            "{%0, %1, %2, %3, %4, %5, %6, %7, %8, %9, %10, %11, %12, %13, %14, %15, %16, %17, %18, %19, %20, %21, %22, %23, "
            "%24, %25, %26, %27, %28, %29, %30, %31, %32, %33, %34, %35, %36, %37, %38, %39, %40, %41, %42, %43, %44, %45, %46, %47, "
            "%48, %49, %50, %51, %52, %53, %54, %55, %56, %57, %58, %59, %60, %61, %62, %63, %64, %65, %66, %67, %68, %69, %70, %71, "
            "%72, %73, %74, %75, %76, %77, %78, %79, %80, %81, %82, %83, %84, %85, %86, %87, %88, %89, %90, %91, %92, %93, %94, %95}, "
            "{%96, %97, %98, %99}, %100, %101, %102, 1, 1, 1, 1;"
            : RW4(0), RW4(4), RW4(8), RW4(12), RW4(16), RW4(20), RW4(24), RW4(28), RW4(32), RW4(36), RW4(40), RW4(44),
              RW4(48), RW4(52), RW4(56), RW4(60), RW4(64), RW4(68), RW4(72), RW4(76), RW4(80), RW4(84), RW4(88), RW4(92)
            : "r"(a0), "r"(a1), "r"(a2), "r"(a3), "l"(descb), "r"(meta), "n"(SEL));
    }
}

#define TR(slot)
#define TRX(slot)
#define TRE(slot)
#define TRT(slot)
#define TRF(slot)
#define TRW(slot)
#define TRG(slot)
#define TRDUMP()

__device__ __forceinline__ void wg_fence() { asm volatile("wgmma.fence.sync.aligned;" ::: "memory"); }
__device__ __forceinline__ void wg_commit() { asm volatile("wgmma.commit_group.sync.aligned;" ::: "memory"); }
template <int N>
__device__ __forceinline__ void wg_wait() { asm volatile("wgmma.wait_group.sync.aligned %0;" ::"n"(N) : "memory"); }

template <int N>
__device__ __forceinline__ void pin(float (&d)[N]) {
#pragma unroll
    for (int i = 0; i < N; i++) asm volatile("" : "+f"(d[i])::"memory");
}
template <int N>
__device__ __forceinline__ void pin(uint32_t (&d)[N]) {
#pragma unroll
    for (int i = 0; i < N; i++) asm volatile("" : "+r"(d[i])::"memory");
}

constexpr uint64_t kDescRing = ((uint64_t)((1u << 30) | (1024u >> 4)) << 32) | (1u << 16) | (s_ring >> 4);
constexpr uint32_t kToV = ((kRingChunk >> 4) - 1) << 20;
__device__ __forceinline__ uint64_t desc_at(uint64_t base, uint32_t byte_off) {
    uint64_t d;
    asm volatile("add.s64 %0, %1, %2;" : "=l"(d) : "l"(base), "l"((uint64_t)(byte_off >> 4)));
    return d;
}

__device__ __forceinline__ void mbar_init(uint32_t bar, uint32_t count) {
    asm volatile("mbarrier.init.shared::cta.b64 [%0], %1;" ::"r"(bar), "r"(count) : "memory");
}
__device__ __forceinline__ void mbar_expect_tx(uint32_t bar, uint32_t bytes) {
    asm volatile("mbarrier.arrive.expect_tx.shared::cta.b64 _, [%0], %1;" ::"r"(bar), "r"(bytes) : "memory");
}
__device__ __forceinline__ void expect_tx_only(uint32_t bar, uint32_t bytes) {
    asm volatile("mbarrier.expect_tx.relaxed.cta.shared::cta.b64 [%0], %1;" ::"r"(bar), "r"(bytes) : "memory");
}
__device__ __forceinline__ void mbar_arrive(uint32_t bar) {
    asm volatile("mbarrier.arrive.shared::cta.b64 _, [%0];" ::"r"(bar) : "memory");
}
__device__ __forceinline__ void mbar_wait(uint32_t bar, uint32_t parity) {
    asm volatile(
        "{\n.reg .pred p;\n"
        "W: mbarrier.try_wait.parity.shared::cta.b64 p, [%0], %1;\n"
        "@!p bra W;\n}\n"
        ::"r"(bar), "r"(parity) : "memory");
}
__device__ __forceinline__ uint32_t clock_now() {
    uint32_t c;
    asm volatile("mov.u32 %0, %%clock;" : "=r"(c)::"memory");
    return c;
}
__device__ __forceinline__ void wait_until(uint32_t t0, int t) {
    if (t == 0) return;
    while ((int)(clock_now() - t0) < t) {}
}
__device__ __forceinline__ bool elect() {
    uint32_t ok;
    asm volatile("{\n.reg .pred p;\nelect.sync _|p, 0xffffffff;\nselp.u32 %0, 1, 0, p;\n}\n" : "=r"(ok));
    return ok != 0;
}
__device__ __forceinline__ void turn_wait(int wg) { asm volatile("bar.sync %0, 256;" ::"r"(1 + wg) : "memory"); }
__device__ __forceinline__ void turn_pass(int wg) { asm volatile("bar.arrive %0, 256;" ::"r"(2 - wg) : "memory"); }

__device__ __forceinline__ void tma_box(uint32_t dst, const CUtensorMap* map, uint32_t bar, int c0, int c2, int c3, int c4) {
    asm volatile(
        "cp.async.bulk.tensor.5d.shared::cluster.global.mbarrier::complete_tx::bytes [%0], [%1, {%3, %4, %5, %6, %7}], [%2];"
        ::"r"(dst), "l"(map), "r"(bar), "r"(c0), "r"(0), "r"(c2), "r"(c3), "r"(c4)
        : "memory");
}
__device__ __forceinline__ void tma_3d(uint32_t dst, const CUtensorMap* map, uint32_t bar, int c1, int c2) {
    asm volatile("cp.async.bulk.tensor.3d.shared::cluster.global.mbarrier::complete_tx::bytes [%0], [%1, {%3, %4, %5}], [%2];"
                 ::"r"(dst), "l"(map), "r"(bar), "r"(0), "r"(c1), "r"(c2)
                 : "memory");
}
__device__ __forceinline__ void prefetch_map(const CUtensorMap* map) {
    asm volatile("prefetch.tensormap [%0];" ::"l"(map) : "memory");
}
__device__ __forceinline__ uint4 ldg(const void* p) {
    uint4 v;
    asm volatile("ld.global.v4.u32 {%0, %1, %2, %3}, [%4];" : "=r"(v.x), "=r"(v.y), "=r"(v.z), "=r"(v.w) : "l"(p) : "memory");
    return v;
}
__device__ __forceinline__ uint32_t pack_bf16(float lo, float hi) {
    uint32_t r;
    asm("cvt.rn.bf16x2.f32 %0, %1, %2;" : "=r"(r) : "f"(hi), "f"(lo));
    return r;
}
__device__ __forceinline__ float ex2(float x) {
    float y;
    asm("ex2.approx.ftz.f32 %0, %1;" : "=f"(y) : "f"(x));
    return y;
}
__device__ __forceinline__ float rcp(float x) {
    float y;
    asm("rcp.approx.ftz.f32 %0, %1;" : "=f"(y) : "f"(x));
    return y;
}
__device__ __forceinline__ void mma16816(float (&d)[4], uint32_t a0, uint32_t a1, uint32_t a2, uint32_t a3, uint32_t b0, uint32_t b1) {
    asm volatile("mma.sync.aligned.m16n8k16.row.col.f32.bf16.bf16.f32 {%0, %1, %2, %3}, {%4, %5, %6, %7}, {%8, %9}, {%0, %1, %2, %3};"
                 : "+f"(d[0]), "+f"(d[1]), "+f"(d[2]), "+f"(d[3])
                 : "r"(a0), "r"(a1), "r"(a2), "r"(a3), "r"(b0), "r"(b1));
}
__device__ __forceinline__ uint4 lds128(uint32_t addr) {
    uint4 v;
    asm volatile("ld.volatile.shared.v4.u32 {%0, %1, %2, %3}, [%4];" : "=r"(v.x), "=r"(v.y), "=r"(v.z), "=r"(v.w) : "r"(addr) : "memory");
    return v;
}
__device__ __forceinline__ uint32_t lds_volatile(uint32_t addr) {
    uint32_t v;
    asm volatile("ld.volatile.shared.u32 %0, [%1];" : "=r"(v) : "r"(addr) : "memory");
    return v;
}

__device__ __forceinline__ int window_start(int n) { return min(max(n, 0), 105); }
__device__ __forceinline__ int origin_u(int u) { return min(max(u, 0), 98); }

struct Work {
    int u, v;
    int step;
    uint32_t su, sv;
    uint32_t base;
    bool corner;
    int ntiles;
    __device__ __forceinline__ void pixel_offsets(int qu, int qv, int j, uint32_t& o0, uint32_t& o1) const {
        const uint32_t b = (qu + window_start(qu)) * su + j * 16 + base;
        o0 = b + (qv + window_start(qv)) * sv;
        o1 = b + (qv + 1 + window_start(qv + 1)) * sv;
    }
};

__device__ __forceinline__ Work decode_work(int c) {
    Work w;
    const bool transposed = (c >> 4) == 7;
    const int px = 6 * (c & 1), py = 3 * (c & 2);
    w.corner = c >= 128;
    w.step = 8 - 4 * (c & 4);
    w.u = (c < 112 ? c & ~7 : 96 + (c & 8)) + (transposed ? py : px) - 6;
    w.v = (w.corner ? 96 : 48 - 2 * (c & 4)) + (transposed ? px : py) - 6;
    w.su = transposed ? kHW * kPixBytes : kPixBytes;
    w.sv = transposed ? kPixBytes : kHW * kPixBytes;
    w.base = px * (kPixBytes / 6) + py * (kHW * kPixBytes / 6) + 6 * (kHW + 1) * kPixBytes;
    w.ntiles = w.corner ? 4 : 6;
    return w;
}

struct RawX { uint4 a[6], b[6]; };
__device__ __forceinline__ void load_raw(RawX& r, const uint8_t* base, uint32_t o0, uint32_t o1) {
    __syncwarp();
#pragma unroll
    for (int c = 0; c < 6; c++) { r.a[c] = ldg(base + o0 + c * 64); r.b[c] = ldg(base + o1 + c * 64); }
    __syncwarp();
}
__device__ __forceinline__ void raw_to_frags(const RawX& r, uint32_t zero, uint32_t (&f)[48]) {
#pragma unroll
    for (int c = 0; c < 6; c++) {
        asm volatile("{\n.reg .b32 t, u;\nadd.u32 t, %4, %8;\nadd.u32 u, %5, %8;\nxor.b32 %0, %6, %8;\nxor.b32 %1, %7, %8;\n"
                     "xor.b32 %2, t, %8;\nxor.b32 %3, u, %8;\n}\n"
                     : "=&r"(f[8 * c + 1]), "=&r"(f[8 * c + 3]), "=&r"(f[8 * c + 4]), "=&r"(f[8 * c + 6])
                     : "r"(r.a[c].y), "r"(r.a[c].w), "r"(r.b[c].x), "r"(r.b[c].z), "r"(zero));
        f[8 * c + 0] = r.a[c].x; f[8 * c + 2] = r.a[c].z; f[8 * c + 5] = r.b[c].y; f[8 * c + 7] = r.b[c].w;
    }
}
__device__ __forceinline__ void acc_to_frags(const float (&d)[96], uint32_t (&f)[48]) {
#pragma unroll
    for (int i = 0; i < 48; i++) f[i] = pack_bf16(d[2 * i], d[2 * i + 1]);
}

template <class F>
__device__ __forceinline__ void proj_gemm(float (&d)[96], const uint32_t (&a)[48], uint64_t dsc, uint32_t img, F after) {
#pragma unroll
    for (int s = 0; s < 12; s++) {
        if (s == 0) wgmma_n192<true>(d, a[4 * s], a[4 * s + 1], a[4 * s + 2], a[4 * s + 3], desc_at(dsc, img - s_ring + (s >> 2) * kWChunk + (s & 3) * 32));
        else wgmma_n192<false>(d, a[4 * s], a[4 * s + 1], a[4 * s + 2], a[4 * s + 3], desc_at(dsc, img - s_ring + (s >> 2) * kWChunk + (s & 3) * 32));
        if (s == 11) wg_commit();
        after(s);
    }
}
__device__ __forceinline__ void pack_out(const float (&acc)[96], uint32_t (&po)[48]) {
#pragma unroll
    for (int g = 0; g < 6; g++)
#pragma unroll
        for (int q = 0; q < 4; q++) {
            po[8 * g + q] = pack_bf16(acc[16 * g + 4 * q], acc[16 * g + 4 * q + 1]);
            po[8 * g + 4 + q] = pack_bf16(acc[16 * g + 4 * q + 2], acc[16 * g + 4 * q + 3]);
        }
}
template <bool PINNED = true>
__device__ __forceinline__ void store_one(bool on, uint8_t* p0, uint8_t* p1, const uint32_t (&po)[48], int n) {
    if (PINNED) __syncwarp();
    asm volatile("{\n.reg .pred p;\nsetp.ne.u32 p, %5, 0;\n@p st.global.v4.u32 [%0], {%1, %2, %3, %4};\n}\n"
                 ::"l"(((n & 1) ? p1 : p0) + (n >> 1) * 64), "r"(po[4 * n]), "r"(po[4 * n + 1]), "r"(po[4 * n + 2]), "r"(po[4 * n + 3]), "r"((uint32_t)on) : "memory");
}

template <int N>
__device__ __forceinline__ float tree_max(const float (&v)[N]) {
    float t[N];
#pragma unroll
    for (int i = 0; i < N; i++) t[i] = v[i];
#pragma unroll
    for (int w = 1; w < N; w *= 2)
#pragma unroll
        for (int i = 0; i + w < N; i += 2 * w) t[i] = fmaxf(t[i], t[i + w]);
    return t[0];
}
template <int N>
__device__ __forceinline__ float tree_sum(const float (&v)[N]) {
    float t[N];
#pragma unroll
    for (int i = 0; i < N; i++) t[i] = v[i];
#pragma unroll
    for (int w = 1; w < N; w *= 2)
#pragma unroll
        for (int i = 0; i + w < N; i += 2 * w) t[i] += t[i + w];
    return t[0];
}

template <int B>
__device__ __forceinline__ void pick(uint32_t h, uint32_t ok, const float* s, float& v0, float& v1) {
    asm("{\n.reg .pred p, q0, q1;\n.reg .b32 t;\nand.b32 t, %6, %7;\nsetp.ne.u32 p, t, 0;\n"
        "and.b32 t, %8, %9;\nsetp.ne.u32 q0, t, 0;\nand.b32 t, %8, %10;\nsetp.ne.u32 q1, t, 0;\n"
        "@q0 selp.f32 %0, %3, %2, p;\n@q1 selp.f32 %1, %5, %4, p;\n}\n"
        : "+f"(v0), "+f"(v1)
        : "f"(s[0]), "f"(s[1]), "f"(s[2]), "f"(s[3]), "r"(h), "n"(1 << ((4 * B) % 7)), "r"(ok), "n"(1 << (2 * B)), "n"(2 << (2 * B)));
}
template <int B, class F>
__device__ __forceinline__ void for_blocks(F f) {
    if constexpr (B > 0) { for_blocks<B - 1>(f); f(std::integral_constant<int, B - 1>{}); }
}
__device__ __forceinline__ void gather_outer(const float (&s)[44], uint32_t h, uint32_t ok, float (&v0)[14], float (&v1)[14]) {
    for_blocks<11>([&](auto B) {
        constexpr int b = B.value < 8 ? (B.value >> 1) + 7 * (B.value & 1) : B.value - 4;
        pick<b>(h, ok, &s[4 * b], v0[b], v1[b]);
    });
}
__device__ __forceinline__ void gather_mid(const float (&sE)[16], uint32_t h, uint32_t ok, float (&v0)[14], float (&v1)[14]) {
    for_blocks<4>([&](auto B) { pick<10 + B.value>(h, ok, &sE[4 * B.value], v0[10 + B.value], v1[10 + B.value]); });
}
__device__ __forceinline__ float quad_max(float m) {
    m = fmaxf(m, __shfl_xor_sync(0xffffffffu, m, 1));
    return fmaxf(m, __shfl_xor_sync(0xffffffffu, m, 2));
}
__device__ __forceinline__ float quad_sum(float s) {
    s += __shfl_xor_sync(0xffffffffu, s, 1);
    return s + __shfl_xor_sync(0xffffffffu, s, 2);
}
template <int B0, int B1>
__device__ __forceinline__ void exp_route(float (&v0)[14], float (&v1)[14], float m0, float m1, const uint4& r, bool even, uint32_t (&y)[14]) {
#pragma unroll
    for (int b = B0; b < B1; b++) { v0[b] = ex2(v0[b] - m0); v1[b] = ex2(v1[b] - m1); }
#pragma unroll
    for (int b = B0; b < B1; b += 2) {
        const uint32_t x0 = pack_bf16(v0[b], v1[b]), x1 = pack_bf16(v0[b + 1], v1[b + 1]);
        const uint32_t u = __shfl_sync(0xffffffffu, even ? x0 : x1, r.x);
        const uint32_t w = __shfl_sync(0xffffffffu, even ? x1 : x0, r.y);
        y[b] = __byte_perm(u, w, r.z); y[b + 1] = __byte_perm(u, w, r.w);
    }
}
template <int BIT0, int N0, int N1>
__device__ __forceinline__ void unfold(const uint32_t (&y)[14], uint32_t fold, uint32_t (&p)[12]) {
    for_blocks<N1 - N0>([&](auto N) {
        constexpr int n = N0 + N.value;
        asm("{\n.reg .pred p;\n.reg .b32 t;\nand.b32 t, %4, %5;\nsetp.ne.u32 p, t, 0;\nselp.b32 %0, %2, 0, p;\nselp.b32 %1, %3, 0, p;\n}\n"
            : "=r"(p[2 * n]), "=r"(p[2 * n + 1]) : "r"(y[2 * n]), "r"(y[2 * n + 1]), "r"(fold), "n"(1 << (BIT0 + n)));
    });
}
__device__ __forceinline__ void keep(bool never, uint32_t a, uint32_t b, uint32_t c, uint32_t d) {
    asm volatile("{\n.reg .pred p;\nsetp.ne.u32 p, %4, 0;\n@p st.volatile.shared.v4.u32 [%5], {%0, %1, %2, %3};\n}\n"
                 ::"r"(a), "r"(b), "r"(c), "r"(d), "r"((uint32_t)never), "r"(s_trace) : "memory");
}

__device__ __forceinline__ uint32_t wimg_offset(uint32_t row, uint32_t s, uint32_t j) {
    return (s >> 2) * kWChunk + row * 128 + (((2 * (s & 3) + (j >> 1)) ^ (row & 7)) << 4) + (j & 1) * 8;
}

__device__ __forceinline__ void ldsm4(uint32_t (&r)[4], uint32_t addr) {
    asm volatile("ldmatrix.sync.aligned.m8n8.x4.shared.b16 {%0, %1, %2, %3}, [%4];" : "=r"(r[0]), "=r"(r[1]), "=r"(r[2]), "=r"(r[3]) : "r"(addr) : "memory");
}
__device__ __forceinline__ void ldsm4_t(uint32_t (&r)[4], uint32_t addr) {
    asm volatile("ldmatrix.sync.aligned.m8n8.x4.trans.shared.b16 {%0, %1, %2, %3}, [%4];" : "=r"(r[0]), "=r"(r[1]), "=r"(r[2]), "=r"(r[3]) : "r"(addr) : "memory");
}
struct MOperands { uint4 A[2][2], B[4][2]; };
__device__ __forceinline__ void m_load(MOperands& m, const uint8_t* wqkv, uint32_t mt, uint32_t s, uint32_t q, uint32_t lane) {
    const uint32_t r8 = lane >> 2, col = q * 128 + (lane & 3) * 16;
    const uint8_t* pa = wqkv + (16 * mt + r8) * 1152 + col;
    const uint8_t* pb = wqkv + (16 * s + 8 * (r8 & 2) + (r8 & 5)) * 1152 + col;
#pragma unroll
    for (int c = 0; c < 2; c++) {
#pragma unroll
        for (int h = 0; h < 2; h++) m.A[h][c] = ldg(pa + 384 + h * 8 * 1152 + c * 64);
#pragma unroll
        for (int n = 0; n < 4; n++) m.B[n][c] = ldg(pb + ((n & 1) * 8 + (n & 2)) * 1152 + c * 64);
    }
}
__device__ __forceinline__ void m_partial(MOperands& m, uint32_t q, uint32_t lane, uint32_t zero) {
    auto& A = m.A;
    auto& B = m.B;
#pragma unroll
    for (int i = 0; i < 4; i++) { uint4& a = A[i >> 1][i & 1]; a.x ^= zero; a.y ^= zero; a.z ^= zero; a.w ^= zero; }
#pragma unroll
    for (int n = 0; n < 4; n++) {
        float d[4] = {0.f, 0.f, 0.f, 0.f};
#pragma unroll
        for (int c = 0; c < 2; c++) {
            mma16816(d, A[0][c].x, A[1][c].x, A[0][c].y, A[1][c].y, B[n][c].x, B[n][c].y);
            mma16816(d, A[0][c].z, A[1][c].z, A[0][c].w, A[1][c].w, B[n][c].z, B[n][c].w);
        }
        asm volatile("st.shared.v4.f32 [%0], {%1, %2, %3, %4};" ::"r"(s_wv + q * 2048 + n * 512 + lane * 16), "f"(d[0]), "f"(d[1]), "f"(d[2]), "f"(d[3]) : "memory");
    }
}
__device__ __forceinline__ void m_reduce(uint32_t e, uint32_t lane, float (&d)[2][4]) {
#pragma unroll
    for (int n = 0; n < 2; n++) {
        float t[3][4];
#pragma unroll
        for (int q = 0; q < 3; q++)
            asm volatile("ld.shared.v4.f32 {%0, %1, %2, %3}, [%4];" : "=f"(t[q][0]), "=f"(t[q][1]), "=f"(t[q][2]), "=f"(t[q][3]) : "r"(s_wv + q * 2048 + e * 1024 + n * 512 + lane * 16) : "memory");
#pragma unroll
        for (int i = 0; i < 4; i++) d[n][i] = (t[0][i] + t[1][i] + t[2][i]) * kScaleLog2e;
    }
}
__device__ __forceinline__ void w_piece(uint32_t q, uint32_t lane, float (&d)[2][4]) {
    const uint32_t rr = lane & 7, mi = lane >> 3, kr = 4 * (rr >> 1) + (mi & 2) + (rr & 1);
    const uint32_t pa = s_wv + q * 32 + (4 * (mi & 2) + rr) * 96 + ((mi & 1) << 4);
    const uint32_t pb = s_wv + 3 * 6144 + kr * 128 + (((mi & 1) ^ (kr & 7)) << 4);
    float e[2][4];
#pragma unroll
    for (int i = 0; i < 8; i++) (&d[0][0])[i] = (&e[0][0])[i] = 0.f;
#pragma unroll
    for (int k = 0; k < 12; k++) {
        uint32_t aq[4], bq[4];
        ldsm4_t(aq, pa + k * 1536);
        ldsm4(bq, (pb ^ ((k & 3) << 5)) + (k >> 2) * 2048);
        mma16816(k & 1 ? e[0] : d[0], aq[0], aq[1], aq[2], aq[3], bq[0], bq[1]);
        mma16816(k & 1 ? e[1] : d[1], aq[0], aq[1], aq[2], aq[3], bq[2], bq[3]);
    }
#pragma unroll
    for (int i = 0; i < 8; i++) (&d[0][0])[i] += (&e[0][0])[i];
}
__device__ __forceinline__ uint32_t piece_offset(uint32_t which, uint32_t s, uint32_t mt, uint32_t lane) {
    const uint32_t r8 = lane >> 2;
    return which * kWBytes + wimg_offset(which ? 32 * (mt >> 1) + 8 * (r8 >> 1) + 4 * (mt & 1) + (r8 & 1) : 16 * mt + r8, s, lane & 3);
}
__device__ __forceinline__ void piece_store(Scratch* g, uint32_t par, uint32_t off0, uint32_t which, const float (&d)[2][4]) {
#pragma unroll
    for (int hf = 0; hf < 2; hf++) {
        const uint32_t off = off0 ^ (hf ? which ? 288 : 1024 : 0);
        const uint32_t a = pack_bf16(d[0][2 * hf], d[0][2 * hf + 1]), b = pack_bf16(d[1][2 * hf], d[1][2 * hf + 1]);
        asm volatile("st.relaxed.gpu.global.v2.u32 [%0], {%1, %2};" ::"l"(g->img[0][0] + (par + off)), "r"(a ? a : 0x8000u), "r"(b) : "memory");
    }
}
__device__ __forceinline__ void piece_clear(Scratch* g, uint32_t par, uint32_t off0, uint32_t which) {
#pragma unroll
    for (int hf = 0; hf < 2; hf++)
        asm volatile("st.relaxed.gpu.global.v2.u32 [%0], {%1, %1};" ::"l"(g->img[0][0] + (par + (off0 ^ (hf ? which ? 288 : 1024 : 0)))), "r"(0) : "memory");
}

__device__ __forceinline__ uint32_t ld_relaxed(const uint32_t* p) {
    uint32_t v;
    asm volatile("ld.relaxed.gpu.global.u32 %0, [%1];" : "=r"(v) : "l"(p) : "memory");
    return v;
}
__device__ __forceinline__ void count_up(uint32_t* p) {
    asm volatile("red.relaxed.gpu.global.add.u32 [%0], %1;" ::"l"(p), "r"(1) : "memory");
}
__device__ __forceinline__ void bulk_g2s(uint32_t dst, const void* src, uint32_t bytes, uint32_t bar) {
    asm volatile("cp.async.bulk.shared::cluster.global.mbarrier::complete_tx::bytes [%0], [%1], %2, [%3];"
                 ::"r"(dst), "l"(src), "r"(bytes), "r"(bar)
                 : "memory");
}

__global__ void __launch_bounds__(kThreads, 1)
nat_fused_kernel(const uint8_t* __restrict__ x, const uint8_t* __restrict__ wqkv, uint8_t* __restrict__ out, Scratch* g,
                 const uint8_t* wo, uint64_t dsc, const __grid_constant__ Maps maps) {
    const int tid = threadIdx.x, lane = tid & 31;
    const int warp = __shfl_sync(0xffffffffu, tid >> 5, 0);
    const int wg = warp >> 2, wq = warp & 3, r8 = lane >> 2, j = lane & 3;
    const int cta = blockIdx.x;
    const Work w = decode_work(cta);
    const uint32_t jq = (cta < 124 ? cta + 8 : cta - 124) / 11u, jr = (cta < 124 ? cta + 8 : cta - 124) - 11 * jq;
    const uint32_t which = jr >= 6, jhi = which ? jr - 6 : jq, jlo = which ? jq : 2 * jr;
    const bool has_job = jr < 10;
    if (wg == 2 && wq < 3) {
#pragma unroll
        for (int r = 0; r < 3; r++)
            asm volatile("st.shared.v4.u32 [%0], {%1, %1, %1, %1};" ::"r"(s_ring + wq * kRingChunk + (r == 0 ? 84 : r == 1 ? 88 : 204) * 128 + lane * 16), "r"(0) : "memory");
        asm volatile("fence.proxy.async.shared::cta;" ::: "memory");
    }
    MOperands mo;
    uint32_t launch = 0;
    if (wg == 1 && wq < 3 && !which) m_load(mo, wqkv, jhi, jlo, wq, lane);
    if (warp == 7) launch = ld_relaxed(g->launches[cta]);
    if (x == nullptr) return;
    const uint32_t t_start = clock_now();
    if (wg == 2) {
        asm volatile("setmaxnreg.dec.sync.aligned.u32 24;");
        if (wq < 3) {
            if (lane < 3 && cta < 128) {
                const uint32_t row = 3 * (cta >> 1) + wq;
                asm volatile("prefetch.global.L2 [%0];" ::"l"((cta & 1 ? wo + row * 384 : wqkv + row * 1152 + 768) + lane * 128));
            }
            asm volatile("bar.sync 7, 192;" ::: "memory");
            const uint32_t par = lds_volatile(s_par);
            uint32_t phase = 0;
#pragma unroll 1
            for (uint32_t c = 0; c < 6; c++) {
                const uint32_t part = c * kWChunk + wq * (kWChunk / 3), img = 8 * min(c, 3u);
                mbar_wait(bar_img + 8 * c, 0);
                if (c == 0 && lane == 0) mbar_arrive(bar_ok);
                if (wq == 0) TRW(10 + c);
#pragma unroll 1
                while (true) {
                    uint32_t lo = ~0u;
#pragma unroll
                    for (int q = 0; q < 8; q++) lo = min(lo, lds_volatile(s_m + part + lane * 32 + (lane & 12) * 2 + q * 1024));
                    if (__all_sync(0xffffffffu, lo) || phase > 65535) break;
                    if (elect()) {
                        mbar_expect_tx(bar_redo + 8 * wq, kWChunk / 3);
                        bulk_g2s(s_m + part, g->img[0][0] + par + part, kWChunk / 3, bar_redo + 8 * wq);
                    }
                    mbar_wait(bar_redo + 8 * wq, phase++ & 1);
                }
                if (c == 2 && phase) asm volatile("st.shared.u32 [%0], %1;" ::"r"(s_again), "r"(1) : "memory");
                if ((c == 2 || c == 5) && lane == 0) mbar_arrive(bar_ok + img);
            }
        } else {
            const CUtensorMap* map = &maps.m[w.sv == kPixBytes ? 2 : 0];
            if (elect()) {
#pragma unroll
                for (int i = 0; i < 23; i++) mbar_init(s_bar + 8 * i, i < 13 ? 1 : i < 18 ? 3 : 4);
                asm volatile("fence.mbarrier_init.release.cluster;" ::: "memory");
                prefetch_map(map + 1);
                expect_tx_only(bar_a, sizeof(Table));
                bulk_g2s(s_tab, &maps.tables->t[w.step < 0], sizeof(Table), bar_a);
            }
            if (which && has_job && elect()) {
                mbar_expect_tx(bar_wop, 4 * 6144);
                tma_3d(s_wv, &maps.wo, bar_wop, 0, jhi);
                tma_3d(s_wv + 3 * 6144, &maps.wv, bar_wop, 16 * jlo, 6);
            }
            int u = w.u, v = w.v;
            uint32_t wait_bar = bar_use, wait_par = 1, slot = 0;
#pragma unroll 1
            for (int step = 0; step < 7 - w.corner; step++) {
                const bool first = step == 0 || (w.corner && step == 4);
                const int row = v + 4 + (first ? -w.step : w.step) / 2, ou = origin_u(u);
                const bool final = step == 6 - w.corner;
                uint32_t dst = final ? s_m : s_ring + (first ? 0 : slot), mid = (final ? s_m : s_ring) + kOffMid + 512, bar = first ? bar_a : bar_b;
                if (final) { wait_bar = bar_free; wait_par = 0; }
#pragma unroll 1
                for (int ch = (cta & 1) * kC, n = 0; n < 3; n++, ch += 64, dst += kRingChunk, mid += kRingChunk) {
                    mbar_wait(wait_bar, wait_par);
                    if (n == 0) TRW(24 + step);
                    if (final) wait_bar += 8;
                    if (elect()) {
                        mbar_expect_tx(bar, first ? kSlotBytes : kSlotBytes + kMidBytes);
                        tma_box(dst, map, bar, ch, ou, (cta >> 1) & 1, row);
                    }
                    if (!first) {
                        if (elect()) tma_box(mid, map + 1, bar, ch, ou, (cta >> 1) & 1, v + 6);
                        bar += 8;
                    }
                }
                if (step == 0) {
                    asm volatile("st.shared.v2.u32 [%0], {%1, %1};" ::"r"(s_late), "r"(0) : "memory");
                    asm volatile("bar.arrive 3, 160;\nbar.arrive 4, 160;\nbar.arrive 8, 128;\nbar.sync 9, 64;" ::: "memory");
                }
                if (step < 2) {
                    if (step) {
                        asm volatile("bar.sync 6, 128;" ::: "memory");
                    }
                    const uint32_t par = __shfl_sync(0xffffffffu, lds_volatile(s_par), 0);
                    wait_until(t_start, step ? TN(5, kTimeW) : TN(6, kTimeM));
                    TRW(5 + 4 * step);
#pragma unroll 1
                    for (int c = 3 * step; c < 3 + 3 * step; c++)
                        if (elect()) {
                            mbar_expect_tx(bar_img + 8 * c, kWChunk);
                            bulk_g2s(s_m + c * kWChunk, g->img[0][0] + (par + c * kWChunk), kWChunk, bar_img + 8 * c);
                        }
                }
                const bool again = w.corner && step == 3;
                wait_bar = step == 0 ? bar_img + 8 * TN(1, 1) : again ? bar_use + 8 : bar_use;
                if (!again) {
                    wait_par = slot ? 0 : step != 0;
                    slot ^= kSlotStride;
                    if (w.corner && step == 2) { u += 8; v -= 8; } else if (step) v += w.step;
                }
            }
        }
        TRDUMP();
        return;
    }
    if (warp == 7) {
        asm volatile("st.shared.u32 [%0], %1;\nbar.arrive 9, 64;" ::"r"(s_par), "r"((launch & 1) * 2 * kWBytes) : "memory");
        g->launches[cta][lane] = launch + 1;
        asm volatile("bar.arrive 5, 128;" ::: "memory");
    }
    if (wg == 1 && wq < 3) {
        if (!which) m_partial(mo, wq, lane, (uint32_t)dsc & 1);
        const uint32_t off = piece_offset(which, which ? jlo : jlo + wq, which ? 3 * jhi + wq : jhi, lane);
        asm volatile("bar.sync %0, %1;" ::"r"(5 + (off >> 31)), "n"(128) : "memory");
        const uint32_t par = lds_volatile(s_par);
        if (which) asm volatile("bar.sync 8, 128;" ::: "memory");
        if (has_job && wq < 2 + which) {
            float d[2][4];
            if (wq == 0) TRX(which ? 1 : 18);
            if (which) {
                mbar_wait(bar_wop, 0);
                if (wq == 0) TRX(2);
                w_piece(wq, lane, d);
            } else {
                m_reduce(wq, lane, d);
            }
            piece_store(g, par, off, which, d);
            __syncwarp();
            piece_clear(g, 2 * kWBytes - par, off, which);
            if (wq == 0) TRX(which ? 3 : 0);
        }
        if (!which) asm volatile("bar.sync 8, 128;" ::: "memory");
        asm volatile("bar.arrive 7, 192;\nbar.arrive 6, 128;" ::: "memory");
    }
    const int order = w.step < 0 ? warp ^ 3 : warp;
    int tu = w.u, tv = w.v + w.step * wg;
    const int du2 = w.corner ? 8 : 0, dv2 = w.corner ? 0 : 2 * w.step;
    uint32_t o0, o1;
    wait_until(t_start, START_TIME);
    asm volatile("setmaxnreg.inc.sync.aligned.u32 240;");
    w.pixel_offsets(tu + r8, tv + 2 * wq, j, o0, o1);
    uint32_t fa[48];
    {
        RawX raw;
        load_raw(raw, x, o0, o1);
        asm volatile("bar.sync %0, 160;" ::"r"(3 + wg) : "memory");
        raw_to_frags(raw, 0, fa);
        pin(fa);
    }
    mbar_wait(bar_ok, 0);
    const uint64_t dA = dsc + wg * (kSlotStride >> 4), dB = dsc + (wg ^ 1) * (kSlotStride >> 4);

    float acc[96];
    uint32_t po[48];
    uint32_t c0, c1;
    asm volatile("" : "=r"(c0), "=r"(c1));
#pragma unroll
    for (int q = 0; q < 48; q++) asm volatile("" : "=r"(po[q]));
#pragma unroll 1
    for (int i = wg; i < w.ntiles; i += 2) {
        const bool first = i == 0, last = i == w.ntiles - 1;

        TRF(8 + 16 * k);
        uint8_t *p0 = out + c0, *p1 = out + c1;
#pragma unroll 1
        for (uint32_t seen = 0;;) {
        wg_fence();
        if (!first) turn_wait(wg);
        proj_gemm(acc, fa, dsc, s_m, [&](int s) {
            if (s == 11 && !first) turn_pass(wg);
            const int n = __builtin_popcount(QSLOTS & ((1 << s) - 1));
            if (((QSLOTS >> s) & 1) && n < 12) store_one(i >= 2, out + c0, out + c1, po, n);
            if (s == 3 || s == 7) { wg_commit(); mbar_wait(bar_img + 2 * s + 2, 0); wg_fence(); }
        });
        __syncwarp();
        TRF(9 + 16 * k);
            if (!first) break;
            mbar_wait(bar_ok + 16, 0);
            if (lds_volatile(s_again) == seen) break;
            wg_wait<0>();
            seen = 1;
        }
        c0 = o0; c1 = o1;
        w.pixel_offsets(tu + du2 + r8, tv + dv2 + 2 * wq, j, o0, o1);
        if (i + 2 >= w.ntiles) o0 = o1 = 0;
        mbar_wait(bar_a, w.corner ? i >> 1 : 0);
        wg_wait<2>();
        if (last && lane == 0) mbar_arrive(bar_free);
        wg_wait<1>();
        if (last && lane == 0) mbar_arrive(bar_free + 8);
        wg_wait<0>();
        if (last && lane == 0) mbar_arrive(bar_free + 16);
        const uint64_t dE = last ? dsc + ((s_m - s_ring) >> 4) : dsc, dN = last ? dE : dB;
        pin(acc);
        TR(11 + 16 * k);
        TRT(80 + k);
#pragma unroll
        for (int n = __builtin_popcount(QSLOTS); n < 12 - __builtin_popcount(ASLOTS) - __builtin_popcount(BSLOTS); n++) store_one(i >= 2, p0, p1, po, n);
        acc_to_frags(acc, fa);
        pin(fa);

        float sA[44], sE[16], sB[44];
        RawX nxt;
        if (!first) turn_wait(wg);
        wg_fence();
#pragma unroll
        for (int s = 0; s < 12; s++) {
            if (s == 0) wgmma_n88<true>(sA, fa[4 * s], fa[4 * s + 1], fa[4 * s + 2], fa[4 * s + 3], desc_at(dA, (s >> 2) * kRingChunk + (s & 3) * 32));
            else wgmma_n88<false>(sA, fa[4 * s], fa[4 * s + 1], fa[4 * s + 2], fa[4 * s + 3], desc_at(dA, (s >> 2) * kRingChunk + (s & 3) * 32));
            if (s == 11) { wg_commit(); if (!first) turn_pass(wg); }
            if ((ASLOTS >> s) & 1) store_one(i >= 2, p0, p1, po, 12 - __builtin_popcount(BSLOTS) - __builtin_popcount(ASLOTS >> s));
        }
#pragma unroll
        for (int s = 12; s < 16; s++)
            if ((ASLOTS >> s) & 1) store_one(i >= 2, p0, p1, po, 12 - __builtin_popcount(BSLOTS) - __builtin_popcount(ASLOTS >> s));
        TRF(12 + 16 * k);
        const int vq = tv + 2 * wq;
        const uint4 tabu = lds128(s_tab + offsetof(Table, u) + (window_start(tu + r8) - origin_u(tu)) * 64 + j * 16);
        const uint4 tabv = lds128(s_tab + offsetof(Table, v) + (window_start(vq) + window_start(vq + 1) - 2 * tv) * 64 + j * 16);
        const uint4 route = lds128(s_tab + lane * 16);
        load_raw(nxt, x, o0, o1);
        float v0[14], v1[14];
#pragma unroll
        for (int b = 0; b < 14; b++) {
            v0[b] = __uint_as_float((b > 10 ? route.x >> (b + 2) : 0u) | 0xff800000u);
            v1[b] = __uint_as_float((b > 10 ? route.x >> (b + 5) : 0u) | 0xff800000u);
        }
        wg_wait<0>();
        pin(sA);
        gather_outer(sA, tabu.x, tabv.x, v0, v1);
        pin(v0); pin(v1);
        if (!first) turn_wait(wg);
#pragma unroll
        for (int c = 0; c < 3; c++) {
            mbar_wait(bar_b + 8 * c, wg);
            TRF(64 + 4 * k + c);
            wg_fence();
#pragma unroll
            for (int s = 4 * c; s < 4 * c + 4; s++) {
                if (s == 0) wgmma_n88<true>(sB, fa[4 * s], fa[4 * s + 1], fa[4 * s + 2], fa[4 * s + 3], desc_at(dN, c * kRingChunk + (s & 3) * 32));
                else wgmma_n88<false>(sB, fa[4 * s], fa[4 * s + 1], fa[4 * s + 2], fa[4 * s + 3], desc_at(dN, c * kRingChunk + (s & 3) * 32));
                if ((BSLOTS >> s) & 1) store_one(i >= 2, p0, p1, po, 12 - __builtin_popcount(BSLOTS >> s));
            }
        }
        wg_commit();
#pragma unroll
        for (int s = 0; s < 12; s++)
            if (s == 0) wgmma_n32<true>(sE, fa[4 * s], fa[4 * s + 1], fa[4 * s + 2], fa[4 * s + 3], desc_at(dE, kOffMid + (s >> 2) * kRingChunk + (s & 3) * 32));
            else wgmma_n32<false>(sE, fa[4 * s], fa[4 * s + 1], fa[4 * s + 2], fa[4 * s + 3], desc_at(dE, kOffMid + (s >> 2) * kRingChunk + (s & 3) * 32));
        wg_commit();
        turn_pass(wg);
        TRF(13 + 16 * k);
        wg_wait<1>();
        pin(sB);
        gather_outer(sB, tabu.w, tabv.y, v0, v1);
        wg_wait<0>();
        pin(sE);
        TRF(14 + 16 * k);
        gather_mid(sE, tabu.w, tabv.z, v0, v1);
        const float m0 = quad_max(tree_max(v0)), m1 = quad_max(tree_max(v1));

        uint32_t y[14], pa[12], pb[12];
        exp_route<0, 14>(v0, v1, m0, m1, route, (j & 1) == 0, y);
        float s0 = tree_sum(v0), s1 = tree_sum(v1);
        asm volatile("" : "+f"(s0), "+f"(s1));
        unfold<0, 0, 6>(y, tabv.w, pa);
        turn_wait(wg + (y[0] >> 31));
        TRF(15 + 16 * k + (y[13] >> 31));
        wg_fence();
        wgmma_sp_n192_tb<true, 0>(acc, pa[0], pa[1], pa[2], pa[3], desc_at(dA, kToV), tabu.y);
        wgmma_sp_n192_tb<false, 1>(acc, pa[4], pa[5], pa[6], pa[7], desc_at(dA, kToV + 4096), tabu.y);
        wgmma_sp_n192_tb<false, 0>(acc, pa[8], pa[9], pa[10], pa[11], desc_at(dA, kToV + 8192), tabu.z);
        wgmma_sp_n192_tb<false, 1>(acc, j == 0 ? 0u : y[10], j == 0 ? 0u : y[11], y[12], y[13], desc_at(dE, kToV + kOffMid), tabu.z);
        wg_commit();
        unfold<8, 0, 6>(y, tabv.w, pb);
        wg_fence();
        wgmma_sp_n192_tb<false, 0>(acc, pb[0], pb[1], pb[2], pb[3], desc_at(dN, kToV), tabu.y);
        wgmma_sp_n192_tb<false, 1>(acc, pb[4], pb[5], pb[6], pb[7], desc_at(dN, kToV + 4096), tabu.y);
        wgmma_sp_n192_tb<false, 0>(acc, pb[8], pb[9], pb[10], pb[11], desc_at(dN, kToV + 8192), tabu.z);
        wg_commit();
        if (!last) turn_pass(wg);
        TRF(16 + 16 * k);
        wg_wait<1>();
        if (lane == 0) mbar_arrive(bar_use);
        TRF(17 + 16 * k);
        mbar_wait(bar_ok + 24, 0);
        wg_wait<0>();
        if (lane == 0) mbar_arrive(bar_use + 8);
        pin(acc);
        TR(18 + 16 * k);

        acc_to_frags(acc, po);
        pin(po);
        if (!last) turn_wait(wg);
        wg_fence();
        proj_gemm(acc, po, dsc, s_wv, [&](int s) {
            if (s + 1 == OSPLIT && i + 2 == w.ntiles) { turn_pass(wg); turn_wait(wg); }
        });
        if (!last) turn_pass(wg);
        TRF(19 + 16 * k);
        const uint32_t zero = lds_volatile(s_late);
        const float inv0 = rcp(quad_sum(s0 + __uint_as_float(zero))), inv1 = rcp(quad_sum(s1 + __uint_as_float(zero)));
        raw_to_frags(nxt, zero, fa);
        pin(fa);
#pragma unroll
        for (int q = 0; q < 48; q += 4) keep(wqkv == nullptr, fa[q], fa[q + 1], fa[q + 2], fa[q + 3]);
        keep(wqkv == nullptr, __float_as_uint(inv0), __float_as_uint(inv1), zero, lane);
        TRF(20 + 16 * k);
        tu += du2; tv += dv2;
        wg_wait<0>();
        pin(acc);
        TR(21 + 16 * k);
#pragma unroll
        for (int q = 0; q < 96; q++) acc[q] *= q & 2 ? inv1 : inv0;
        pack_out(acc, po);
#pragma unroll
        for (int n = 0; n < INLOOP; n++) store_one<false>(last, out + c0, out + c1, po, n);
        pin(po);
    }
#pragma unroll
    for (int n = 0; n < 12; n++) {
        asm volatile("{\n.reg .pred p;\nsetp.eq.u32 p, %0, 0;\n@p nanosleep.u32 %1;\n}\n" ::"r"(wg), "n"(NAP) : "memory");
        store_one<false>(n >= INLOOP || wg == 0, out + c0, out + c1, po, n);
    }
    TRE(7);
    TRG(1);
    TRDUMP();
}

typedef CUresult (*EncodeTiledFn)(CUtensorMap*, CUtensorMapDataType, cuuint32_t, void*, const cuuint64_t*, const cuuint64_t*,
                                  const cuuint32_t*, const cuuint32_t*, CUtensorMapInterleave, CUtensorMapSwizzle,
                                  CUtensorMapL2promotion, CUtensorMapFloatOOBfill);

bool make_maps(EncodeTiledFn fn, Maps* maps, void* x, void* wqkv, void* wo) {
    const cuuint64_t pix2 = 2 * kPixBytes, row = (cuuint64_t)kHW * kPixBytes;
    const cuuint32_t estr[5] = {1, 1, 1, 1, 1};
    bool ok = true;
    for (int tr = 0; tr < 2; tr++)
        for (int b = 0; b < 2; b++) {
            const cuuint64_t su = tr ? 2 * row : pix2, sv = tr ? pix2 : 2 * row;
            const cuuint64_t dims[5] = {2 * kC, 2, 105, 2, 112};
            const cuuint64_t strides[4] = {7 * su, su, row, sv};
            const cuuint32_t box[5] = {64, 2, 7, 1, b ? 2u : 6u};
            ok = ok && fn(&maps->m[2 * tr + b], CU_TENSOR_MAP_DATA_TYPE_BFLOAT16, 5, x, dims, strides, box, estr,
                          CU_TENSOR_MAP_INTERLEAVE_NONE, CU_TENSOR_MAP_SWIZZLE_128B, CU_TENSOR_MAP_L2_PROMOTION_L2_128B,
                          CU_TENSOR_MAP_FLOAT_OOB_FILL_NONE) == CUDA_SUCCESS;
        }
    for (int b = 0; b < 2; b++) {
        const cuuint64_t dims[3] = {b ? 64u : 48u, kC, b ? 9u : 4u}, strides[2] = {(b ? 3u : 1u) * kPixBytes, b ? 128u : 96u};
        const cuuint32_t box[3] = {b ? 64u : 48u, b ? 16u : 192u, b ? 3u : 1u};
        ok = ok && fn(b ? &maps->wv : &maps->wo, CU_TENSOR_MAP_DATA_TYPE_BFLOAT16, 3, b ? wqkv : wo, dims, strides, box, estr,
                      CU_TENSOR_MAP_INTERLEAVE_NONE, b ? CU_TENSOR_MAP_SWIZZLE_128B : CU_TENSOR_MAP_SWIZZLE_NONE, CU_TENSOR_MAP_L2_PROMOTION_L2_128B,
                      CU_TENSOR_MAP_FLOAT_OOB_FILL_NONE) == CUDA_SUCCESS;
    }
    return ok;
}

}

extern "C" void kernel_launch(void* const* d_in, const int* in_sizes, int n_in, void* d_out, int out_size) {
    static EncodeTiledFn encode = nullptr;
    static Scratch* scratch = nullptr;
    static Tables* tables = nullptr;
    if (!encode) {
        int dev = 0, reserved = 0;
        cudaFuncAttributes attr;
        cudaGetDevice(&dev);
        cudaDeviceGetAttribute(&reserved, cudaDevAttrReservedSharedMemoryPerBlock, dev);
        cudaFuncGetAttributes(&attr, nat_fused_kernel);
        if (reserved != (int)kSmemBase || attr.sharedSizeBytes != 0) return;
        cudaGetSymbolAddress((void**)&scratch, g_scratch);
        cudaGetSymbolAddress((void**)&tables, g_tables);
        void* fn = nullptr;
        cudaDriverEntryPointQueryResult st;
        cudaGetDriverEntryPoint("cuTensorMapEncodeTiled", &fn, cudaEnableDefault, &st);
        encode = (EncodeTiledFn)fn;
        cudaFuncSetAttribute(nat_fused_kernel, cudaFuncAttributeMaxDynamicSharedMemorySize, kSmemBytes);
    }
    Maps maps;
    maps.tables = tables;
    if (!encode || !make_maps(encode, &maps, d_in[0], d_in[1], d_in[2])) return;
    nat_fused_kernel<<<kGrid, kThreads, kSmemBytes>>>((const uint8_t*)d_in[0], (const uint8_t*)d_in[1], (uint8_t*)d_out, scratch, (const uint8_t*)d_in[2],
                                                      kDescRing, maps);
}
```

```cpp
#include <cuda_runtime.h>
#include <cuda_bf16.h>
#include <cuda.h>
#include <stdint.h>
#include <type_traits>
#include <stdlib.h>
#include <stdio.h>
#include <stddef.h>

#define ASLOTS 0x3800
#define BSLOTS 0x6
#define QSLOTS 0x78a
#define OSPLIT 2
#define NAP 40
#define INLOOP 2

namespace {

constexpr int kC          = 192;
constexpr int kHW         = 224;
constexpr int kPixBytes   = kC * 2;
constexpr int kSlotBytes  = 84 * 128;
constexpr int kMidBytes   = 28 * 128;
constexpr int kOffMid     = 88 * 128;
constexpr int kSlotStride = 120 * 128;
constexpr int kRingChunk  = 208 * 128;
constexpr int kWChunk     = 192 * 128;
constexpr int kWBytes     = 3 * kWChunk;
constexpr uint32_t kSmemBase = 1024;
constexpr uint32_t s_ring = kSmemBase, s_m = s_ring + 3 * kRingChunk, s_wv = s_m + kWBytes, s_bar = s_wv + kWBytes;
constexpr uint32_t bar_b = s_bar, bar_mid = s_bar + 24, bar_a = s_bar + 32, bar_img = s_bar + 40, bar_redo = s_bar + 88,
                   bar_wop = s_bar + 112, bar_ok = s_bar + 120, bar_use = s_bar + 144, bar_free = s_bar + 168;
constexpr uint32_t s_par = s_bar + 192, s_late = s_bar + 200, s_again = s_bar + 204, s_tab = s_bar + 256, s_trace = s_tab + 2048;
constexpr int kSmemBytes  = s_trace + 2048 - kSmemBase;
constexpr int kThreads    = 384;
constexpr int kGrid       = 132;
constexpr int kTimeM = 2500, kTimeW = 5100;
constexpr float kScaleLog2e = 0.07216878364870322f * 1.4426950408889634f;

struct Maps {
    CUtensorMap m[4];
    CUtensorMap wo, wv;
    const struct Tables* tables;
};
#define TN(i, dflt) (dflt)
#define START_TIME (wg ? 850 + 500 * order : 250 + 560 * order)

struct Scratch {
    uint8_t img[2][2][kWBytes];
    uint32_t launches[kGrid][32];
};
__device__ __align__(1024) Scratch g_scratch;

struct Table {
    uint32_t route[32][4];
    uint32_t u[8][4][4];
    uint32_t v[16][4][4];
};
struct Tables { Table t[2]; };
constexpr Tables make_tables() {
    Tables r = {};
    for (int rev = 0; rev < 2; rev++)
        for (int j = 0; j < 4; j++) {
            Table& t = r.t[rev];
            for (int q = 0; q < 8; q++) {
                uint32_t* e = t.route[4 * q + j];
                e[0] = 4 * q + 2 * (j & 1) + (j >> 1); e[1] = e[0] ^ 1;
                e[2] = j < 2 ? 0x5410u : 0x1054u; e[3] = e[2] + 0x2222u;
                e = t.u[q][j];
                for (int n = 0; n < 7; n++) e[0] |= ((n + j) % 7 < q ? 1u : 0u) << n;
                e[3] = e[0];
                for (int k = 0; k < 2; k++) {
                    const int step = 2 * k + (j >> 1), p0 = (step < 3 ? 16 * step : 40) + 8 * (j & 1);
                    uint32_t m = 0x8888u;
                    for (int n = 0; n < 8; n++) m |= ((p0 + n) % 7 < q ? 1u : 0u) << (2 * n);
                    e[1 + k] = m * 0x10001u;
                }
            }
            for (int sum = 0; sum < 15; sum++) {
                uint32_t* e = t.v[sum][j];
                for (int row = 0; row < 2; row++)
                    for (int b = 0; b < 14; b++) {
                        const int off = (sum + row) / 2, p = 4 * b + j;
                        const uint32_t bit = 1u << (2 * b + row);
                        if (p < 42 && p >= 7 * off) e[rev] |= bit;
                        if (p < 7 * off - 7) e[1 - rev] |= bit;
                        if (p >= 42 && p >= 7 * off && p < 7 * off + 49) e[2] |= bit;
                    }
                for (int n = 0; n < 6; n++)
                    if (8 * n + 2 * j < 42) e[3] |= 1u << (n + ((8 * n + 2 * j >= 7 * (sum / 2 & ~1)) != rev ? 0 : 8));
            }
        }
    return r;
}
__device__ __align__(128) const Tables g_tables = make_tables();

#define WO4(i) "=f"(d[i]), "=f"(d[i + 1]), "=f"(d[i + 2]), "=f"(d[i + 3])
#define RW4(i) "+f"(d[i]), "+f"(d[i + 1]), "+f"(d[i + 2]), "+f"(d[i + 3])

template <bool FIRST>
__device__ __forceinline__ void wgmma_n192(float (&d)[96], uint32_t a0, uint32_t a1, uint32_t a2, uint32_t a3, uint64_t descb) {
    if constexpr (FIRST) {
        asm volatile(
            "wgmma.mma_async.sync.aligned.m64n192k16.f32.bf16.bf16 "
            "{%0, %1, %2, %3, %4, %5, %6, %7, %8, %9, %10, %11, %12, %13, %14, %15, %16, %17, %18, %19, %20, %21, %22, %23, "
            "%24, %25, %26, %27, %28, %29, %30, %31, %32, %33, %34, %35, %36, %37, %38, %39, %40, %41, %42, %43, %44, %45, %46, %47, "
            "%48, %49, %50, %51, %52, %53, %54, %55, %56, %57, %58, %59, %60, %61, %62, %63, %64, %65, %66, %67, %68, %69, %70, %71, "
            "%72, %73, %74, %75, %76, %77, %78, %79, %80, %81, %82, %83, %84, %85, %86, %87, %88, %89, %90, %91, %92, %93, %94, %95}, "
            "{%96, %97, %98, %99}, %100, 0, 1, 1, 0;"
            : WO4(0), WO4(4), WO4(8), WO4(12), WO4(16), WO4(20), WO4(24), WO4(28), WO4(32), WO4(36), WO4(40), WO4(44),
              WO4(48), WO4(52), WO4(56), WO4(60), WO4(64), WO4(68), WO4(72), WO4(76), WO4(80), WO4(84), WO4(88), WO4(92)
            : "r"(a0), "r"(a1), "r"(a2), "r"(a3), "l"(descb));
    } else {
        asm volatile(
            "wgmma.mma_async.sync.aligned.m64n192k16.f32.bf16.bf16 "
            "{%0, %1, %2, %3, %4, %5, %6, %7, %8, %9, %10, %11, %12, %13, %14, %15, %16, %17, %18, %19, %20, %21, %22, %23, "
            "%24, %25, %26, %27, %28, %29, %30, %31, %32, %33, %34, %35, %36, %37, %38, %39, %40, %41, %42, %43, %44, %45, %46, %47, "
            "%48, %49, %50, %51, %52, %53, %54, %55, %56, %57, %58, %59, %60, %61, %62, %63, %64, %65, %66, %67, %68, %69, %70, %71, "
            "%72, %73, %74, %75, %76, %77, %78, %79, %80, %81, %82, %83, %84, %85, %86, %87, %88, %89, %90, %91, %92, %93, %94, %95}, "
            "{%96, %97, %98, %99}, %100, 1, 1, 1, 0;"
            : RW4(0), RW4(4), RW4(8), RW4(12), RW4(16), RW4(20), RW4(24), RW4(28), RW4(32), RW4(36), RW4(40), RW4(44),
              RW4(48), RW4(52), RW4(56), RW4(60), RW4(64), RW4(68), RW4(72), RW4(76), RW4(80), RW4(84), RW4(88), RW4(92)
            : "r"(a0), "r"(a1), "r"(a2), "r"(a3), "l"(descb));
    }
}

template <bool FIRST>
__device__ __forceinline__ void wgmma_n88(float (&d)[44], uint32_t a0, uint32_t a1, uint32_t a2, uint32_t a3, uint64_t descb) {
    if constexpr (FIRST) {
        asm volatile(
            "wgmma.mma_async.sync.aligned.m64n88k16.f32.bf16.bf16 "
            "{%0, %1, %2, %3, %4, %5, %6, %7, %8, %9, %10, %11, %12, %13, %14, %15, %16, %17, %18, %19, %20, %21, %22, %23, "
            "%24, %25, %26, %27, %28, %29, %30, %31, %32, %33, %34, %35, %36, %37, %38, %39, %40, %41, %42, %43}, "
            "{%44, %45, %46, %47}, %48, 0, 1, 1, 0;"
            : WO4(0), WO4(4), WO4(8), WO4(12), WO4(16), WO4(20), WO4(24), WO4(28), WO4(32), WO4(36), WO4(40)
            : "r"(a0), "r"(a1), "r"(a2), "r"(a3), "l"(descb));
    } else {
        asm volatile(
            "wgmma.mma_async.sync.aligned.m64n88k16.f32.bf16.bf16 "
            "{%0, %1, %2, %3, %4, %5, %6, %7, %8, %9, %10, %11, %12, %13, %14, %15, %16, %17, %18, %19, %20, %21, %22, %23, "
            "%24, %25, %26, %27, %28, %29, %30, %31, %32, %33, %34, %35, %36, %37, %38, %39, %40, %41, %42, %43}, "
            "{%44, %45, %46, %47}, %48, 1, 1, 1, 0;"
            : RW4(0), RW4(4), RW4(8), RW4(12), RW4(16), RW4(20), RW4(24), RW4(28), RW4(32), RW4(36), RW4(40)
            : "r"(a0), "r"(a1), "r"(a2), "r"(a3), "l"(descb));
    }
}

template <bool FIRST>
__device__ __forceinline__ void wgmma_n32(float (&d)[16], uint32_t a0, uint32_t a1, uint32_t a2, uint32_t a3, uint64_t descb) {
    if constexpr (FIRST) {
        asm volatile(
            "wgmma.mma_async.sync.aligned.m64n32k16.f32.bf16.bf16 "
            "{%0, %1, %2, %3, %4, %5, %6, %7, %8, %9, %10, %11, %12, %13, %14, %15}, "
            "{%16, %17, %18, %19}, %20, 0, 1, 1, 0;"
            : WO4(0), WO4(4), WO4(8), WO4(12)
            : "r"(a0), "r"(a1), "r"(a2), "r"(a3), "l"(descb));
    } else {
        asm volatile(
            "wgmma.mma_async.sync.aligned.m64n32k16.f32.bf16.bf16 "
            "{%0, %1, %2, %3, %4, %5, %6, %7, %8, %9, %10, %11, %12, %13, %14, %15}, "
            "{%16, %17, %18, %19}, %20, 1, 1, 1, 0;"
            : RW4(0), RW4(4), RW4(8), RW4(12)
            : "r"(a0), "r"(a1), "r"(a2), "r"(a3), "l"(descb));
    }
}

template <bool FIRST, int SEL>
__device__ __forceinline__ void wgmma_sp_n192_tb(float (&d)[96], uint32_t a0, uint32_t a1, uint32_t a2, uint32_t a3, uint64_t descb, uint32_t meta) {
    if constexpr (FIRST) {
        asm volatile(
            "wgmma.mma_async.sp.sync.aligned.m64n192k32.f32.bf16.bf16 "
            "{%0, %1, %2, %3, %4, %5, %6, %7, %8, %9, %10, %11, %12, %13, %14, %15, %16, %17, %18, %19, %20, %21, %22, %23, "
            "%24, %25, %26, %27, %28, %29, %30, %31, %32, %33, %34, %35, %36, %37, %38, %39, %40, %41, %42, %43, %44, %45, %46, %47, "
            "%48, %49, %50, %51, %52, %53, %54, %55, %56, %57, %58, %59, %60, %61, %62, %63, %64, %65, %66, %67, %68, %69, %70, %71, "
            "%72, %73, %74, %75, %76, %77, %78, %79, %80, %81, %82, %83, %84, %85, %86, %87, %88, %89, %90, %91, %92, %93, %94, %95}, "
            "{%96, %97, %98, %99}, %100, %101, %102, 0, 1, 1, 1;"
            : WO4(0), WO4(4), WO4(8), WO4(12), WO4(16), WO4(20), WO4(24), WO4(28), WO4(32), WO4(36), WO4(40), WO4(44),
              WO4(48), WO4(52), WO4(56), WO4(60), WO4(64), WO4(68), WO4(72), WO4(76), WO4(80), WO4(84), WO4(88), WO4(92)
            : "r"(a0), "r"(a1), "r"(a2), "r"(a3), "l"(descb), "r"(meta), "n"(SEL));
    } else {
        asm volatile(
            "wgmma.mma_async.sp.sync.aligned.m64n192k32.f32.bf16.bf16 "
            "{%0, %1, %2, %3, %4, %5, %6, %7, %8, %9, %10, %11, %12, %13, %14, %15, %16, %17, %18, %19, %20, %21, %22, %23, "
            "%24, %25, %26, %27, %28, %29, %30, %31, %32, %33, %34, %35, %36, %37, %38, %39, %40, %41, %42, %43, %44, %45, %46, %47, "
            "%48, %49, %50, %51, %52, %53, %54, %55, %56, %57, %58, %59, %60, %61, %62, %63, %64, %65, %66, %67, %68, %69, %70, %71, "
            "%72, %73, %74, %75, %76, %77, %78, %79, %80, %81, %82, %83, %84, %85, %86, %87, %88, %89, %90, %91, %92, %93, %94, %95}, "
            "{%96, %97, %98, %99}, %100, %101, %102, 1, 1, 1, 1;"
            : RW4(0), RW4(4), RW4(8), RW4(12), RW4(16), RW4(20), RW4(24), RW4(28), RW4(32), RW4(36), RW4(40), RW4(44),
              RW4(48), RW4(52), RW4(56), RW4(60), RW4(64), RW4(68), RW4(72), RW4(76), RW4(80), RW4(84), RW4(88), RW4(92)
            : "r"(a0), "r"(a1), "r"(a2), "r"(a3), "l"(descb), "r"(meta), "n"(SEL));
    }
}

#define TR(slot)
#define TRX(slot)
#define TRE(slot)
#define TRT(slot)
#define TRF(slot)
#define TRW(slot)
#define TRG(slot)
#define TRDUMP()

__device__ __forceinline__ void wg_fence() { asm volatile("wgmma.fence.sync.aligned;" ::: "memory"); }
__device__ __forceinline__ void wg_commit() { asm volatile("wgmma.commit_group.sync.aligned;" ::: "memory"); }
template <int N>
__device__ __forceinline__ void wg_wait() { asm volatile("wgmma.wait_group.sync.aligned %0;" ::"n"(N) : "memory"); }

template <int N>
__device__ __forceinline__ void pin(float (&d)[N]) {
#pragma unroll
    for (int i = 0; i < N; i++) asm volatile("" : "+f"(d[i])::"memory");
}
template <int N>
__device__ __forceinline__ void pin(uint32_t (&d)[N]) {
#pragma unroll
    for (int i = 0; i < N; i++) asm volatile("" : "+r"(d[i])::"memory");
}

constexpr uint64_t kDescRing = ((uint64_t)((1u << 30) | (1024u >> 4)) << 32) | (1u << 16) | (s_ring >> 4);
constexpr uint32_t kToV = ((kRingChunk >> 4) - 1) << 20;
__device__ __forceinline__ uint64_t desc_at(uint64_t base, uint32_t byte_off) {
    uint64_t d;
    asm volatile("add.s64 %0, %1, %2;" : "=l"(d) : "l"(base), "l"((uint64_t)(byte_off >> 4)));
    return d;
}

__device__ __forceinline__ void mbar_init(uint32_t bar, uint32_t count) {
    asm volatile("mbarrier.init.shared::cta.b64 [%0], %1;" ::"r"(bar), "r"(count) : "memory");
}
__device__ __forceinline__ void mbar_expect_tx(uint32_t bar, uint32_t bytes) {
    asm volatile("mbarrier.arrive.expect_tx.shared::cta.b64 _, [%0], %1;" ::"r"(bar), "r"(bytes) : "memory");
}
__device__ __forceinline__ void expect_tx_only(uint32_t bar, uint32_t bytes) {
    asm volatile("mbarrier.expect_tx.relaxed.cta.shared::cta.b64 [%0], %1;" ::"r"(bar), "r"(bytes) : "memory");
}
__device__ __forceinline__ void mbar_arrive(uint32_t bar) {
    asm volatile("mbarrier.arrive.shared::cta.b64 _, [%0];" ::"r"(bar) : "memory");
}
__device__ __forceinline__ void mbar_wait(uint32_t bar, uint32_t parity) {
    asm volatile(
        "{\n.reg .pred p;\n"
        "W: mbarrier.try_wait.parity.shared::cta.b64 p, [%0], %1;\n"
        "@!p bra W;\n}\n"
        ::"r"(bar), "r"(parity) : "memory");
}
__device__ __forceinline__ uint32_t clock_now() {
    uint32_t c;
    asm volatile("mov.u32 %0, %%clock;" : "=r"(c)::"memory");
    return c;
}
__device__ __forceinline__ void wait_until(uint32_t t0, int t) {
    if (t == 0) return;
    while ((int)(clock_now() - t0) < t) {}
}
__device__ __forceinline__ bool elect() {
    uint32_t ok;
    asm volatile("{\n.reg .pred p;\nelect.sync _|p, 0xffffffff;\nselp.u32 %0, 1, 0, p;\n}\n" : "=r"(ok));
    return ok != 0;
}
__device__ __forceinline__ void turn_wait(int wg) { asm volatile("bar.sync %0, 256;" ::"r"(1 + wg) : "memory"); }
__device__ __forceinline__ void turn_pass(int wg) { asm volatile("bar.arrive %0, 256;" ::"r"(2 - wg) : "memory"); }

__device__ __forceinline__ void tma_box(uint32_t dst, const CUtensorMap* map, uint32_t bar, int c0, int c2, int c3, int c4) {
    asm volatile(
        "cp.async.bulk.tensor.5d.shared::cluster.global.mbarrier::complete_tx::bytes [%0], [%1, {%3, %4, %5, %6, %7}], [%2];"
        ::"r"(dst), "l"(map), "r"(bar), "r"(c0), "r"(0), "r"(c2), "r"(c3), "r"(c4)
        : "memory");
}
__device__ __forceinline__ void tma_3d(uint32_t dst, const CUtensorMap* map, uint32_t bar, int c1, int c2) {
    asm volatile("cp.async.bulk.tensor.3d.shared::cluster.global.mbarrier::complete_tx::bytes [%0], [%1, {%3, %4, %5}], [%2];"
                 ::"r"(dst), "l"(map), "r"(bar), "r"(0), "r"(c1), "r"(c2)
                 : "memory");
}
__device__ __forceinline__ void prefetch_map(const CUtensorMap* map) {
    asm volatile("prefetch.tensormap [%0];" ::"l"(map) : "memory");
}
__device__ __forceinline__ uint4 ldg(const void* p) {
    uint4 v;
    asm volatile("ld.global.v4.u32 {%0, %1, %2, %3}, [%4];" : "=r"(v.x), "=r"(v.y), "=r"(v.z), "=r"(v.w) : "l"(p) : "memory");
    return v;
}
__device__ __forceinline__ uint32_t pack_bf16(float lo, float hi) {
    uint32_t r;
    asm("cvt.rn.bf16x2.f32 %0, %1, %2;" : "=r"(r) : "f"(hi), "f"(lo));
    return r;
}
__device__ __forceinline__ float ex2(float x) {
    float y;
    asm("ex2.approx.ftz.f32 %0, %1;" : "=f"(y) : "f"(x));
    return y;
}
__device__ __forceinline__ float rcp(float x) {
    float y;
    asm("rcp.approx.ftz.f32 %0, %1;" : "=f"(y) : "f"(x));
    return y;
}
__device__ __forceinline__ void mma16816(float (&d)[4], uint32_t a0, uint32_t a1, uint32_t a2, uint32_t a3, uint32_t b0, uint32_t b1) {
    asm volatile("mma.sync.aligned.m16n8k16.row.col.f32.bf16.bf16.f32 {%0, %1, %2, %3}, {%4, %5, %6, %7}, {%8, %9}, {%0, %1, %2, %3};"
                 : "+f"(d[0]), "+f"(d[1]), "+f"(d[2]), "+f"(d[3])
                 : "r"(a0), "r"(a1), "r"(a2), "r"(a3), "r"(b0), "r"(b1));
}
__device__ __forceinline__ uint4 lds128(uint32_t addr) {
    uint4 v;
    asm volatile("ld.volatile.shared.v4.u32 {%0, %1, %2, %3}, [%4];" : "=r"(v.x), "=r"(v.y), "=r"(v.z), "=r"(v.w) : "r"(addr) : "memory");
    return v;
}
__device__ __forceinline__ uint32_t lds_volatile(uint32_t addr) {
    uint32_t v;
    asm volatile("ld.volatile.shared.u32 %0, [%1];" : "=r"(v) : "r"(addr) : "memory");
    return v;
}

__device__ __forceinline__ int window_start(int n) { return min(max(n, 0), 105); }
__device__ __forceinline__ int origin_u(int u) { return min(max(u, 0), 98); }

struct Work {
    int u, v;
    int step;
    uint32_t su, sv;
    uint32_t base;
    bool corner;
    int ntiles;
    __device__ __forceinline__ void pixel_offsets(int qu, int qv, int j, uint32_t& o0, uint32_t& o1) const {
        const uint32_t b = (qu + window_start(qu)) * su + j * 16 + base;
        o0 = b + (qv + window_start(qv)) * sv;
        o1 = b + (qv + 1 + window_start(qv + 1)) * sv;
    }
};

__device__ __forceinline__ Work decode_work(int c) {
    Work w;
    const bool transposed = (c >> 4) == 7;
    const int px = 6 * (c & 1), py = 3 * (c & 2);
    w.corner = c >= 128;
    w.step = 8 - 4 * (c & 4);
    w.u = (c < 112 ? c & ~7 : 96 + (c & 8)) + (transposed ? py : px) - 6;
    w.v = (w.corner ? 96 : 48 - 2 * (c & 4)) + (transposed ? px : py) - 6;
    w.su = transposed ? kHW * kPixBytes : kPixBytes;
    w.sv = transposed ? kPixBytes : kHW * kPixBytes;
    w.base = px * (kPixBytes / 6) + py * (kHW * kPixBytes / 6) + 6 * (kHW + 1) * kPixBytes;
    w.ntiles = w.corner ? 4 : 6;
    return w;
}

struct RawX { uint4 a[6], b[6]; };
__device__ __forceinline__ void load_raw(RawX& r, const uint8_t* base, uint32_t o0, uint32_t o1) {
    __syncwarp();
#pragma unroll
    for (int c = 0; c < 6; c++) { r.a[c] = ldg(base + o0 + c * 64); r.b[c] = ldg(base + o1 + c * 64); }
    __syncwarp();
}
__device__ __forceinline__ void raw_to_frags(const RawX& r, uint32_t zero, uint32_t (&f)[48]) {
#pragma unroll
    for (int c = 0; c < 6; c++) {
        asm volatile("{\n.reg .b32 t, u;\nadd.u32 t, %4, %8;\nadd.u32 u, %5, %8;\nxor.b32 %0, %6, %8;\nxor.b32 %1, %7, %8;\n"
                     "xor.b32 %2, t, %8;\nxor.b32 %3, u, %8;\n}\n"
                     : "=&r"(f[8 * c + 1]), "=&r"(f[8 * c + 3]), "=&r"(f[8 * c + 4]), "=&r"(f[8 * c + 6])
                     : "r"(r.a[c].y), "r"(r.a[c].w), "r"(r.b[c].x), "r"(r.b[c].z), "r"(zero));
        f[8 * c + 0] = r.a[c].x; f[8 * c + 2] = r.a[c].z; f[8 * c + 5] = r.b[c].y; f[8 * c + 7] = r.b[c].w;
    }
}
__device__ __forceinline__ void acc_to_frags(const float (&d)[96], uint32_t (&f)[48]) {
#pragma unroll
    for (int i = 0; i < 48; i++) f[i] = pack_bf16(d[2 * i], d[2 * i + 1]);
}

template <class F>
__device__ __forceinline__ void proj_gemm(float (&d)[96], const uint32_t (&a)[48], uint64_t dsc, uint32_t img, F after) {
#pragma unroll
    for (int s = 0; s < 12; s++) {
        if (s == 0) wgmma_n192<true>(d, a[4 * s], a[4 * s + 1], a[4 * s + 2], a[4 * s + 3], desc_at(dsc, img - s_ring + (s >> 2) * kWChunk + (s & 3) * 32));
        else wgmma_n192<false>(d, a[4 * s], a[4 * s + 1], a[4 * s + 2], a[4 * s + 3], desc_at(dsc, img - s_ring + (s >> 2) * kWChunk + (s & 3) * 32));
        if (s == 11) wg_commit();
        after(s);
    }
}
__device__ __forceinline__ void pack_out(const float (&acc)[96], uint32_t (&po)[48]) {
#pragma unroll
    for (int g = 0; g < 6; g++)
#pragma unroll
        for (int q = 0; q < 4; q++) {
            po[8 * g + q] = pack_bf16(acc[16 * g + 4 * q], acc[16 * g + 4 * q + 1]);
            po[8 * g + 4 + q] = pack_bf16(acc[16 * g + 4 * q + 2], acc[16 * g + 4 * q + 3]);
        }
}
template <bool PINNED = true>
__device__ __forceinline__ void store_one(bool on, uint8_t* p0, uint8_t* p1, const uint32_t (&po)[48], int n) {
    if (PINNED) __syncwarp();
    asm volatile("{\n.reg .pred p;\nsetp.ne.u32 p, %5, 0;\n@p st.global.v4.u32 [%0], {%1, %2, %3, %4};\n}\n"
                 ::"l"(((n & 1) ? p1 : p0) + (n >> 1) * 64), "r"(po[4 * n]), "r"(po[4 * n + 1]), "r"(po[4 * n + 2]), "r"(po[4 * n + 3]), "r"((uint32_t)on) : "memory");
}

template <int N>
__device__ __forceinline__ float tree_max(const float (&v)[N]) {
    float t[N];
#pragma unroll
    for (int i = 0; i < N; i++) t[i] = v[i];
#pragma unroll
    for (int w = 1; w < N; w *= 2)
#pragma unroll
        for (int i = 0; i + w < N; i += 2 * w) t[i] = fmaxf(t[i], t[i + w]);
    return t[0];
}
template <int N>
__device__ __forceinline__ float tree_sum(const float (&v)[N]) {
    float t[N];
#pragma unroll
    for (int i = 0; i < N; i++) t[i] = v[i];
#pragma unroll
    for (int w = 1; w < N; w *= 2)
#pragma unroll
        for (int i = 0; i + w < N; i += 2 * w) t[i] += t[i + w];
    return t[0];
}

template <int B>
__device__ __forceinline__ void pick(uint32_t h, uint32_t ok, const float* s, float& v0, float& v1) {
    asm("{\n.reg .pred p, q0, q1;\n.reg .b32 t;\nand.b32 t, %6, %7;\nsetp.ne.u32 p, t, 0;\n"
        "and.b32 t, %8, %9;\nsetp.ne.u32 q0, t, 0;\nand.b32 t, %8, %10;\nsetp.ne.u32 q1, t, 0;\n"
        "@q0 selp.f32 %0, %3, %2, p;\n@q1 selp.f32 %1, %5, %4, p;\n}\n"
        : "+f"(v0), "+f"(v1)
        : "f"(s[0]), "f"(s[1]), "f"(s[2]), "f"(s[3]), "r"(h), "n"(1 << ((4 * B) % 7)), "r"(ok), "n"(1 << (2 * B)), "n"(2 << (2 * B)));
}
template <int B, class F>
__device__ __forceinline__ void for_blocks(F f) {
    if constexpr (B > 0) { for_blocks<B - 1>(f); f(std::integral_constant<int, B - 1>{}); }
}
__device__ __forceinline__ void gather_outer(const float (&s)[44], uint32_t h, uint32_t ok, float (&v0)[14], float (&v1)[14]) {
    for_blocks<11>([&](auto B) {
        constexpr int b = B.value < 8 ? (B.value >> 1) + 7 * (B.value & 1) : B.value - 4;
        pick<b>(h, ok, &s[4 * b], v0[b], v1[b]);
    });
}
__device__ __forceinline__ void gather_mid(const float (&sE)[16], uint32_t h, uint32_t ok, float (&v0)[14], float (&v1)[14]) {
    for_blocks<4>([&](auto B) { pick<10 + B.value>(h, ok, &sE[4 * B.value], v0[10 + B.value], v1[10 + B.value]); });
}
__device__ __forceinline__ float quad_max(float m) {
    m = fmaxf(m, __shfl_xor_sync(0xffffffffu, m, 1));
    return fmaxf(m, __shfl_xor_sync(0xffffffffu, m, 2));
}
__device__ __forceinline__ float quad_sum(float s) {
    s += __shfl_xor_sync(0xffffffffu, s, 1);
    return s + __shfl_xor_sync(0xffffffffu, s, 2);
}
template <int B0, int B1>
__device__ __forceinline__ void exp_route(float (&v0)[14], float (&v1)[14], float m0, float m1, const uint4& r, bool even, uint32_t (&y)[14]) {
#pragma unroll
    for (int b = B0; b < B1; b++) { v0[b] = ex2(v0[b] - m0); v1[b] = ex2(v1[b] - m1); }
#pragma unroll
    for (int b = B0; b < B1; b += 2) {
        const uint32_t x0 = pack_bf16(v0[b], v1[b]), x1 = pack_bf16(v0[b + 1], v1[b + 1]);
        const uint32_t u = __shfl_sync(0xffffffffu, even ? x0 : x1, r.x);
        const uint32_t w = __shfl_sync(0xffffffffu, even ? x1 : x0, r.y);
        y[b] = __byte_perm(u, w, r.z); y[b + 1] = __byte_perm(u, w, r.w);
    }
}
template <int BIT0, int N0, int N1>
__device__ __forceinline__ void unfold(const uint32_t (&y)[14], uint32_t fold, uint32_t (&p)[12]) {
    for_blocks<N1 - N0>([&](auto N) {
        constexpr int n = N0 + N.value;
        asm("{\n.reg .pred p;\n.reg .b32 t;\nand.b32 t, %4, %5;\nsetp.ne.u32 p, t, 0;\nselp.b32 %0, %2, 0, p;\nselp.b32 %1, %3, 0, p;\n}\n"
            : "=r"(p[2 * n]), "=r"(p[2 * n + 1]) : "r"(y[2 * n]), "r"(y[2 * n + 1]), "r"(fold), "n"(1 << (BIT0 + n)));
    });
}
__device__ __forceinline__ void keep(bool never, uint32_t a, uint32_t b, uint32_t c, uint32_t d) {
    asm volatile("{\n.reg .pred p;\nsetp.ne.u32 p, %4, 0;\n@p st.volatile.shared.v4.u32 [%5], {%0, %1, %2, %3};\n}\n"
                 ::"r"(a), "r"(b), "r"(c), "r"(d), "r"((uint32_t)never), "r"(s_trace) : "memory");
}

__device__ __forceinline__ uint32_t wimg_offset(uint32_t row, uint32_t s, uint32_t j) {
    return (s >> 2) * kWChunk + row * 128 + (((2 * (s & 3) + (j >> 1)) ^ (row & 7)) << 4) + (j & 1) * 8;
}

__device__ __forceinline__ void ldsm4(uint32_t (&r)[4], uint32_t addr) {
    asm volatile("ldmatrix.sync.aligned.m8n8.x4.shared.b16 {%0, %1, %2, %3}, [%4];" : "=r"(r[0]), "=r"(r[1]), "=r"(r[2]), "=r"(r[3]) : "r"(addr) : "memory");
}
__device__ __forceinline__ void ldsm4_t(uint32_t (&r)[4], uint32_t addr) {
    asm volatile("ldmatrix.sync.aligned.m8n8.x4.trans.shared.b16 {%0, %1, %2, %3}, [%4];" : "=r"(r[0]), "=r"(r[1]), "=r"(r[2]), "=r"(r[3]) : "r"(addr) : "memory");
}
struct MOperands { uint4 A[2][2], B[4][2]; };
__device__ __forceinline__ void m_load(MOperands& m, const uint8_t* wqkv, uint32_t mt, uint32_t s, uint32_t q, uint32_t lane) {
    const uint32_t r8 = lane >> 2, col = q * 128 + (lane & 3) * 16;
    const uint8_t* pa = wqkv + (16 * mt + r8) * 1152 + col;
    const uint8_t* pb = wqkv + (16 * s + 8 * (r8 & 2) + (r8 & 5)) * 1152 + col;
#pragma unroll
    for (int c = 0; c < 2; c++) {
#pragma unroll
        for (int h = 0; h < 2; h++) m.A[h][c] = ldg(pa + 384 + h * 8 * 1152 + c * 64);
#pragma unroll
        for (int n = 0; n < 4; n++) m.B[n][c] = ldg(pb + ((n & 1) * 8 + (n & 2)) * 1152 + c * 64);
    }
}
__device__ __forceinline__ void m_partial(MOperands& m, uint32_t q, uint32_t lane, uint32_t zero) {
    auto& A = m.A;
    auto& B = m.B;
#pragma unroll
    for (int i = 0; i < 4; i++) { uint4& a = A[i >> 1][i & 1]; a.x ^= zero; a.y ^= zero; a.z ^= zero; a.w ^= zero; }
#pragma unroll
    for (int n = 0; n < 4; n++) {
        float d[4] = {0.f, 0.f, 0.f, 0.f};
#pragma unroll
        for (int c = 0; c < 2; c++) {
            mma16816(d, A[0][c].x, A[1][c].x, A[0][c].y, A[1][c].y, B[n][c].x, B[n][c].y);
            mma16816(d, A[0][c].z, A[1][c].z, A[0][c].w, A[1][c].w, B[n][c].z, B[n][c].w);
        }
        asm volatile("st.shared.v4.f32 [%0], {%1, %2, %3, %4};" ::"r"(s_wv + q * 2048 + n * 512 + lane * 16), "f"(d[0]), "f"(d[1]), "f"(d[2]), "f"(d[3]) : "memory");
    }
}
__device__ __forceinline__ void m_reduce(uint32_t e, uint32_t lane, float (&d)[2][4]) {
#pragma unroll
    for (int n = 0; n < 2; n++) {
        float t[3][4];
#pragma unroll
        for (int q = 0; q < 3; q++)
            asm volatile("ld.shared.v4.f32 {%0, %1, %2, %3}, [%4];" : "=f"(t[q][0]), "=f"(t[q][1]), "=f"(t[q][2]), "=f"(t[q][3]) : "r"(s_wv + q * 2048 + e * 1024 + n * 512 + lane * 16) : "memory");
#pragma unroll
        for (int i = 0; i < 4; i++) d[n][i] = (t[0][i] + t[1][i] + t[2][i]) * kScaleLog2e;
    }
}
__device__ __forceinline__ void w_piece(uint32_t q, uint32_t lane, float (&d)[2][4]) {
    const uint32_t rr = lane & 7, mi = lane >> 3, kr = 4 * (rr >> 1) + (mi & 2) + (rr & 1);
    const uint32_t pa = s_wv + q * 32 + (4 * (mi & 2) + rr) * 96 + ((mi & 1) << 4);
    const uint32_t pb = s_wv + 3 * 6144 + kr * 128 + (((mi & 1) ^ (kr & 7)) << 4);
    float e[2][4];
#pragma unroll
    for (int i = 0; i < 8; i++) (&d[0][0])[i] = (&e[0][0])[i] = 0.f;
#pragma unroll
    for (int k = 0; k < 12; k++) {
        uint32_t aq[4], bq[4];
        ldsm4_t(aq, pa + k * 1536);
        ldsm4(bq, (pb ^ ((k & 3) << 5)) + (k >> 2) * 2048);
        mma16816(k & 1 ? e[0] : d[0], aq[0], aq[1], aq[2], aq[3], bq[0], bq[1]);
        mma16816(k & 1 ? e[1] : d[1], aq[0], aq[1], aq[2], aq[3], bq[2], bq[3]);
    }
#pragma unroll
    for (int i = 0; i < 8; i++) (&d[0][0])[i] += (&e[0][0])[i];
}
__device__ __forceinline__ uint32_t piece_offset(uint32_t which, uint32_t s, uint32_t mt, uint32_t lane) {
    const uint32_t r8 = lane >> 2;
    return which * kWBytes + wimg_offset(which ? 32 * (mt >> 1) + 8 * (r8 >> 1) + 4 * (mt & 1) + (r8 & 1) : 16 * mt + r8, s, lane & 3);
}
__device__ __forceinline__ void piece_store(Scratch* g, uint32_t par, uint32_t off0, uint32_t which, const float (&d)[2][4]) {
#pragma unroll
    for (int hf = 0; hf < 2; hf++) {
        const uint32_t off = off0 ^ (hf ? which ? 288 : 1024 : 0);
        const uint32_t a = pack_bf16(d[0][2 * hf], d[0][2 * hf + 1]), b = pack_bf16(d[1][2 * hf], d[1][2 * hf + 1]);
        asm volatile("st.relaxed.gpu.global.v2.u32 [%0], {%1, %2};" ::"l"(g->img[0][0] + (par + off)), "r"(a ? a : 0x8000u), "r"(b) : "memory");
    }
}
__device__ __forceinline__ void piece_clear(Scratch* g, uint32_t par, uint32_t off0, uint32_t which) {
#pragma unroll
    for (int hf = 0; hf < 2; hf++)
        asm volatile("st.relaxed.gpu.global.v2.u32 [%0], {%1, %1};" ::"l"(g->img[0][0] + (par + (off0 ^ (hf ? which ? 288 : 1024 : 0)))), "r"(0) : "memory");
}

__device__ __forceinline__ uint32_t ld_relaxed(const uint32_t* p) {
    uint32_t v;
    asm volatile("ld.relaxed.gpu.global.u32 %0, [%1];" : "=r"(v) : "l"(p) : "memory");
    return v;
}
__device__ __forceinline__ void count_up(uint32_t* p) {
    asm volatile("red.relaxed.gpu.global.add.u32 [%0], %1;" ::"l"(p), "r"(1) : "memory");
}
__device__ __forceinline__ void bulk_g2s(uint32_t dst, const void* src, uint32_t bytes, uint32_t bar) {
    asm volatile("cp.async.bulk.shared::cluster.global.mbarrier::complete_tx::bytes [%0], [%1], %2, [%3];"
                 ::"r"(dst), "l"(src), "r"(bytes), "r"(bar)
                 : "memory");
}

__global__ void __launch_bounds__(kThreads, 1)
nat_fused_kernel(const uint8_t* __restrict__ x, const uint8_t* __restrict__ wqkv, uint8_t* __restrict__ out, Scratch* g,
                 const uint8_t* wo, uint64_t dsc, const __grid_constant__ Maps maps) {
    const int tid = threadIdx.x, lane = tid & 31;
    const int warp = __shfl_sync(0xffffffffu, tid >> 5, 0);
    const int wg = warp >> 2, wq = warp & 3, r8 = lane >> 2, j = lane & 3;
    const int cta = blockIdx.x;
    const Work w = decode_work(cta);
    const uint32_t jq = (cta < 124 ? cta + 8 : cta - 124) / 11u, jr = (cta < 124 ? cta + 8 : cta - 124) - 11 * jq;
    const uint32_t which = jr >= 6, jhi = which ? jr - 6 : jq, jlo = which ? jq : 2 * jr;
    const bool has_job = jr < 10;
    if (wg == 2 && wq < 3) {
#pragma unroll
        for (int r = 0; r < 3; r++)
            asm volatile("st.shared.v4.u32 [%0], {%1, %1, %1, %1};" ::"r"(s_ring + wq * kRingChunk + (r == 0 ? 84 : r == 1 ? 88 : 204) * 128 + lane * 16), "r"(0) : "memory");
        asm volatile("fence.proxy.async.shared::cta;" ::: "memory");
    }
    MOperands mo;
    uint32_t launch = 0;
    if (wg == 1 && wq < 3 && !which) m_load(mo, wqkv, jhi, jlo, wq, lane);
    if (warp == 7) launch = ld_relaxed(g->launches[cta]);
    if (x == nullptr) return;
    const uint32_t t_start = clock_now();
    if (wg == 2) {
        asm volatile("setmaxnreg.dec.sync.aligned.u32 24;");
        if (wq < 3) {
            if (lane < 3 && cta < 128) {
                const uint32_t row = 3 * (cta >> 1) + wq;
                asm volatile("prefetch.global.L2 [%0];" ::"l"((cta & 1 ? wo + row * 384 : wqkv + row * 1152 + 768) + lane * 128));
            }
            asm volatile("bar.sync 7, 192;" ::: "memory");
            const uint32_t par = lds_volatile(s_par);
            uint32_t phase = 0;
#pragma unroll 1
            for (uint32_t c = 0; c < 6; c++) {
                const uint32_t part = c * kWChunk + wq * (kWChunk / 3);
                mbar_wait(bar_img + 8 * c, 0);
                if (c == 0 && lane == 0) mbar_arrive(bar_ok);
                if (wq == 0) TRW(10 + c);
#pragma unroll 1
                while (true) {
                    uint32_t lo = ~0u;
#pragma unroll
                    for (int q = 0; q < 8; q++) lo = min(lo, lds_volatile(s_m + part + lane * 32 + (lane & 12) * 2 + q * 1024));
                    if (__all_sync(0xffffffffu, lo) || phase > 65535) break;
                    if (elect()) {
                        mbar_expect_tx(bar_redo + 8 * wq, kWChunk / 3);
                        bulk_g2s(s_m + part, g->img[0][0] + par + part, kWChunk / 3, bar_redo + 8 * wq);
                    }
                    mbar_wait(bar_redo + 8 * wq, phase++ & 1);
                }
                if (c == 2 && phase) asm volatile("st.shared.u32 [%0], %1;" ::"r"(s_again), "r"(1) : "memory");
                if ((c == 2 || c == 5) && lane == 0) mbar_arrive(bar_ok + (c == 2 ? 8 : 16));
            }
        } else {
            const CUtensorMap* map = &maps.m[w.sv == kPixBytes ? 2 : 0];
            if (elect()) {
#pragma unroll
                for (int i = 0; i < 24; i++) mbar_init(s_bar + 8 * i, i < 15 ? 1 : i < 18 ? 3 : 4);
                asm volatile("fence.mbarrier_init.release.cluster;" ::: "memory");
                prefetch_map(map + 1);
                expect_tx_only(bar_a, sizeof(Table));
                bulk_g2s(s_tab, &maps.tables->t[w.step < 0], sizeof(Table), bar_a);
            }
            if (which && has_job && elect()) {
                mbar_expect_tx(bar_wop, 4 * 6144);
                tma_3d(s_wv, &maps.wo, bar_wop, 0, jhi);
                tma_3d(s_wv + 3 * 6144, &maps.wv, bar_wop, 16 * jlo, 6);
            }
            int u = w.u, v = w.v;
            uint32_t wait_bar = bar_use, wait_par = 1, slot = 0;
#pragma unroll 1
            for (int step = 0; step < 7 - w.corner; step++) {
                const bool first = step == 0 || (w.corner && step == 4);
                const int ou = origin_u(u);
                const bool final = step == 6 - w.corner;
                if (final) { wait_bar = bar_free; wait_par = 0; }
#pragma unroll 1
                for (uint32_t bar = first ? bar_a : bar_b; bar <= (first ? bar_a : bar_mid); bar += 8) {
                    mbar_wait(bar, first ? !step : slot != 0);
                    if (elect()) mbar_expect_tx(bar, first ? 3 * kSlotBytes : bar < bar_mid ? kSlotBytes : 3 * kMidBytes);
                }
                int row = v + 4 + (first ? -w.step : w.step) / 2;
                uint32_t dst = final ? s_m : s_ring + (first ? 0 : slot), bar = first ? bar_a : bar_b, dbar = first ? 0 : 8;
#pragma unroll 1
                for (int r = 0; r < 2 - first; r++) {
                    mbar_wait(wait_bar, wait_par);
                    if (r == 0) TRW(24 + step);
#pragma unroll
                    for (int n = 0; n < 3; n++) {
                        if (n && final) mbar_wait(bar_free + 8 * n, 0);
                        if (elect()) tma_box(dst + n * kRingChunk, map + r, bar + n * dbar, (cta & 1) * kC + 64 * n, ou, (cta >> 1) & 1, row);
                    }
                    row = v + 6; bar = bar_mid; dbar = 0;
                    dst = (final ? s_m : s_ring) + kOffMid + 512;
                    if (wait_bar == bar_use) wait_bar = bar_use + 16;
                }
                TRW(32 + 8 * step + 4);
                if (step == 0) {
                    asm volatile("st.shared.v2.u32 [%0], {%1, %1};" ::"r"(s_late), "r"(0) : "memory");
                    asm volatile("bar.arrive 3, 160;\nbar.arrive 4, 160;\nbar.arrive 8, 128;\nbar.sync 9, 64;" ::: "memory");
                }
                if (step < 2) {
                    if (step) {
                        asm volatile("bar.sync 6, 128;" ::: "memory");
                    }
                    const uint32_t par = __shfl_sync(0xffffffffu, lds_volatile(s_par), 0);
                    wait_until(t_start, step ? TN(5, kTimeW) : TN(6, kTimeM));
                    TRW(5 + 4 * step);
#pragma unroll 1
                    for (int c = 3 * step; c < 3 + 3 * step; c++)
                        if (elect()) {
                            mbar_expect_tx(bar_img + 8 * c, kWChunk);
                            bulk_g2s(s_m + c * kWChunk, g->img[0][0] + (par + c * kWChunk), kWChunk, bar_img + 8 * c);
                        }
                }
                const bool again = w.corner && step == 3;
                wait_bar = step == 0 ? bar_img + 8 * TN(1, 1) : again ? bar_use + 8 : bar_use;
                if (!again) {
                    wait_par = slot ? 0 : step != 0;
                    slot ^= kSlotStride;
                    if (w.corner && step == 2) { u += 8; v -= 8; } else if (step) v += w.step;
                }
            }
        }
        TRDUMP();
        return;
    }
    if (warp == 7) {
        asm volatile("st.shared.u32 [%0], %1;\nbar.arrive 9, 64;" ::"r"(s_par), "r"((launch & 1) * 2 * kWBytes) : "memory");
        g->launches[cta][lane] = launch + 1;
        asm volatile("bar.arrive 5, 128;" ::: "memory");
    }
    if (wg == 1 && wq < 3) {
        if (!which) m_partial(mo, wq, lane, (uint32_t)dsc & 1);
        const uint32_t off = piece_offset(which, which ? jlo : jlo + wq, which ? 3 * jhi + wq : jhi, lane);
        asm volatile("bar.sync %0, %1;" ::"r"(5 + (off >> 31)), "n"(128) : "memory");
        const uint32_t par = lds_volatile(s_par);
        if (which) asm volatile("bar.sync 8, 128;" ::: "memory");
        if (has_job && wq < 2 + which) {
            float d[2][4];
            if (wq == 0) TRX(which ? 1 : 18);
            if (which) {
                mbar_wait(bar_wop, 0);
                if (wq == 0) TRX(2);
                w_piece(wq, lane, d);
            } else {
                m_reduce(wq, lane, d);
            }
            piece_store(g, par, off, which, d);
            __syncwarp();
            piece_clear(g, 2 * kWBytes - par, off, which);
            if (wq == 0) TRX(which ? 3 : 0);
        }
        if (!which) asm volatile("bar.sync 8, 128;" ::: "memory");
        asm volatile("bar.arrive 7, 192;\nbar.arrive 6, 128;" ::: "memory");
    }
    const int order = w.step < 0 ? warp ^ 3 : warp;
    int tu = w.u, tv = w.v + w.step * wg;
    const int du2 = w.corner ? 8 : 0, dv2 = w.corner ? 0 : 2 * w.step;
    uint32_t o0, o1;
    wait_until(t_start, START_TIME);
    asm volatile("setmaxnreg.inc.sync.aligned.u32 240;");
    w.pixel_offsets(tu + r8, tv + 2 * wq, j, o0, o1);
    uint32_t fa[48];
    {
        RawX raw;
        load_raw(raw, x, o0, o1);
        asm volatile("bar.sync %0, 160;" ::"r"(3 + wg) : "memory");
        raw_to_frags(raw, 0, fa);
        pin(fa);
    }
    mbar_wait(bar_ok, 0);
    const uint64_t dA = dsc + wg * (kSlotStride >> 4), dB = dsc + (wg ^ 1) * (kSlotStride >> 4);

    float acc[96];
    uint32_t po[48];
    uint32_t c0, c1;
    asm volatile("" : "=r"(c0), "=r"(c1));
#pragma unroll
    for (int q = 0; q < 48; q++) asm volatile("" : "=r"(po[q]));
#pragma unroll 1
    for (int i = wg; i < w.ntiles; i += 2) {
        const bool first = i == 0, last = i == w.ntiles - 1;

        TRF(8 + 16 * k);
        uint8_t *p0 = out + c0, *p1 = out + c1;
#pragma unroll 1
        for (uint32_t seen = 0;;) {
        wg_fence();
        if (!first) turn_wait(wg);
        proj_gemm(acc, fa, dsc, s_m, [&](int s) {
            if (s == 11 && !first) turn_pass(wg);
            const int n = __builtin_popcount(QSLOTS & ((1 << s) - 1));
            if (((QSLOTS >> s) & 1) && n < 12) store_one(i >= 2, out + c0, out + c1, po, n);
            if (s == 3 || s == 7) { wg_commit(); mbar_wait(bar_img + 2 * s + 2, 0); wg_fence(); }
        });
        __syncwarp();
        TRF(9 + 16 * k);
            if (!first) break;
            mbar_wait(bar_ok + 8, 0);
            if (lds_volatile(s_again) == seen) break;
            wg_wait<0>();
            seen = 1;
        }
        c0 = o0; c1 = o1;
        w.pixel_offsets(tu + du2 + r8, tv + dv2 + 2 * wq, j, o0, o1);
        if (i + 2 >= w.ntiles) o0 = o1 = 0;
        mbar_wait(bar_a, w.corner ? i >> 1 : 0);
        wg_wait<2>();
        if (last && lane == 0) mbar_arrive(bar_free);
        wg_wait<1>();
        if (last && lane == 0) mbar_arrive(bar_free + 8);
        wg_wait<0>();
        if (last && lane == 0) mbar_arrive(bar_free + 16);
        const uint64_t dE = last ? dsc + ((s_m - s_ring) >> 4) : dsc, dN = last ? dE : dB;
        pin(acc);
        TR(11 + 16 * k);
        TRT(80 + k);
#pragma unroll
        for (int n = __builtin_popcount(QSLOTS); n < 12 - __builtin_popcount(ASLOTS) - __builtin_popcount(BSLOTS); n++) store_one(i >= 2, p0, p1, po, n);
        acc_to_frags(acc, fa);
        pin(fa);

        float sA[44], sE[16], sB[44];
        RawX nxt;
        if (!first) turn_wait(wg);
        wg_fence();
#pragma unroll
        for (int s = 0; s < 12; s++) {
            if (s == 0) wgmma_n88<true>(sA, fa[4 * s], fa[4 * s + 1], fa[4 * s + 2], fa[4 * s + 3], desc_at(dA, (s >> 2) * kRingChunk + (s & 3) * 32));
            else wgmma_n88<false>(sA, fa[4 * s], fa[4 * s + 1], fa[4 * s + 2], fa[4 * s + 3], desc_at(dA, (s >> 2) * kRingChunk + (s & 3) * 32));
            if (s == 11) { wg_commit(); if (!first) turn_pass(wg); }
            if ((ASLOTS >> s) & 1) store_one(i >= 2, p0, p1, po, 12 - __builtin_popcount(BSLOTS) - __builtin_popcount(ASLOTS >> s));
        }
#pragma unroll
        for (int s = 12; s < 16; s++)
            if ((ASLOTS >> s) & 1) store_one(i >= 2, p0, p1, po, 12 - __builtin_popcount(BSLOTS) - __builtin_popcount(ASLOTS >> s));
        TRF(12 + 16 * k);
        const int vq = tv + 2 * wq;
        const uint4 tabu = lds128(s_tab + offsetof(Table, u) + (window_start(tu + r8) - origin_u(tu)) * 64 + j * 16);
        const uint4 tabv = lds128(s_tab + offsetof(Table, v) + (window_start(vq) + window_start(vq + 1) - 2 * tv) * 64 + j * 16);
        const uint4 route = lds128(s_tab + lane * 16);
        load_raw(nxt, x, o0, o1);
        float v0[14], v1[14];
#pragma unroll
        for (int b = 0; b < 14; b++) {
            v0[b] = __uint_as_float((b > 10 ? route.x >> (b + 2) : 0u) | 0xff800000u);
            v1[b] = __uint_as_float((b > 10 ? route.x >> (b + 5) : 0u) | 0xff800000u);
        }
        wg_wait<0>();
        pin(sA);
        gather_outer(sA, tabu.x, tabv.x, v0, v1);
        pin(v0); pin(v1);
        if (!first) turn_wait(wg);
#pragma unroll
        for (int c = 0; c < 3; c++) {
            mbar_wait(bar_b + 8 * c, wg);
            TRF(64 + 4 * k + c);
            wg_fence();
#pragma unroll
            for (int s = 4 * c; s < 4 * c + 4; s++) {
                if (s == 0) wgmma_n88<true>(sB, fa[4 * s], fa[4 * s + 1], fa[4 * s + 2], fa[4 * s + 3], desc_at(dN, c * kRingChunk + (s & 3) * 32));
                else wgmma_n88<false>(sB, fa[4 * s], fa[4 * s + 1], fa[4 * s + 2], fa[4 * s + 3], desc_at(dN, c * kRingChunk + (s & 3) * 32));
                if ((BSLOTS >> s) & 1) store_one(i >= 2, p0, p1, po, 12 - __builtin_popcount(BSLOTS >> s));
            }
        }
        wg_commit();
        mbar_wait(bar_mid, wg);
        wg_fence();
#pragma unroll
        for (int s = 0; s < 12; s++)
            if (s == 0) wgmma_n32<true>(sE, fa[4 * s], fa[4 * s + 1], fa[4 * s + 2], fa[4 * s + 3], desc_at(dE, kOffMid + (s >> 2) * kRingChunk + (s & 3) * 32));
            else wgmma_n32<false>(sE, fa[4 * s], fa[4 * s + 1], fa[4 * s + 2], fa[4 * s + 3], desc_at(dE, kOffMid + (s >> 2) * kRingChunk + (s & 3) * 32));
        wg_commit();
        turn_pass(wg);
        TRF(13 + 16 * k);
        wg_wait<1>();
        pin(sB);
        gather_outer(sB, tabu.w, tabv.y, v0, v1);
        wg_wait<0>();
        pin(sE);
        TRF(14 + 16 * k);
        gather_mid(sE, tabu.w, tabv.z, v0, v1);
        const float m0 = quad_max(tree_max(v0)), m1 = quad_max(tree_max(v1));

        uint32_t y[14], pa[12], pb[12];
        exp_route<0, 14>(v0, v1, m0, m1, route, (j & 1) == 0, y);
        float s0 = tree_sum(v0), s1 = tree_sum(v1);
        asm volatile("" : "+f"(s0), "+f"(s1));
        unfold<0, 0, 6>(y, tabv.w, pa);
        turn_wait(wg + (y[0] >> 31));
        TRF(15 + 16 * k + (y[13] >> 31));
        wg_fence();
        wgmma_sp_n192_tb<true, 0>(acc, pa[0], pa[1], pa[2], pa[3], desc_at(dA, kToV), tabu.y);
        wgmma_sp_n192_tb<false, 1>(acc, pa[4], pa[5], pa[6], pa[7], desc_at(dA, kToV + 4096), tabu.y);
        wgmma_sp_n192_tb<false, 0>(acc, pa[8], pa[9], pa[10], pa[11], desc_at(dA, kToV + 8192), tabu.z);
        wg_commit();
        wgmma_sp_n192_tb<false, 1>(acc, j == 0 ? 0u : y[10], j == 0 ? 0u : y[11], y[12], y[13], desc_at(dE, kToV + kOffMid), tabu.z);
        wg_commit();
        unfold<8, 0, 6>(y, tabv.w, pb);
        wg_fence();
        wgmma_sp_n192_tb<false, 0>(acc, pb[0], pb[1], pb[2], pb[3], desc_at(dN, kToV), tabu.y);
        wgmma_sp_n192_tb<false, 1>(acc, pb[4], pb[5], pb[6], pb[7], desc_at(dN, kToV + 4096), tabu.y);
        wgmma_sp_n192_tb<false, 0>(acc, pb[8], pb[9], pb[10], pb[11], desc_at(dN, kToV + 8192), tabu.z);
        wg_commit();
        if (!last) turn_pass(wg);
        TRF(16 + 16 * k);
        wg_wait<2>();
        if (lane == 0) mbar_arrive(bar_use);
        wg_wait<1>();
        if (lane == 0) mbar_arrive(bar_use + 16);
        TRF(17 + 16 * k);
        mbar_wait(bar_ok + 16, 0);
        wg_wait<0>();
        if (lane == 0) mbar_arrive(bar_use + 8);
        pin(acc);
        TR(18 + 16 * k);

        acc_to_frags(acc, po);
        pin(po);
        if (!last) turn_wait(wg);
        wg_fence();
        proj_gemm(acc, po, dsc, s_wv, [&](int s) {
            if (s + 1 == OSPLIT && i + 2 == w.ntiles) { turn_pass(wg); turn_wait(wg); }
        });
        if (!last) turn_pass(wg);
        TRF(19 + 16 * k);
        const uint32_t zero = lds_volatile(s_late);
        const float inv0 = rcp(quad_sum(s0 + __uint_as_float(zero))), inv1 = rcp(quad_sum(s1 + __uint_as_float(zero)));
        raw_to_frags(nxt, zero, fa);
        pin(fa);
#pragma unroll
        for (int q = 0; q < 48; q += 4) keep(wqkv == nullptr, fa[q], fa[q + 1], fa[q + 2], fa[q + 3]);
        keep(wqkv == nullptr, __float_as_uint(inv0), __float_as_uint(inv1), zero, lane);
        TRF(20 + 16 * k);
        tu += du2; tv += dv2;
        wg_wait<0>();
        pin(acc);
        TR(21 + 16 * k);
#pragma unroll
        for (int q = 0; q < 96; q++) acc[q] *= q & 2 ? inv1 : inv0;
        pack_out(acc, po);
#pragma unroll
        for (int n = 0; n < INLOOP; n++) store_one<false>(last, out + c0, out + c1, po, n);
        pin(po);
    }
    if (wg == 0) {
#pragma unroll
        for (int n = 0; n < 12; n++) {
            __nanosleep(NAP);
            store_one<false>(true, out + c0, out + c1, po, n);
        }
    } else {
#pragma unroll
        for (int n = INLOOP; n < 12; n++) store_one<false>(true, out + c0, out + c1, po, n);
    }
    TRE(7);
    TRG(1);
    TRDUMP();
}

typedef CUresult (*EncodeTiledFn)(CUtensorMap*, CUtensorMapDataType, cuuint32_t, void*, const cuuint64_t*, const cuuint64_t*,
                                  const cuuint32_t*, const cuuint32_t*, CUtensorMapInterleave, CUtensorMapSwizzle,
                                  CUtensorMapL2promotion, CUtensorMapFloatOOBfill);

bool make_maps(EncodeTiledFn fn, Maps* maps, void* x, void* wqkv, void* wo) {
    const cuuint64_t pix2 = 2 * kPixBytes, row = (cuuint64_t)kHW * kPixBytes;
    const cuuint32_t estr[5] = {1, 1, 1, 1, 1};
    bool ok = true;
    for (int tr = 0; tr < 2; tr++)
        for (int b = 0; b < 2; b++) {
            const cuuint64_t su = tr ? 2 * row : pix2, sv = tr ? pix2 : 2 * row;
            const cuuint64_t dims[5] = {2 * kC, 2, 105, 2, 112};
            const cuuint64_t strides[4] = {7 * su, su, row, sv};
            const cuuint32_t box[5] = {64, 2, 7, 1, b ? 2u : 6u};
            ok = ok && fn(&maps->m[2 * tr + b], CU_TENSOR_MAP_DATA_TYPE_BFLOAT16, 5, x, dims, strides, box, estr,
                          CU_TENSOR_MAP_INTERLEAVE_NONE, CU_TENSOR_MAP_SWIZZLE_128B, CU_TENSOR_MAP_L2_PROMOTION_L2_128B,
                          CU_TENSOR_MAP_FLOAT_OOB_FILL_NONE) == CUDA_SUCCESS;
        }
    for (int b = 0; b < 2; b++) {
        const cuuint64_t dims[3] = {b ? 64u : 48u, kC, b ? 9u : 4u}, strides[2] = {(b ? 3u : 1u) * kPixBytes, b ? 128u : 96u};
        const cuuint32_t box[3] = {b ? 64u : 48u, b ? 16u : 192u, b ? 3u : 1u};
        ok = ok && fn(b ? &maps->wv : &maps->wo, CU_TENSOR_MAP_DATA_TYPE_BFLOAT16, 3, b ? wqkv : wo, dims, strides, box, estr,
                      CU_TENSOR_MAP_INTERLEAVE_NONE, b ? CU_TENSOR_MAP_SWIZZLE_128B : CU_TENSOR_MAP_SWIZZLE_NONE, CU_TENSOR_MAP_L2_PROMOTION_L2_128B,
                      CU_TENSOR_MAP_FLOAT_OOB_FILL_NONE) == CUDA_SUCCESS;
    }
    return ok;
}

}

extern "C" void kernel_launch(void* const* d_in, const int* in_sizes, int n_in, void* d_out, int out_size) {
    static EncodeTiledFn encode = nullptr;
    static Scratch* scratch = nullptr;
    static Tables* tables = nullptr;
    if (!encode) {
        int dev = 0, reserved = 0;
        cudaFuncAttributes attr;
        cudaGetDevice(&dev);
        cudaDeviceGetAttribute(&reserved, cudaDevAttrReservedSharedMemoryPerBlock, dev);
        cudaFuncGetAttributes(&attr, nat_fused_kernel);
        if (reserved != (int)kSmemBase || attr.sharedSizeBytes != 0) return;
        cudaGetSymbolAddress((void**)&scratch, g_scratch);
        cudaGetSymbolAddress((void**)&tables, g_tables);
        void* fn = nullptr;
        cudaDriverEntryPointQueryResult st;
        cudaGetDriverEntryPoint("cuTensorMapEncodeTiled", &fn, cudaEnableDefault, &st);
        encode = (EncodeTiledFn)fn;
        cudaFuncSetAttribute(nat_fused_kernel, cudaFuncAttributeMaxDynamicSharedMemorySize, kSmemBytes);
    }
    Maps maps;
    maps.tables = tables;
    if (!encode || !make_maps(encode, &maps, d_in[0], d_in[1], d_in[2])) return;
    nat_fused_kernel<<<kGrid, kThreads, kSmemBytes>>>((const uint8_t*)d_in[0], (const uint8_t*)d_in[1], (uint8_t*)d_out, scratch, (const uint8_t*)d_in[2],
                                                      kDescRing, maps);
}
```

```cpp
#include <cuda_runtime.h>
#include <cuda_bf16.h>
#include <cuda.h>
#include <stdint.h>
#include <type_traits>
#include <stdlib.h>
#include <stdio.h>
#include <stddef.h>

#define ASLOTS 0x1800
#define BSLOTS 0x2
#define QSLOTS 0xfae
#define OSPLIT 2
#define NAP 40
#define INLOOP 2

namespace {

constexpr int kC          = 192;
constexpr int kHW         = 224;
constexpr int kPixBytes   = kC * 2;
constexpr int kSlotBytes  = 84 * 128;
constexpr int kMidBytes   = 28 * 128;
constexpr int kOffMid     = 88 * 128;
constexpr int kSlotStride = 120 * 128;
constexpr int kRingChunk  = 208 * 128;
constexpr int kWChunk     = 192 * 128;
constexpr int kWBytes     = 3 * kWChunk;
constexpr uint32_t kSmemBase = 1024;
constexpr uint32_t s_ring = kSmemBase, s_m = s_ring + 3 * kRingChunk, s_wv = s_m + kWBytes, s_bar = s_wv + kWBytes;
constexpr uint32_t bar_b = s_bar, bar_mid = s_bar + 24, bar_a = s_bar + 32, bar_img = s_bar + 40, bar_redo = s_bar + 88,
                   bar_wop = s_bar + 112, bar_ok = s_bar + 120, bar_use = s_bar + 144, bar_free = s_bar + 168;
constexpr uint32_t s_par = s_bar + 192, s_late = s_bar + 200, s_again = s_bar + 204, s_tab = s_bar + 256, s_trace = s_tab + 2048;
constexpr int kSmemBytes  = s_trace + 2048 - kSmemBase;
constexpr int kThreads    = 384;
constexpr int kGrid       = 132;
constexpr int kTimeM = 2500, kTimeW = 5100;
constexpr float kScaleLog2e = 0.07216878364870322f * 1.4426950408889634f;

struct Maps {
    CUtensorMap m[4];
    CUtensorMap wo, wv;
    const struct Tables* tables;
};
#define TN(i, dflt) (dflt)
#define START_TIME (wg ? 850 + 500 * order : 250 + 560 * order)

struct Scratch {
    uint8_t img[2][2][kWBytes];
    uint32_t launches[kGrid][32];
};
__device__ __align__(1024) Scratch g_scratch;

struct Table {
    uint32_t route[32][4];
    uint32_t u[8][4][4];
    uint32_t v[16][4][4];
};
struct Tables { Table t[2]; };
constexpr Tables make_tables() {
    Tables r = {};
    for (int rev = 0; rev < 2; rev++)
        for (int j = 0; j < 4; j++) {
            Table& t = r.t[rev];
            for (int q = 0; q < 8; q++) {
                uint32_t* e = t.route[4 * q + j];
                e[0] = 4 * q + 2 * (j & 1) + (j >> 1); e[1] = e[0] ^ 1;
                e[2] = j < 2 ? 0x5410u : 0x1054u; e[3] = e[2] + 0x2222u;
                e = t.u[q][j];
                for (int n = 0; n < 7; n++) e[0] |= ((n + j) % 7 < q ? 1u : 0u) << n;
                e[3] = e[0];
                for (int k = 0; k < 2; k++) {
                    const int step = 2 * k + (j >> 1), p0 = (step < 3 ? 16 * step : 40) + 8 * (j & 1);
                    uint32_t m = 0x8888u;
                    for (int n = 0; n < 8; n++) m |= ((p0 + n) % 7 < q ? 1u : 0u) << (2 * n);
                    e[1 + k] = m * 0x10001u;
                }
            }
            for (int sum = 0; sum < 15; sum++) {
                uint32_t* e = t.v[sum][j];
                for (int row = 0; row < 2; row++)
                    for (int b = 0; b < 14; b++) {
                        const int off = (sum + row) / 2, p = 4 * b + j;
                        const uint32_t bit = 1u << (2 * b + row);
                        if (p < 42 && p >= 7 * off) e[rev] |= bit;
                        if (p < 7 * off - 7) e[1 - rev] |= bit;
                        if (p >= 42 && p >= 7 * off && p < 7 * off + 49) e[2] |= bit;
                    }
                for (int n = 0; n < 6; n++)
                    if (8 * n + 2 * j < 42) e[3] |= 1u << (n + ((8 * n + 2 * j >= 7 * (sum / 2 & ~1)) != rev ? 0 : 8));
            }
        }
    return r;
}
__device__ __align__(128) const Tables g_tables = make_tables();

#define WO4(i) "=f"(d[i]), "=f"(d[i + 1]), "=f"(d[i + 2]), "=f"(d[i + 3])
#define RW4(i) "+f"(d[i]), "+f"(d[i + 1]), "+f"(d[i + 2]), "+f"(d[i + 3])

template <bool FIRST>
__device__ __forceinline__ void wgmma_n192(float (&d)[96], uint32_t a0, uint32_t a1, uint32_t a2, uint32_t a3, uint64_t descb) {
    if constexpr (FIRST) {
        asm volatile(
            "wgmma.mma_async.sync.aligned.m64n192k16.f32.bf16.bf16 "
            "{%0, %1, %2, %3, %4, %5, %6, %7, %8, %9, %10, %11, %12, %13, %14, %15, %16, %17, %18, %19, %20, %21, %22, %23, "
            "%24, %25, %26, %27, %28, %29, %30, %31, %32, %33, %34, %35, %36, %37, %38, %39, %40, %41, %42, %43, %44, %45, %46, %47, "
            "%48, %49, %50, %51, %52, %53, %54, %55, %56, %57, %58, %59, %60, %61, %62, %63, %64, %65, %66, %67, %68, %69, %70, %71, "
            "%72, %73, %74, %75, %76, %77, %78, %79, %80, %81, %82, %83, %84, %85, %86, %87, %88, %89, %90, %91, %92, %93, %94, %95}, "
            "{%96, %97, %98, %99}, %100, 0, 1, 1, 0;"
            : WO4(0), WO4(4), WO4(8), WO4(12), WO4(16), WO4(20), WO4(24), WO4(28), WO4(32), WO4(36), WO4(40), WO4(44),
              WO4(48), WO4(52), WO4(56), WO4(60), WO4(64), WO4(68), WO4(72), WO4(76), WO4(80), WO4(84), WO4(88), WO4(92)
            : "r"(a0), "r"(a1), "r"(a2), "r"(a3), "l"(descb));
    } else {
        asm volatile(
            "wgmma.mma_async.sync.aligned.m64n192k16.f32.bf16.bf16 "
            "{%0, %1, %2, %3, %4, %5, %6, %7, %8, %9, %10, %11, %12, %13, %14, %15, %16, %17, %18, %19, %20, %21, %22, %23, "
            "%24, %25, %26, %27, %28, %29, %30, %31, %32, %33, %34, %35, %36, %37, %38, %39, %40, %41, %42, %43, %44, %45, %46, %47, "
            "%48, %49, %50, %51, %52, %53, %54, %55, %56, %57, %58, %59, %60, %61, %62, %63, %64, %65, %66, %67, %68, %69, %70, %71, "
            "%72, %73, %74, %75, %76, %77, %78, %79, %80, %81, %82, %83, %84, %85, %86, %87, %88, %89, %90, %91, %92, %93, %94, %95}, "
            "{%96, %97, %98, %99}, %100, 1, 1, 1, 0;"
            : RW4(0), RW4(4), RW4(8), RW4(12), RW4(16), RW4(20), RW4(24), RW4(28), RW4(32), RW4(36), RW4(40), RW4(44),
              RW4(48), RW4(52), RW4(56), RW4(60), RW4(64), RW4(68), RW4(72), RW4(76), RW4(80), RW4(84), RW4(88), RW4(92)
            : "r"(a0), "r"(a1), "r"(a2), "r"(a3), "l"(descb));
    }
}

template <bool FIRST>
__device__ __forceinline__ void wgmma_n88(float (&d)[44], uint32_t a0, uint32_t a1, uint32_t a2, uint32_t a3, uint64_t descb) {
    if constexpr (FIRST) {
        asm volatile(
            "wgmma.mma_async.sync.aligned.m64n88k16.f32.bf16.bf16 "
            "{%0, %1, %2, %3, %4, %5, %6, %7, %8, %9, %10, %11, %12, %13, %14, %15, %16, %17, %18, %19, %20, %21, %22, %23, "
            "%24, %25, %26, %27, %28, %29, %30, %31, %32, %33, %34, %35, %36, %37, %38, %39, %40, %41, %42, %43}, "
            "{%44, %45, %46, %47}, %48, 0, 1, 1, 0;"
            : WO4(0), WO4(4), WO4(8), WO4(12), WO4(16), WO4(20), WO4(24), WO4(28), WO4(32), WO4(36), WO4(40)
            : "r"(a0), "r"(a1), "r"(a2), "r"(a3), "l"(descb));
    } else {
        asm volatile(
            "wgmma.mma_async.sync.aligned.m64n88k16.f32.bf16.bf16 "
            "{%0, %1, %2, %3, %4, %5, %6, %7, %8, %9, %10, %11, %12, %13, %14, %15, %16, %17, %18, %19, %20, %21, %22, %23, "
            "%24, %25, %26, %27, %28, %29, %30, %31, %32, %33, %34, %35, %36, %37, %38, %39, %40, %41, %42, %43}, "
            "{%44, %45, %46, %47}, %48, 1, 1, 1, 0;"
            : RW4(0), RW4(4), RW4(8), RW4(12), RW4(16), RW4(20), RW4(24), RW4(28), RW4(32), RW4(36), RW4(40)
            : "r"(a0), "r"(a1), "r"(a2), "r"(a3), "l"(descb));
    }
}

template <bool FIRST>
__device__ __forceinline__ void wgmma_n32(float (&d)[16], uint32_t a0, uint32_t a1, uint32_t a2, uint32_t a3, uint64_t descb) {
    if constexpr (FIRST) {
        asm volatile(
            "wgmma.mma_async.sync.aligned.m64n32k16.f32.bf16.bf16 "
            "{%0, %1, %2, %3, %4, %5, %6, %7, %8, %9, %10, %11, %12, %13, %14, %15}, "
            "{%16, %17, %18, %19}, %20, 0, 1, 1, 0;"
            : WO4(0), WO4(4), WO4(8), WO4(12)
            : "r"(a0), "r"(a1), "r"(a2), "r"(a3), "l"(descb));
    } else {
        asm volatile(
            "wgmma.mma_async.sync.aligned.m64n32k16.f32.bf16.bf16 "
            "{%0, %1, %2, %3, %4, %5, %6, %7, %8, %9, %10, %11, %12, %13, %14, %15}, "
            "{%16, %17, %18, %19}, %20, 1, 1, 1, 0;"
            : RW4(0), RW4(4), RW4(8), RW4(12)
            : "r"(a0), "r"(a1), "r"(a2), "r"(a3), "l"(descb));
    }
}

template <bool FIRST, int SEL>
__device__ __forceinline__ void wgmma_sp_n192_tb(float (&d)[96], uint32_t a0, uint32_t a1, uint32_t a2, uint32_t a3, uint64_t descb, uint32_t meta) {
    if constexpr (FIRST) {
        asm volatile(
            "wgmma.mma_async.sp.sync.aligned.m64n192k32.f32.bf16.bf16 "
            "{%0, %1, %2, %3, %4, %5, %6, %7, %8, %9, %10, %11, %12, %13, %14, %15, %16, %17, %18, %19, %20, %21, %22, %23, "
            "%24, %25, %26, %27, %28, %29, %30, %31, %32, %33, %34, %35, %36, %37, %38, %39, %40, %41, %42, %43, %44, %45, %46, %47, "
            "%48, %49, %50, %51, %52, %53, %54, %55, %56, %57, %58, %59, %60, %61, %62, %63, %64, %65, %66, %67, %68, %69, %70, %71, "
            "%72, %73, %74, %75, %76, %77, %78, %79, %80, %81, %82, %83, %84, %85, %86, %87, %88, %89, %90, %91, %92, %93, %94, %95}, "
            "{%96, %97, %98, %99}, %100, %101, %102, 0, 1, 1, 1;"
            : WO4(0), WO4(4), WO4(8), WO4(12), WO4(16), WO4(20), WO4(24), WO4(28), WO4(32), WO4(36), WO4(40), WO4(44),
              WO4(48), WO4(52), WO4(56), WO4(60), WO4(64), WO4(68), WO4(72), WO4(76), WO4(80), WO4(84), WO4(88), WO4(92)
            : "r"(a0), "r"(a1), "r"(a2), "r"(a3), "l"(descb), "r"(meta), "n"(SEL));
    } else {
        asm volatile(
            "wgmma.mma_async.sp.sync.aligned.m64n192k32.f32.bf16.bf16 "
            "{%0, %1, %2, %3, %4, %5, %6, %7, %8, %9, %10, %11, %12, %13, %14, %15, %16, %17, %18, %19, %20, %21, %22, %23, "
            "%24, %25, %26, %27, %28, %29, %30, %31, %32, %33, %34, %35, %36, %37, %38, %39, %40, %41, %42, %43, %44, %45, %46, %47, "
            "%48, %49, %50, %51, %52, %53, %54, %55, %56, %57, %58, %59, %60, %61, %62, %63, %64, %65, %66, %67, %68, %69, %70, %71, "
            "%72, %73, %74, %75, %76, %77, %78, %79, %80, %81, %82, %83, %84, %85, %86, %87, %88, %89, %90, %91, %92, %93, %94, %95}, "
            "{%96, %97, %98, %99}, %100, %101, %102, 1, 1, 1, 1;"
            : RW4(0), RW4(4), RW4(8), RW4(12), RW4(16), RW4(20), RW4(24), RW4(28), RW4(32), RW4(36), RW4(40), RW4(44),
              RW4(48), RW4(52), RW4(56), RW4(60), RW4(64), RW4(68), RW4(72), RW4(76), RW4(80), RW4(84), RW4(88), RW4(92)
            : "r"(a0), "r"(a1), "r"(a2), "r"(a3), "l"(descb), "r"(meta), "n"(SEL));
    }
}

#define TR(slot)
#define TRX(slot)
#define TRE(slot)
#define TRT(slot)
#define TRF(slot)
#define TRW(slot)
#define TRG(slot)
#define TRDUMP()

__device__ __forceinline__ void wg_fence() { asm volatile("wgmma.fence.sync.aligned;" ::: "memory"); }
__device__ __forceinline__ void wg_commit() { asm volatile("wgmma.commit_group.sync.aligned;" ::: "memory"); }
template <int N>
__device__ __forceinline__ void wg_wait() { asm volatile("wgmma.wait_group.sync.aligned %0;" ::"n"(N) : "memory"); }

template <int N>
__device__ __forceinline__ void pin(float (&d)[N]) {
#pragma unroll
    for (int i = 0; i < N; i++) asm volatile("" : "+f"(d[i])::"memory");
}
template <int N>
__device__ __forceinline__ void pin(uint32_t (&d)[N]) {
#pragma unroll
    for (int i = 0; i < N; i++) asm volatile("" : "+r"(d[i])::"memory");
}

constexpr uint64_t kDescRing = ((uint64_t)((1u << 30) | (1024u >> 4)) << 32) | (1u << 16) | (s_ring >> 4);
constexpr uint32_t kToV = ((kRingChunk >> 4) - 1) << 20;
__device__ __forceinline__ uint64_t desc_at(uint64_t base, uint32_t byte_off) {
    uint64_t d;
    asm volatile("add.s64 %0, %1, %2;" : "=l"(d) : "l"(base), "l"((uint64_t)(byte_off >> 4)));
    return d;
}

__device__ __forceinline__ void mbar_init(uint32_t bar, uint32_t count) {
    asm volatile("mbarrier.init.shared::cta.b64 [%0], %1;" ::"r"(bar), "r"(count) : "memory");
}
__device__ __forceinline__ void mbar_expect_tx(uint32_t bar, uint32_t bytes) {
    asm volatile("mbarrier.arrive.expect_tx.shared::cta.b64 _, [%0], %1;" ::"r"(bar), "r"(bytes) : "memory");
}
__device__ __forceinline__ void expect_tx_only(uint32_t bar, uint32_t bytes) {
    asm volatile("mbarrier.expect_tx.relaxed.cta.shared::cta.b64 [%0], %1;" ::"r"(bar), "r"(bytes) : "memory");
}
__device__ __forceinline__ void mbar_arrive(uint32_t bar) {
    asm volatile("mbarrier.arrive.shared::cta.b64 _, [%0];" ::"r"(bar) : "memory");
}
__device__ __forceinline__ void mbar_wait(uint32_t bar, uint32_t parity) {
    asm volatile(
        "{\n.reg .pred p;\n"
        "W: mbarrier.try_wait.parity.shared::cta.b64 p, [%0], %1;\n"
        "@!p bra W;\n}\n"
        ::"r"(bar), "r"(parity) : "memory");
}
__device__ __forceinline__ uint32_t clock_now() {
    uint32_t c;
    asm volatile("mov.u32 %0, %%clock;" : "=r"(c)::"memory");
    return c;
}
__device__ __forceinline__ void wait_until(uint32_t t0, int t) {
    if (t == 0) return;
    while ((int)(clock_now() - t0) < t) {}
}
__device__ __forceinline__ bool elect() {
    uint32_t ok;
    asm volatile("{\n.reg .pred p;\nelect.sync _|p, 0xffffffff;\nselp.u32 %0, 1, 0, p;\n}\n" : "=r"(ok));
    return ok != 0;
}
__device__ __forceinline__ void turn_wait(int wg) { asm volatile("bar.sync %0, 256;" ::"r"(1 + wg) : "memory"); }
__device__ __forceinline__ void turn_pass(int wg) { asm volatile("bar.arrive %0, 256;" ::"r"(2 - wg) : "memory"); }

__device__ __forceinline__ void tma_box(uint32_t dst, const CUtensorMap* map, uint32_t bar, int c0, int c2, int c3, int c4) {
    asm volatile(
        "cp.async.bulk.tensor.5d.shared::cluster.global.mbarrier::complete_tx::bytes [%0], [%1, {%3, %4, %5, %6, %7}], [%2];"
        ::"r"(dst), "l"(map), "r"(bar), "r"(c0), "r"(0), "r"(c2), "r"(c3), "r"(c4)
        : "memory");
}
__device__ __forceinline__ void tma_3d(uint32_t dst, const CUtensorMap* map, uint32_t bar, int c1, int c2) {
    asm volatile("cp.async.bulk.tensor.3d.shared::cluster.global.mbarrier::complete_tx::bytes [%0], [%1, {%3, %4, %5}], [%2];"
                 ::"r"(dst), "l"(map), "r"(bar), "r"(0), "r"(c1), "r"(c2)
                 : "memory");
}
__device__ __forceinline__ void prefetch_map(const CUtensorMap* map) {
    asm volatile("prefetch.tensormap [%0];" ::"l"(map) : "memory");
}
__device__ __forceinline__ uint4 ldg(const void* p) {
    uint4 v;
    asm volatile("ld.global.v4.u32 {%0, %1, %2, %3}, [%4];" : "=r"(v.x), "=r"(v.y), "=r"(v.z), "=r"(v.w) : "l"(p) : "memory");
    return v;
}
__device__ __forceinline__ uint32_t pack_bf16(float lo, float hi) {
    uint32_t r;
    asm("cvt.rn.bf16x2.f32 %0, %1, %2;" : "=r"(r) : "f"(hi), "f"(lo));
    return r;
}
__device__ __forceinline__ float ex2(float x) {
    float y;
    asm("ex2.approx.ftz.f32 %0, %1;" : "=f"(y) : "f"(x));
    return y;
}
__device__ __forceinline__ float rcp(float x) {
    float y;
    asm("rcp.approx.ftz.f32 %0, %1;" : "=f"(y) : "f"(x));
    return y;
}
__device__ __forceinline__ void mma16816(float (&d)[4], uint32_t a0, uint32_t a1, uint32_t a2, uint32_t a3, uint32_t b0, uint32_t b1) {
    asm volatile("mma.sync.aligned.m16n8k16.row.col.f32.bf16.bf16.f32 {%0, %1, %2, %3}, {%4, %5, %6, %7}, {%8, %9}, {%0, %1, %2, %3};"
                 : "+f"(d[0]), "+f"(d[1]), "+f"(d[2]), "+f"(d[3])
                 : "r"(a0), "r"(a1), "r"(a2), "r"(a3), "r"(b0), "r"(b1));
}
__device__ __forceinline__ uint4 lds128(uint32_t addr) {
    uint4 v;
    asm volatile("ld.volatile.shared.v4.u32 {%0, %1, %2, %3}, [%4];" : "=r"(v.x), "=r"(v.y), "=r"(v.z), "=r"(v.w) : "r"(addr) : "memory");
    return v;
}
__device__ __forceinline__ uint32_t lds_volatile(uint32_t addr) {
    uint32_t v;
    asm volatile("ld.volatile.shared.u32 %0, [%1];" : "=r"(v) : "r"(addr) : "memory");
    return v;
}

__device__ __forceinline__ int window_start(int n) { return min(max(n, 0), 105); }
__device__ __forceinline__ int origin_u(int u) { return min(max(u, 0), 98); }

struct Work {
    int u, v;
    int step;
    uint32_t su, sv;
    uint32_t base;
    bool corner;
    int ntiles;
    __device__ __forceinline__ void pixel_offsets(int qu, int qv, int j, uint32_t& o0, uint32_t& o1) const {
        const uint32_t b = (qu + window_start(qu)) * su + j * 16 + base;
        o0 = b + (qv + window_start(qv)) * sv;
        o1 = b + (qv + 1 + window_start(qv + 1)) * sv;
    }
};

__device__ __forceinline__ Work decode_work(int c) {
    Work w;
    const bool transposed = (c >> 4) == 7;
    const int px = 6 * (c & 1), py = 3 * (c & 2);
    w.corner = c >= 128;
    w.step = 8 - 4 * (c & 4);
    w.u = (c < 112 ? c & ~7 : 96 + (c & 8)) + (transposed ? py : px) - 6;
    w.v = (w.corner ? 96 : 48 - 2 * (c & 4)) + (transposed ? px : py) - 6;
    w.su = transposed ? kHW * kPixBytes : kPixBytes;
    w.sv = transposed ? kPixBytes : kHW * kPixBytes;
    w.base = px * (kPixBytes / 6) + py * (kHW * kPixBytes / 6) + 6 * (kHW + 1) * kPixBytes;
    w.ntiles = w.corner ? 4 : 6;
    return w;
}

struct RawX { uint4 a[6], b[6]; };
__device__ __forceinline__ void load_raw(RawX& r, const uint8_t* base, uint32_t o0, uint32_t o1) {
    __syncwarp();
#pragma unroll
    for (int c = 0; c < 6; c++) { r.a[c] = ldg(base + o0 + c * 64); r.b[c] = ldg(base + o1 + c * 64); }
    __syncwarp();
}
__device__ __forceinline__ void raw_to_frags(const RawX& r, uint32_t zero, uint32_t (&f)[48]) {
#pragma unroll
    for (int c = 0; c < 6; c++) {
        asm volatile("{\n.reg .b32 t, u;\nadd.u32 t, %4, %8;\nadd.u32 u, %5, %8;\nxor.b32 %0, %6, %8;\nxor.b32 %1, %7, %8;\n"
                     "xor.b32 %2, t, %8;\nxor.b32 %3, u, %8;\n}\n"
                     : "=&r"(f[8 * c + 1]), "=&r"(f[8 * c + 3]), "=&r"(f[8 * c + 4]), "=&r"(f[8 * c + 6])
                     : "r"(r.a[c].y), "r"(r.a[c].w), "r"(r.b[c].x), "r"(r.b[c].z), "r"(zero));
        f[8 * c + 0] = r.a[c].x; f[8 * c + 2] = r.a[c].z; f[8 * c + 5] = r.b[c].y; f[8 * c + 7] = r.b[c].w;
    }
}
__device__ __forceinline__ void acc_to_frags(const float (&d)[96], uint32_t (&f)[48]) {
#pragma unroll
    for (int i = 0; i < 48; i++) f[i] = pack_bf16(d[2 * i], d[2 * i + 1]);
}

template <class F>
__device__ __forceinline__ void proj_gemm(float (&d)[96], const uint32_t (&a)[48], uint64_t dsc, uint32_t img, F after) {
#pragma unroll
    for (int s = 0; s < 12; s++) {
        if (s == 0) wgmma_n192<true>(d, a[4 * s], a[4 * s + 1], a[4 * s + 2], a[4 * s + 3], desc_at(dsc, img - s_ring + (s >> 2) * kWChunk + (s & 3) * 32));
        else wgmma_n192<false>(d, a[4 * s], a[4 * s + 1], a[4 * s + 2], a[4 * s + 3], desc_at(dsc, img - s_ring + (s >> 2) * kWChunk + (s & 3) * 32));
        if (s == 11) wg_commit();
        after(s);
    }
}
__device__ __forceinline__ void pack_out(const float (&acc)[96], uint32_t (&po)[48]) {
#pragma unroll
    for (int g = 0; g < 6; g++)
#pragma unroll
        for (int q = 0; q < 4; q++) {
            po[8 * g + q] = pack_bf16(acc[16 * g + 4 * q], acc[16 * g + 4 * q + 1]);
            po[8 * g + 4 + q] = pack_bf16(acc[16 * g + 4 * q + 2], acc[16 * g + 4 * q + 3]);
        }
}
template <bool PINNED = true>
__device__ __forceinline__ void store_one(bool on, uint8_t* p0, uint8_t* p1, const uint32_t (&po)[48], int n) {
    if (PINNED) __syncwarp();
    asm volatile("{\n.reg .pred p;\nsetp.ne.u32 p, %5, 0;\n@p st.global.v4.u32 [%0], {%1, %2, %3, %4};\n}\n"
                 ::"l"(((n & 1) ? p1 : p0) + (n >> 1) * 64), "r"(po[4 * n]), "r"(po[4 * n + 1]), "r"(po[4 * n + 2]), "r"(po[4 * n + 3]), "r"((uint32_t)on) : "memory");
}

template <int N>
__device__ __forceinline__ float tree_max(const float (&v)[N]) {
    float t[N];
#pragma unroll
    for (int i = 0; i < N; i++) t[i] = v[i];
#pragma unroll
    for (int w = 1; w < N; w *= 2)
#pragma unroll
        for (int i = 0; i + w < N; i += 2 * w) t[i] = fmaxf(t[i], t[i + w]);
    return t[0];
}
template <int N>
__device__ __forceinline__ float tree_sum(const float (&v)[N]) {
    float t[N];
#pragma unroll
    for (int i = 0; i < N; i++) t[i] = v[i];
#pragma unroll
    for (int w = 1; w < N; w *= 2)
#pragma unroll
        for (int i = 0; i + w < N; i += 2 * w) t[i] += t[i + w];
    return t[0];
}

template <int B>
__device__ __forceinline__ void pick(uint32_t h, uint32_t ok, const float* s, float& v0, float& v1) {
    asm("{\n.reg .pred p, q0, q1;\n.reg .b32 t;\nand.b32 t, %6, %7;\nsetp.ne.u32 p, t, 0;\n"
        "and.b32 t, %8, %9;\nsetp.ne.u32 q0, t, 0;\nand.b32 t, %8, %10;\nsetp.ne.u32 q1, t, 0;\n"
        "@q0 selp.f32 %0, %3, %2, p;\n@q1 selp.f32 %1, %5, %4, p;\n}\n"
        : "+f"(v0), "+f"(v1)
        : "f"(s[0]), "f"(s[1]), "f"(s[2]), "f"(s[3]), "r"(h), "n"(1 << ((4 * B) % 7)), "r"(ok), "n"(1 << (2 * B)), "n"(2 << (2 * B)));
}
template <int B, class F>
__device__ __forceinline__ void for_blocks(F f) {
    if constexpr (B > 0) { for_blocks<B - 1>(f); f(std::integral_constant<int, B - 1>{}); }
}
__device__ __forceinline__ void gather_outer(const float (&s)[44], uint32_t h, uint32_t ok, float (&v0)[14], float (&v1)[14]) {
    for_blocks<11>([&](auto B) {
        constexpr int b = B.value < 8 ? (B.value >> 1) + 7 * (B.value & 1) : B.value - 4;
        pick<b>(h, ok, &s[4 * b], v0[b], v1[b]);
    });
}
__device__ __forceinline__ void gather_mid(const float (&sE)[16], uint32_t h, uint32_t ok, float (&v0)[14], float (&v1)[14]) {
    for_blocks<4>([&](auto B) { pick<10 + B.value>(h, ok, &sE[4 * B.value], v0[10 + B.value], v1[10 + B.value]); });
}
__device__ __forceinline__ float quad_max(float m) {
    m = fmaxf(m, __shfl_xor_sync(0xffffffffu, m, 1));
    return fmaxf(m, __shfl_xor_sync(0xffffffffu, m, 2));
}
__device__ __forceinline__ float quad_sum(float s) {
    s += __shfl_xor_sync(0xffffffffu, s, 1);
    return s + __shfl_xor_sync(0xffffffffu, s, 2);
}
template <int B0, int B1>
__device__ __forceinline__ void exp_route(float (&v0)[14], float (&v1)[14], float m0, float m1, const uint4& r, bool even, uint32_t (&y)[14]) {
#pragma unroll
    for (int b = B0; b < B1; b++) { v0[b] = ex2(v0[b] - m0); v1[b] = ex2(v1[b] - m1); }
#pragma unroll
    for (int b = B0; b < B1; b += 2) {
        const uint32_t x0 = pack_bf16(v0[b], v1[b]), x1 = pack_bf16(v0[b + 1], v1[b + 1]);
        const uint32_t u = __shfl_sync(0xffffffffu, even ? x0 : x1, r.x);
        const uint32_t w = __shfl_sync(0xffffffffu, even ? x1 : x0, r.y);
        y[b] = __byte_perm(u, w, r.z); y[b + 1] = __byte_perm(u, w, r.w);
    }
}
template <int BIT0, int N0, int N1>
__device__ __forceinline__ void unfold(const uint32_t (&y)[14], uint32_t fold, uint32_t (&p)[12]) {
    for_blocks<N1 - N0>([&](auto N) {
        constexpr int n = N0 + N.value;
        asm("{\n.reg .pred p;\n.reg .b32 t;\nand.b32 t, %4, %5;\nsetp.ne.u32 p, t, 0;\nselp.b32 %0, %2, 0, p;\nselp.b32 %1, %3, 0, p;\n}\n"
            : "=r"(p[2 * n]), "=r"(p[2 * n + 1]) : "r"(y[2 * n]), "r"(y[2 * n + 1]), "r"(fold), "n"(1 << (BIT0 + n)));
    });
}
__device__ __forceinline__ void keep(bool never, uint32_t a, uint32_t b, uint32_t c, uint32_t d) {
    asm volatile("{\n.reg .pred p;\nsetp.ne.u32 p, %4, 0;\n@p st.volatile.shared.v4.u32 [%5], {%0, %1, %2, %3};\n}\n"
                 ::"r"(a), "r"(b), "r"(c), "r"(d), "r"((uint32_t)never), "r"(s_trace) : "memory");
}

__device__ __forceinline__ uint32_t wimg_offset(uint32_t row, uint32_t s, uint32_t j) {
    return (s >> 2) * kWChunk + row * 128 + (((2 * (s & 3) + (j >> 1)) ^ (row & 7)) << 4) + (j & 1) * 8;
}

__device__ __forceinline__ void ldsm4(uint32_t (&r)[4], uint32_t addr) {
    asm volatile("ldmatrix.sync.aligned.m8n8.x4.shared.b16 {%0, %1, %2, %3}, [%4];" : "=r"(r[0]), "=r"(r[1]), "=r"(r[2]), "=r"(r[3]) : "r"(addr) : "memory");
}
__device__ __forceinline__ void ldsm4_t(uint32_t (&r)[4], uint32_t addr) {
    asm volatile("ldmatrix.sync.aligned.m8n8.x4.trans.shared.b16 {%0, %1, %2, %3}, [%4];" : "=r"(r[0]), "=r"(r[1]), "=r"(r[2]), "=r"(r[3]) : "r"(addr) : "memory");
}
struct MOperands { uint4 A[2][2], B[4][2]; };
__device__ __forceinline__ void m_load(MOperands& m, const uint8_t* wqkv, uint32_t mt, uint32_t s, uint32_t q, uint32_t lane) {
    const uint32_t r8 = lane >> 2, col = q * 128 + (lane & 3) * 16;
    const uint8_t* pa = wqkv + (16 * mt + r8) * 1152 + col;
    const uint8_t* pb = wqkv + (16 * s + 8 * (r8 & 2) + (r8 & 5)) * 1152 + col;
#pragma unroll
    for (int c = 0; c < 2; c++) {
#pragma unroll
        for (int h = 0; h < 2; h++) m.A[h][c] = ldg(pa + 384 + h * 8 * 1152 + c * 64);
#pragma unroll
        for (int n = 0; n < 4; n++) m.B[n][c] = ldg(pb + ((n & 1) * 8 + (n & 2)) * 1152 + c * 64);
    }
}
__device__ __forceinline__ void m_partial(MOperands& m, uint32_t q, uint32_t lane, uint32_t zero) {
    auto& A = m.A;
    auto& B = m.B;
#pragma unroll
    for (int i = 0; i < 4; i++) { uint4& a = A[i >> 1][i & 1]; a.x ^= zero; a.y ^= zero; a.z ^= zero; a.w ^= zero; }
#pragma unroll
    for (int n = 0; n < 4; n++) {
        float d[4] = {0.f, 0.f, 0.f, 0.f};
#pragma unroll
        for (int c = 0; c < 2; c++) {
            mma16816(d, A[0][c].x, A[1][c].x, A[0][c].y, A[1][c].y, B[n][c].x, B[n][c].y);
            mma16816(d, A[0][c].z, A[1][c].z, A[0][c].w, A[1][c].w, B[n][c].z, B[n][c].w);
        }
        asm volatile("st.shared.v4.f32 [%0], {%1, %2, %3, %4};" ::"r"(s_wv + q * 2048 + n * 512 + lane * 16), "f"(d[0]), "f"(d[1]), "f"(d[2]), "f"(d[3]) : "memory");
    }
}
__device__ __forceinline__ void m_reduce(uint32_t e, uint32_t lane, float (&d)[2][4]) {
#pragma unroll
    for (int n = 0; n < 2; n++) {
        float t[3][4];
#pragma unroll
        for (int q = 0; q < 3; q++)
            asm volatile("ld.shared.v4.f32 {%0, %1, %2, %3}, [%4];" : "=f"(t[q][0]), "=f"(t[q][1]), "=f"(t[q][2]), "=f"(t[q][3]) : "r"(s_wv + q * 2048 + e * 1024 + n * 512 + lane * 16) : "memory");
#pragma unroll
        for (int i = 0; i < 4; i++) d[n][i] = (t[0][i] + t[1][i] + t[2][i]) * kScaleLog2e;
    }
}
__device__ __forceinline__ void w_piece(uint32_t q, uint32_t lane, float (&d)[2][4]) {
    const uint32_t rr = lane & 7, mi = lane >> 3, kr = 4 * (rr >> 1) + (mi & 2) + (rr & 1);
    const uint32_t pa = s_wv + q * 32 + (4 * (mi & 2) + rr) * 96 + ((mi & 1) << 4);
    const uint32_t pb = s_wv + 3 * 6144 + kr * 128 + (((mi & 1) ^ (kr & 7)) << 4);
    float e[2][4];
#pragma unroll
    for (int i = 0; i < 8; i++) (&d[0][0])[i] = (&e[0][0])[i] = 0.f;
#pragma unroll
    for (int k = 0; k < 12; k++) {
        uint32_t aq[4], bq[4];
        ldsm4_t(aq, pa + k * 1536);
        ldsm4(bq, (pb ^ ((k & 3) << 5)) + (k >> 2) * 2048);
        mma16816(k & 1 ? e[0] : d[0], aq[0], aq[1], aq[2], aq[3], bq[0], bq[1]);
        mma16816(k & 1 ? e[1] : d[1], aq[0], aq[1], aq[2], aq[3], bq[2], bq[3]);
    }
#pragma unroll
    for (int i = 0; i < 8; i++) (&d[0][0])[i] += (&e[0][0])[i];
}
__device__ __forceinline__ uint32_t piece_offset(uint32_t which, uint32_t s, uint32_t mt, uint32_t lane) {
    const uint32_t r8 = lane >> 2;
    return which * kWBytes + wimg_offset(which ? 32 * (mt >> 1) + 8 * (r8 >> 1) + 4 * (mt & 1) + (r8 & 1) : 16 * mt + r8, s, lane & 3);
}
__device__ __forceinline__ void piece_store(Scratch* g, uint32_t par, uint32_t off0, uint32_t which, const float (&d)[2][4]) {
#pragma unroll
    for (int hf = 0; hf < 2; hf++) {
        const uint32_t off = off0 ^ (hf ? which ? 288 : 1024 : 0);
        const uint32_t a = pack_bf16(d[0][2 * hf], d[0][2 * hf + 1]), b = pack_bf16(d[1][2 * hf], d[1][2 * hf + 1]);
        asm volatile("st.relaxed.gpu.global.v2.u32 [%0], {%1, %2};" ::"l"(g->img[0][0] + (par + off)), "r"(a ? a : 0x8000u), "r"(b) : "memory");
    }
}
__device__ __forceinline__ void piece_clear(Scratch* g, uint32_t par, uint32_t off0, uint32_t which) {
#pragma unroll
    for (int hf = 0; hf < 2; hf++)
        asm volatile("st.relaxed.gpu.global.v2.u32 [%0], {%1, %1};" ::"l"(g->img[0][0] + (par + (off0 ^ (hf ? which ? 288 : 1024 : 0)))), "r"(0) : "memory");
}

__device__ __forceinline__ uint32_t ld_relaxed(const uint32_t* p) {
    uint32_t v;
    asm volatile("ld.relaxed.gpu.global.u32 %0, [%1];" : "=r"(v) : "l"(p) : "memory");
    return v;
}
__device__ __forceinline__ void count_up(uint32_t* p) {
    asm volatile("red.relaxed.gpu.global.add.u32 [%0], %1;" ::"l"(p), "r"(1) : "memory");
}
__device__ __forceinline__ void bulk_g2s(uint32_t dst, const void* src, uint32_t bytes, uint32_t bar) {
    asm volatile("cp.async.bulk.shared::cluster.global.mbarrier::complete_tx::bytes [%0], [%1], %2, [%3];"
                 ::"r"(dst), "l"(src), "r"(bytes), "r"(bar)
                 : "memory");
}

__global__ void __launch_bounds__(kThreads, 1)
nat_fused_kernel(const uint8_t* __restrict__ x, const uint8_t* __restrict__ wqkv, uint8_t* __restrict__ out, Scratch* g,
                 const uint8_t* wo, uint64_t dsc, const __grid_constant__ Maps maps) {
    const int tid = threadIdx.x, lane = tid & 31;
    const int warp = __shfl_sync(0xffffffffu, tid >> 5, 0);
    const int wg = warp >> 2, wq = warp & 3, r8 = lane >> 2, j = lane & 3;
    const int cta = blockIdx.x;
    const Work w = decode_work(cta);
    const uint32_t jq = (cta < 124 ? cta + 8 : cta - 124) / 11u, jr = (cta < 124 ? cta + 8 : cta - 124) - 11 * jq;
    const uint32_t which = jr >= 6, jhi = which ? jr - 6 : jq, jlo = which ? jq : 2 * jr;
    const bool has_job = jr < 10;
    if (wg == 2 && wq < 3) {
#pragma unroll
        for (int r = 0; r < 3; r++)
            asm volatile("st.shared.v4.u32 [%0], {%1, %1, %1, %1};" ::"r"(s_ring + wq * kRingChunk + (r == 0 ? 84 : r == 1 ? 88 : 204) * 128 + lane * 16), "r"(0) : "memory");
        asm volatile("fence.proxy.async.shared::cta;" ::: "memory");
    }
    MOperands mo;
    uint32_t launch = 0;
    if (wg == 1 && wq < 3 && !which) m_load(mo, wqkv, jhi, jlo, wq, lane);
    if (warp == 7) launch = ld_relaxed(g->launches[cta]);
    if (x == nullptr) return;
    const uint32_t t_start = clock_now();
    if (wg == 2) {
        asm volatile("setmaxnreg.dec.sync.aligned.u32 24;");
        if (wq < 3) {
            if (lane < 3 && cta < 128) {
                const uint32_t row = 3 * (cta >> 1) + wq;
                asm volatile("prefetch.global.L2 [%0];" ::"l"((cta & 1 ? wo + row * 384 : wqkv + row * 1152 + 768) + lane * 128));
            }
            asm volatile("bar.sync 7, 192;" ::: "memory");
            const uint32_t par = lds_volatile(s_par);
            uint32_t phase = 0;
#pragma unroll 1
            for (uint32_t c = 0; c < 6; c++) {
                const uint32_t part = c * kWChunk + wq * (kWChunk / 3);
                mbar_wait(bar_img + 8 * c, 0);
                if (c == 0 && lane == 0) mbar_arrive(bar_ok);
                if (wq == 0) TRW(10 + c);
#pragma unroll 1
                while (true) {
                    uint32_t lo = ~0u;
#pragma unroll
                    for (int q = 0; q < 8; q++) lo = min(lo, lds_volatile(s_m + part + lane * 32 + (lane & 12) * 2 + q * 1024));
                    if (__all_sync(0xffffffffu, lo) || phase > 65535) break;
                    if (elect()) {
                        mbar_expect_tx(bar_redo + 8 * wq, kWChunk / 3);
                        bulk_g2s(s_m + part, g->img[0][0] + par + part, kWChunk / 3, bar_redo + 8 * wq);
                    }
                    mbar_wait(bar_redo + 8 * wq, phase++ & 1);
                }
                if (c == 2 && phase) asm volatile("st.shared.u32 [%0], %1;" ::"r"(s_again), "r"(1) : "memory");
                if ((c == 2 || c == 5) && lane == 0) mbar_arrive(bar_ok + (c == 2 ? 8 : 16));
            }
        } else {
            const CUtensorMap* map = &maps.m[w.sv == kPixBytes ? 2 : 0];
            if (elect()) {
#pragma unroll
                for (int i = 0; i < 24; i++) mbar_init(s_bar + 8 * i, i < 15 ? 1 : i < 18 ? 3 : 4);
                asm volatile("fence.mbarrier_init.release.cluster;" ::: "memory");
                prefetch_map(map + 1);
                expect_tx_only(bar_a, sizeof(Table));
                bulk_g2s(s_tab, &maps.tables->t[w.step < 0], sizeof(Table), bar_a);
            }
            if (which && has_job && elect()) {
                mbar_expect_tx(bar_wop, 4 * 6144);
                tma_3d(s_wv, &maps.wo, bar_wop, 0, jhi);
                tma_3d(s_wv + 3 * 6144, &maps.wv, bar_wop, 16 * jlo, 6);
            }
            int u = w.u, v = w.v;
            uint32_t wait_bar = bar_use, wait_par = 1, slot = 0;
#pragma unroll 1
            for (int step = 0; step < 7 - w.corner; step++) {
                const bool first = step == 0 || (w.corner && step == 4);
                const int ou = origin_u(u);
                const bool final = step == 6 - w.corner;
                if (final) { wait_bar = bar_free; wait_par = 0; }
#pragma unroll 1
                for (uint32_t bar = first ? bar_a : bar_b; bar <= (first ? bar_a : bar_mid); bar += 8) {
                    mbar_wait(bar, first ? !step : slot != 0);
                    if (elect()) mbar_expect_tx(bar, first ? 3 * kSlotBytes : bar < bar_mid ? kSlotBytes : 3 * kMidBytes);
                }
                int row = v + 4 + (first ? -w.step : w.step) / 2;
                uint32_t dst = final ? s_m : s_ring + (first ? 0 : slot), bar = first ? bar_a : bar_b, dbar = first ? 0 : 8;
#pragma unroll 1
                for (int r = 0; r < 2 - first; r++) {
                    mbar_wait(wait_bar, wait_par);
                    if (r == 0) TRW(24 + step);
#pragma unroll
                    for (int n = 0; n < 3; n++) {
                        if (n && final) mbar_wait(bar_free + 8 * n, 0);
                        if (elect()) tma_box(dst + n * kRingChunk, map + r, bar + n * dbar, (cta & 1) * kC + 64 * n, ou, (cta >> 1) & 1, row);
                    }
                    row = v + 6; bar = bar_mid; dbar = 0;
                    dst = (final ? s_m : s_ring) + kOffMid + 512;
                    if (wait_bar == bar_use) wait_bar = bar_use + 16;
                }
                TRW(32 + 8 * step + 4);
                if (step == 0) {
                    asm volatile("st.shared.v2.u32 [%0], {%1, %1};" ::"r"(s_late), "r"(0) : "memory");
                    asm volatile("bar.arrive 3, 160;\nbar.arrive 4, 160;\nbar.arrive 8, 128;\nbar.sync 9, 64;" ::: "memory");
                }
                if (step < 2) {
                    if (step) {
                        asm volatile("bar.sync 6, 128;" ::: "memory");
                    }
                    const uint32_t par = __shfl_sync(0xffffffffu, lds_volatile(s_par), 0);
                    wait_until(t_start, step ? TN(5, kTimeW) : TN(6, kTimeM));
                    TRW(5 + 4 * step);
#pragma unroll 1
                    for (int c = 3 * step; c < 3 + 3 * step; c++)
                        if (elect()) {
                            mbar_expect_tx(bar_img + 8 * c, kWChunk);
                            bulk_g2s(s_m + c * kWChunk, g->img[0][0] + (par + c * kWChunk), kWChunk, bar_img + 8 * c);
                        }
                }
                const bool again = w.corner && step == 3;
                wait_bar = step == 0 ? bar_img + 8 * TN(1, 1) : again ? bar_use + 8 : bar_use;
                if (!again) {
                    wait_par = slot ? 0 : step != 0;
                    slot ^= kSlotStride;
                    if (w.corner && step == 2) { u += 8; v -= 8; } else if (step) v += w.step;
                }
            }
        }
        TRDUMP();
        return;
    }
    if (warp == 7) {
        asm volatile("st.shared.u32 [%0], %1;\nbar.arrive 9, 64;" ::"r"(s_par), "r"((launch & 1) * 2 * kWBytes) : "memory");
        g->launches[cta][lane] = launch + 1;
        asm volatile("bar.arrive 5, 128;" ::: "memory");
    }
    if (wg == 1 && wq < 3) {
        if (!which) m_partial(mo, wq, lane, (uint32_t)dsc & 1);
        const uint32_t off = piece_offset(which, which ? jlo : jlo + wq, which ? 3 * jhi + wq : jhi, lane);
        asm volatile("bar.sync %0, %1;" ::"r"(5 + (off >> 31)), "n"(128) : "memory");
        const uint32_t par = lds_volatile(s_par);
        if (which) asm volatile("bar.sync 8, 128;" ::: "memory");
        if (has_job && wq < 2 + which) {
            float d[2][4];
            if (wq == 0) TRX(which ? 1 : 18);
            if (which) {
                mbar_wait(bar_wop, 0);
                if (wq == 0) TRX(2);
                w_piece(wq, lane, d);
            } else {
                m_reduce(wq, lane, d);
            }
            piece_store(g, par, off, which, d);
            __syncwarp();
            piece_clear(g, 2 * kWBytes - par, off, which);
            if (wq == 0) TRX(which ? 3 : 0);
        }
        if (!which) asm volatile("bar.sync 8, 128;" ::: "memory");
        asm volatile("bar.arrive 7, 192;\nbar.arrive 6, 128;" ::: "memory");
    }
    const int order = w.step < 0 ? warp ^ 3 : warp;
    int tu = w.u, tv = w.v + w.step * wg;
    const int du2 = w.corner ? 8 : 0, dv2 = w.corner ? 0 : 2 * w.step;
    uint32_t o0, o1;
    wait_until(t_start, START_TIME);
    asm volatile("setmaxnreg.inc.sync.aligned.u32 240;");
    w.pixel_offsets(tu + r8, tv + 2 * wq, j, o0, o1);
    uint32_t fa[48];
    {
        RawX raw;
        load_raw(raw, x, o0, o1);
        asm volatile("bar.sync %0, 160;" ::"r"(3 + wg) : "memory");
        raw_to_frags(raw, 0, fa);
        pin(fa);
    }
    mbar_wait(bar_ok, 0);
    const uint64_t dA = dsc + wg * (kSlotStride >> 4), dB = dsc + (wg ^ 1) * (kSlotStride >> 4);

    float acc[96];
    uint32_t po[48];
    uint32_t c0 = 0, c1 = 0;
#pragma unroll
    for (int q = 0; q < 48; q++) asm volatile("" : "=r"(po[q]));
#pragma unroll 1
    for (int i = wg; i < w.ntiles; i += 2) {
        const bool first = i == 0, last = i == w.ntiles - 1;

        TRF(8 + 16 * k);
        uint8_t *p0 = out + c0, *p1 = out + c1;
#pragma unroll 1
        for (uint32_t seen = 0;;) {
        wg_fence();
        if (!first) turn_wait(wg);
        proj_gemm(acc, fa, dsc, s_m, [&](int s) {
            if (s == 11 && !first) turn_pass(wg);
            const int n = __builtin_popcount(QSLOTS & ((1 << s) - 1));
            if (((QSLOTS >> s) & 1) && n < 12) store_one(i >= 2, out + c0, out + c1, po, n);
            if (s == 3 || s == 7) { wg_commit(); mbar_wait(bar_img + 2 * s + 2, 0); wg_fence(); }
        });
        __syncwarp();
        TRF(9 + 16 * k);
            if (!first) break;
            mbar_wait(bar_ok + 8, 0);
            if (lds_volatile(s_again) == seen) break;
            wg_wait<0>();
            seen = 1;
        }
        c0 = o0; c1 = o1;
        w.pixel_offsets(tu + du2 + r8, tv + dv2 + 2 * wq, j, o0, o1);
        if (i + 2 >= w.ntiles) o0 = o1 = 0;
        mbar_wait(bar_a, w.corner ? i >> 1 : 0);
        wg_wait<2>();
        if (last && lane == 0) mbar_arrive(bar_free);
        wg_wait<1>();
        if (last && lane == 0) mbar_arrive(bar_free + 8);
#pragma unroll
        for (int s = 12; s < 14; s++)
            if ((QSLOTS >> s) & 1) { store_one(i >= 2, p0, p1, po, __builtin_popcount(QSLOTS & ((1 << s) - 1))); __syncwarp(); }
        wg_wait<0>();
        if (last && lane == 0) mbar_arrive(bar_free + 16);
        const uint64_t dE = last ? dsc + ((s_m - s_ring) >> 4) : dsc, dN = last ? dE : dB;
        pin(acc);
        TR(11 + 16 * k);
        TRT(80 + k);
#pragma unroll
        for (int n = __builtin_popcount(QSLOTS); n < 12 - __builtin_popcount(ASLOTS) - __builtin_popcount(BSLOTS); n++) store_one(i >= 2, p0, p1, po, n);
        acc_to_frags(acc, fa);
        pin(fa);

        float sA[44], sE[16], sB[44];
        RawX nxt;
        if (!first) turn_wait(wg);
        wg_fence();
#pragma unroll
        for (int s = 0; s < 12; s++) {
            if (s == 0) wgmma_n88<true>(sA, fa[4 * s], fa[4 * s + 1], fa[4 * s + 2], fa[4 * s + 3], desc_at(dA, (s >> 2) * kRingChunk + (s & 3) * 32));
            else wgmma_n88<false>(sA, fa[4 * s], fa[4 * s + 1], fa[4 * s + 2], fa[4 * s + 3], desc_at(dA, (s >> 2) * kRingChunk + (s & 3) * 32));
            if (s == 11) { wg_commit(); if (!first) turn_pass(wg); }
            if ((ASLOTS >> s) & 1) store_one(i >= 2, p0, p1, po, 12 - __builtin_popcount(BSLOTS) - __builtin_popcount(ASLOTS >> s));
        }
#pragma unroll
        for (int s = 12; s < 16; s++)
            if ((ASLOTS >> s) & 1) store_one(i >= 2, p0, p1, po, 12 - __builtin_popcount(BSLOTS) - __builtin_popcount(ASLOTS >> s));
        TRF(12 + 16 * k);
        const int vq = tv + 2 * wq;
        const uint4 tabu = lds128(s_tab + offsetof(Table, u) + (window_start(tu + r8) - origin_u(tu)) * 64 + j * 16);
        const uint4 tabv = lds128(s_tab + offsetof(Table, v) + (window_start(vq) + window_start(vq + 1) - 2 * tv) * 64 + j * 16);
        const uint4 route = lds128(s_tab + lane * 16);
        load_raw(nxt, x, o0, o1);
        float v0[14], v1[14];
#pragma unroll
        for (int b = 0; b < 14; b++) {
            v0[b] = __uint_as_float((b > 10 ? route.x >> (b + 2) : 0u) | 0xff800000u);
            v1[b] = __uint_as_float((b > 10 ? route.x >> (b + 5) : 0u) | 0xff800000u);
        }
        wg_wait<0>();
        pin(sA);
        gather_outer(sA, tabu.x, tabv.x, v0, v1);
        pin(v0); pin(v1);
        if (!first) turn_wait(wg);
#pragma unroll
        for (int c = 0; c < 3; c++) {
            mbar_wait(bar_b + 8 * c, wg);
            TRF(64 + 4 * k + c);
            wg_fence();
#pragma unroll
            for (int s = 4 * c; s < 4 * c + 4; s++) {
                if (s == 0) wgmma_n88<true>(sB, fa[4 * s], fa[4 * s + 1], fa[4 * s + 2], fa[4 * s + 3], desc_at(dN, c * kRingChunk + (s & 3) * 32));
                else wgmma_n88<false>(sB, fa[4 * s], fa[4 * s + 1], fa[4 * s + 2], fa[4 * s + 3], desc_at(dN, c * kRingChunk + (s & 3) * 32));
                if ((BSLOTS >> s) & 1) store_one(i >= 2, p0, p1, po, 12 - __builtin_popcount(BSLOTS >> s));
            }
        }
        wg_commit();
        mbar_wait(bar_mid, wg);
        wg_fence();
#pragma unroll
        for (int s = 0; s < 12; s++)
            if (s == 0) wgmma_n32<true>(sE, fa[4 * s], fa[4 * s + 1], fa[4 * s + 2], fa[4 * s + 3], desc_at(dE, kOffMid + (s >> 2) * kRingChunk + (s & 3) * 32));
            else wgmma_n32<false>(sE, fa[4 * s], fa[4 * s + 1], fa[4 * s + 2], fa[4 * s + 3], desc_at(dE, kOffMid + (s >> 2) * kRingChunk + (s & 3) * 32));
        wg_commit();
        turn_pass(wg);
        TRF(13 + 16 * k);
        wg_wait<1>();
        pin(sB);
        gather_outer(sB, tabu.w, tabv.y, v0, v1);
        wg_wait<0>();
        pin(sE);
        TRF(14 + 16 * k);
        gather_mid(sE, tabu.w, tabv.z, v0, v1);
        const float m0 = quad_max(tree_max(v0)), m1 = quad_max(tree_max(v1));

        uint32_t y[14], pa[12], pb[12];
        exp_route<0, 14>(v0, v1, m0, m1, route, (j & 1) == 0, y);
        float s0 = tree_sum(v0), s1 = tree_sum(v1);
        asm volatile("" : "+f"(s0), "+f"(s1));
        unfold<0, 0, 6>(y, tabv.w, pa);
        turn_wait(wg + (y[0] >> 31));
        TRF(15 + 16 * k + (y[13] >> 31));
        wg_fence();
        wgmma_sp_n192_tb<true, 0>(acc, pa[0], pa[1], pa[2], pa[3], desc_at(dA, kToV), tabu.y);
        wgmma_sp_n192_tb<false, 1>(acc, pa[4], pa[5], pa[6], pa[7], desc_at(dA, kToV + 4096), tabu.y);
        wgmma_sp_n192_tb<false, 0>(acc, pa[8], pa[9], pa[10], pa[11], desc_at(dA, kToV + 8192), tabu.z);
        wg_commit();
        wgmma_sp_n192_tb<false, 1>(acc, j == 0 ? 0u : y[10], j == 0 ? 0u : y[11], y[12], y[13], desc_at(dE, kToV + kOffMid), tabu.z);
        wg_commit();
        unfold<8, 0, 6>(y, tabv.w, pb);
        wg_fence();
        wgmma_sp_n192_tb<false, 0>(acc, pb[0], pb[1], pb[2], pb[3], desc_at(dN, kToV), tabu.y);
        wgmma_sp_n192_tb<false, 1>(acc, pb[4], pb[5], pb[6], pb[7], desc_at(dN, kToV + 4096), tabu.y);
        wgmma_sp_n192_tb<false, 0>(acc, pb[8], pb[9], pb[10], pb[11], desc_at(dN, kToV + 8192), tabu.z);
        wg_commit();
        if (!last) turn_pass(wg);
        TRF(16 + 16 * k);
        wg_wait<2>();
        if (lane == 0) mbar_arrive(bar_use);
        wg_wait<1>();
        if (lane == 0) mbar_arrive(bar_use + 16);
        TRF(17 + 16 * k);
        mbar_wait(bar_ok + 16, 0);
        wg_wait<0>();
        if (lane == 0) mbar_arrive(bar_use + 8);
        pin(acc);
        TR(18 + 16 * k);

        acc_to_frags(acc, po);
        pin(po);
        if (!last) turn_wait(wg);
        wg_fence();
        proj_gemm(acc, po, dsc, s_wv, [&](int s) {
            if (s + 1 == OSPLIT && i + 2 == w.ntiles) { turn_pass(wg); turn_wait(wg); }
        });
        if (!last) turn_pass(wg);
        TRF(19 + 16 * k);
        const uint32_t zero = lds_volatile(s_late);
        const float inv0 = rcp(quad_sum(s0 + __uint_as_float(zero))), inv1 = rcp(quad_sum(s1 + __uint_as_float(zero)));
        raw_to_frags(nxt, zero, fa);
        pin(fa);
#pragma unroll
        for (int q = 0; q < 48; q += 4) keep(wqkv == nullptr, fa[q], fa[q + 1], fa[q + 2], fa[q + 3]);
        keep(wqkv == nullptr, __float_as_uint(inv0), __float_as_uint(inv1), zero, lane);
        TRF(20 + 16 * k);
        tu += du2; tv += dv2;
        wg_wait<0>();
        pin(acc);
        TR(21 + 16 * k);
#pragma unroll
        for (int q = 0; q < 96; q++) acc[q] *= q & 2 ? inv1 : inv0;
        pack_out(acc, po);
#pragma unroll
        for (int n = 0; n < INLOOP; n++) store_one<false>(last, out + c0, out + c1, po, n);
        pin(po);
    }
    if (wg == 0) {
#pragma unroll
        for (int n = 0; n < 12; n++) {
            __nanosleep(NAP);
            store_one<false>(true, out + c0, out + c1, po, n);
        }
    } else {
#pragma unroll
        for (int n = INLOOP; n < 12; n++) store_one<false>(true, out + c0, out + c1, po, n);
    }
    TRE(7);
    TRG(1);
    TRDUMP();
}

typedef CUresult (*EncodeTiledFn)(CUtensorMap*, CUtensorMapDataType, cuuint32_t, void*, const cuuint64_t*, const cuuint64_t*,
                                  const cuuint32_t*, const cuuint32_t*, CUtensorMapInterleave, CUtensorMapSwizzle,
                                  CUtensorMapL2promotion, CUtensorMapFloatOOBfill);

bool make_maps(EncodeTiledFn fn, Maps* maps, void* x, void* wqkv, void* wo) {
    const cuuint64_t pix2 = 2 * kPixBytes, row = (cuuint64_t)kHW * kPixBytes;
    const cuuint32_t estr[5] = {1, 1, 1, 1, 1};
    bool ok = true;
    for (int tr = 0; tr < 2; tr++)
        for (int b = 0; b < 2; b++) {
            const cuuint64_t su = tr ? 2 * row : pix2, sv = tr ? pix2 : 2 * row;
            const cuuint64_t dims[5] = {2 * kC, 2, 105, 2, 112};
            const cuuint64_t strides[4] = {7 * su, su, row, sv};
            const cuuint32_t box[5] = {64, 2, 7, 1, b ? 2u : 6u};
            ok = ok && fn(&maps->m[2 * tr + b], CU_TENSOR_MAP_DATA_TYPE_BFLOAT16, 5, x, dims, strides, box, estr,
                          CU_TENSOR_MAP_INTERLEAVE_NONE, CU_TENSOR_MAP_SWIZZLE_128B, CU_TENSOR_MAP_L2_PROMOTION_L2_128B,
                          CU_TENSOR_MAP_FLOAT_OOB_FILL_NONE) == CUDA_SUCCESS;
        }
    for (int b = 0; b < 2; b++) {
        const cuuint64_t dims[3] = {b ? 64u : 48u, kC, b ? 9u : 4u}, strides[2] = {(b ? 3u : 1u) * kPixBytes, b ? 128u : 96u};
        const cuuint32_t box[3] = {b ? 64u : 48u, b ? 16u : 192u, b ? 3u : 1u};
        ok = ok && fn(b ? &maps->wv : &maps->wo, CU_TENSOR_MAP_DATA_TYPE_BFLOAT16, 3, b ? wqkv : wo, dims, strides, box, estr,
                      CU_TENSOR_MAP_INTERLEAVE_NONE, b ? CU_TENSOR_MAP_SWIZZLE_128B : CU_TENSOR_MAP_SWIZZLE_NONE, CU_TENSOR_MAP_L2_PROMOTION_L2_128B,
                      CU_TENSOR_MAP_FLOAT_OOB_FILL_NONE) == CUDA_SUCCESS;
    }
    return ok;
}

}

extern "C" void kernel_launch(void* const* d_in, const int* in_sizes, int n_in, void* d_out, int out_size) {
    static EncodeTiledFn encode = nullptr;
    static Scratch* scratch = nullptr;
    static Tables* tables = nullptr;
    if (!encode) {
        int dev = 0, reserved = 0;
        cudaFuncAttributes attr;
        cudaGetDevice(&dev);
        cudaDeviceGetAttribute(&reserved, cudaDevAttrReservedSharedMemoryPerBlock, dev);
        cudaFuncGetAttributes(&attr, nat_fused_kernel);
        if (reserved != (int)kSmemBase || attr.sharedSizeBytes != 0) return;
        cudaGetSymbolAddress((void**)&scratch, g_scratch);
        cudaGetSymbolAddress((void**)&tables, g_tables);
        void* fn = nullptr;
        cudaDriverEntryPointQueryResult st;
        cudaGetDriverEntryPoint("cuTensorMapEncodeTiled", &fn, cudaEnableDefault, &st);
        encode = (EncodeTiledFn)fn;
        cudaFuncSetAttribute(nat_fused_kernel, cudaFuncAttributeMaxDynamicSharedMemorySize, kSmemBytes);
    }
    Maps maps;
    maps.tables = tables;
    if (!encode || !make_maps(encode, &maps, d_in[0], d_in[1], d_in[2])) return;
    nat_fused_kernel<<<kGrid, kThreads, kSmemBytes>>>((const uint8_t*)d_in[0], (const uint8_t*)d_in[1], (uint8_t*)d_out, scratch, (const uint8_t*)d_in[2],
                                                      kDescRing, maps);
}
```

```cpp
#include <cuda_runtime.h>
#include <cuda_bf16.h>
#include <cuda.h>
#include <stdint.h>
#include <type_traits>
#include <stdlib.h>
#include <stdio.h>
#include <stddef.h>

#define ASLOTS 0x1800
#define BSLOTS 0x2
#define QSLOTS 0xfae
#define OSPLIT 2
#define INL 2
#define NAP 50

namespace {

constexpr int kC          = 192;
constexpr int kHW         = 224;
constexpr int kPixBytes   = kC * 2;
constexpr int kSlotBytes  = 84 * 128;
constexpr int kMidBytes   = 28 * 128;
constexpr int kOffMid     = 88 * 128;
constexpr int kSlotStride = 120 * 128;
constexpr int kRingChunk  = 208 * 128;
constexpr int kWChunk     = 192 * 128;
constexpr int kWBytes     = 3 * kWChunk;
constexpr uint32_t kSmemBase = 1024;
constexpr uint32_t s_ring = kSmemBase, s_m = s_ring + 3 * kRingChunk, s_wv = s_m + kWBytes, s_bar = s_wv + kWBytes;
constexpr uint32_t bar_b = s_bar, bar_mid = s_bar + 24, bar_a = s_bar + 32, bar_img = s_bar + 40, bar_redo = s_bar + 88,
                   bar_wop = s_bar + 112, bar_ok = s_bar + 120, bar_use = s_bar + 144, bar_free = s_bar + 168;
constexpr uint32_t s_par = s_bar + 192, s_late = s_bar + 200, s_again = s_bar + 204, s_tab = s_bar + 256, s_trace = s_tab + 2048;
constexpr int kSmemBytes  = s_trace + 2048 - kSmemBase;
constexpr int kThreads    = 384;
constexpr int kGrid       = 132;
constexpr int kTimeM = 2500, kTimeW = 5100;
constexpr float kScaleLog2e = 0.07216878364870322f * 1.4426950408889634f;

struct Maps {
    CUtensorMap m[4];
    CUtensorMap wo, wv;
    const struct Tables* tables;
};
#define TN(i, dflt) (dflt)
#define START_TIME (wg ? 850 + 500 * order : 250 + 560 * order)

struct Scratch {
    uint8_t img[2][2][kWBytes];
    uint32_t launches[kGrid][32];
};
__device__ __align__(1024) Scratch g_scratch;

struct Table {
    uint32_t route[32][4];
    uint32_t u[8][4][4];
    uint32_t v[16][4][4];
};
struct Tables { Table t[2]; };
constexpr Tables make_tables() {
    Tables r = {};
    for (int rev = 0; rev < 2; rev++)
        for (int j = 0; j < 4; j++) {
            Table& t = r.t[rev];
            for (int q = 0; q < 8; q++) {
                uint32_t* e = t.route[4 * q + j];
                e[0] = 4 * q + 2 * (j & 1) + (j >> 1); e[1] = e[0] ^ 1;
                e[2] = j < 2 ? 0x5410u : 0x1054u; e[3] = e[2] + 0x2222u;
                e = t.u[q][j];
                for (int n = 0; n < 7; n++) e[0] |= ((n + j) % 7 < q ? 1u : 0u) << n;
                e[3] = e[0];
                for (int k = 0; k < 2; k++) {
                    const int step = 2 * k + (j >> 1), p0 = (step < 3 ? 16 * step : 40) + 8 * (j & 1);
                    uint32_t m = 0x8888u;
                    for (int n = 0; n < 8; n++) m |= ((p0 + n) % 7 < q ? 1u : 0u) << (2 * n);
                    e[1 + k] = m * 0x10001u;
                }
            }
            for (int sum = 0; sum < 15; sum++) {
                uint32_t* e = t.v[sum][j];
                for (int row = 0; row < 2; row++)
                    for (int b = 0; b < 14; b++) {
                        const int off = (sum + row) / 2, p = 4 * b + j;
                        const uint32_t bit = 1u << (2 * b + row);
                        if (p < 42 && p >= 7 * off) e[rev] |= bit;
                        if (p < 7 * off - 7) e[1 - rev] |= bit;
                        if (p >= 42 && p >= 7 * off && p < 7 * off + 49) e[2] |= bit;
                    }
                for (int n = 0; n < 6; n++)
                    if (8 * n + 2 * j < 42) e[3] |= 1u << (n + ((8 * n + 2 * j >= 7 * (sum / 2 & ~1)) != rev ? 0 : 8));
            }
        }
    return r;
}
__device__ __align__(128) const Tables g_tables = make_tables();

#define WO4(i) "=f"(d[i]), "=f"(d[i + 1]), "=f"(d[i + 2]), "=f"(d[i + 3])
#define RW4(i) "+f"(d[i]), "+f"(d[i + 1]), "+f"(d[i + 2]), "+f"(d[i + 3])

template <bool FIRST>
__device__ __forceinline__ void wgmma_n192(float (&d)[96], uint32_t a0, uint32_t a1, uint32_t a2, uint32_t a3, uint64_t descb) {
    if constexpr (FIRST) {
        asm volatile(
            "wgmma.mma_async.sync.aligned.m64n192k16.f32.bf16.bf16 "
            "{%0, %1, %2, %3, %4, %5, %6, %7, %8, %9, %10, %11, %12, %13, %14, %15, %16, %17, %18, %19, %20, %21, %22, %23, "
            "%24, %25, %26, %27, %28, %29, %30, %31, %32, %33, %34, %35, %36, %37, %38, %39, %40, %41, %42, %43, %44, %45, %46, %47, "
            "%48, %49, %50, %51, %52, %53, %54, %55, %56, %57, %58, %59, %60, %61, %62, %63, %64, %65, %66, %67, %68, %69, %70, %71, "
            "%72, %73, %74, %75, %76, %77, %78, %79, %80, %81, %82, %83, %84, %85, %86, %87, %88, %89, %90, %91, %92, %93, %94, %95}, "
            "{%96, %97, %98, %99}, %100, 0, 1, 1, 0;"
            : WO4(0), WO4(4), WO4(8), WO4(12), WO4(16), WO4(20), WO4(24), WO4(28), WO4(32), WO4(36), WO4(40), WO4(44),
              WO4(48), WO4(52), WO4(56), WO4(60), WO4(64), WO4(68), WO4(72), WO4(76), WO4(80), WO4(84), WO4(88), WO4(92)
            : "r"(a0), "r"(a1), "r"(a2), "r"(a3), "l"(descb));
    } else {
        asm volatile(
            "wgmma.mma_async.sync.aligned.m64n192k16.f32.bf16.bf16 "
            "{%0, %1, %2, %3, %4, %5, %6, %7, %8, %9, %10, %11, %12, %13, %14, %15, %16, %17, %18, %19, %20, %21, %22, %23, "
            "%24, %25, %26, %27, %28, %29, %30, %31, %32, %33, %34, %35, %36, %37, %38, %39, %40, %41, %42, %43, %44, %45, %46, %47, "
            "%48, %49, %50, %51, %52, %53, %54, %55, %56, %57, %58, %59, %60, %61, %62, %63, %64, %65, %66, %67, %68, %69, %70, %71, "
            "%72, %73, %74, %75, %76, %77, %78, %79, %80, %81, %82, %83, %84, %85, %86, %87, %88, %89, %90, %91, %92, %93, %94, %95}, "
            "{%96, %97, %98, %99}, %100, 1, 1, 1, 0;"
            : RW4(0), RW4(4), RW4(8), RW4(12), RW4(16), RW4(20), RW4(24), RW4(28), RW4(32), RW4(36), RW4(40), RW4(44),
              RW4(48), RW4(52), RW4(56), RW4(60), RW4(64), RW4(68), RW4(72), RW4(76), RW4(80), RW4(84), RW4(88), RW4(92)
            : "r"(a0), "r"(a1), "r"(a2), "r"(a3), "l"(descb));
    }
}

template <bool FIRST>
__device__ __forceinline__ void wgmma_n64(float (&d)[32], uint32_t a0, uint32_t a1, uint32_t a2, uint32_t a3, uint64_t descb) {
    if constexpr (FIRST) {
        asm volatile(
            "wgmma.mma_async.sync.aligned.m64n64k16.f32.bf16.bf16 "
            "{%0, %1, %2, %3, %4, %5, %6, %7, %8, %9, %10, %11, %12, %13, %14, %15, %16, %17, %18, %19, %20, %21, %22, %23, "
            "%24, %25, %26, %27, %28, %29, %30, %31}, "
            "{%32, %33, %34, %35}, %36, 0, 1, 1, 0;"
            : WO4(0), WO4(4), WO4(8), WO4(12), WO4(16), WO4(20), WO4(24), WO4(28)
            : "r"(a0), "r"(a1), "r"(a2), "r"(a3), "l"(descb));
    } else {
        asm volatile(
            "wgmma.mma_async.sync.aligned.m64n64k16.f32.bf16.bf16 "
            "{%0, %1, %2, %3, %4, %5, %6, %7, %8, %9, %10, %11, %12, %13, %14, %15, %16, %17, %18, %19, %20, %21, %22, %23, "
            "%24, %25, %26, %27, %28, %29, %30, %31}, "
            "{%32, %33, %34, %35}, %36, 1, 1, 1, 0;"
            : RW4(0), RW4(4), RW4(8), RW4(12), RW4(16), RW4(20), RW4(24), RW4(28)
            : "r"(a0), "r"(a1), "r"(a2), "r"(a3), "l"(descb));
    }
}

template <bool FIRST>
__device__ __forceinline__ void wgmma_n88(float (&d)[44], uint32_t a0, uint32_t a1, uint32_t a2, uint32_t a3, uint64_t descb) {
    if constexpr (FIRST) {
        asm volatile(
            "wgmma.mma_async.sync.aligned.m64n88k16.f32.bf16.bf16 "
            "{%0, %1, %2, %3, %4, %5, %6, %7, %8, %9, %10, %11, %12, %13, %14, %15, %16, %17, %18, %19, %20, %21, %22, %23, "
            "%24, %25, %26, %27, %28, %29, %30, %31, %32, %33, %34, %35, %36, %37, %38, %39, %40, %41, %42, %43}, "
            "{%44, %45, %46, %47}, %48, 0, 1, 1, 0;"
            : WO4(0), WO4(4), WO4(8), WO4(12), WO4(16), WO4(20), WO4(24), WO4(28), WO4(32), WO4(36), WO4(40)
            : "r"(a0), "r"(a1), "r"(a2), "r"(a3), "l"(descb));
    } else {
        asm volatile(
            "wgmma.mma_async.sync.aligned.m64n88k16.f32.bf16.bf16 "
            "{%0, %1, %2, %3, %4, %5, %6, %7, %8, %9, %10, %11, %12, %13, %14, %15, %16, %17, %18, %19, %20, %21, %22, %23, "
            "%24, %25, %26, %27, %28, %29, %30, %31, %32, %33, %34, %35, %36, %37, %38, %39, %40, %41, %42, %43}, "
            "{%44, %45, %46, %47}, %48, 1, 1, 1, 0;"
            : RW4(0), RW4(4), RW4(8), RW4(12), RW4(16), RW4(20), RW4(24), RW4(28), RW4(32), RW4(36), RW4(40)
            : "r"(a0), "r"(a1), "r"(a2), "r"(a3), "l"(descb));
    }
}

template <bool FIRST>
__device__ __forceinline__ void wgmma_n32(float (&d)[16], uint32_t a0, uint32_t a1, uint32_t a2, uint32_t a3, uint64_t descb) {
    if constexpr (FIRST) {
        asm volatile(
            "wgmma.mma_async.sync.aligned.m64n32k16.f32.bf16.bf16 "
            "{%0, %1, %2, %3, %4, %5, %6, %7, %8, %9, %10, %11, %12, %13, %14, %15}, "
            "{%16, %17, %18, %19}, %20, 0, 1, 1, 0;"
            : WO4(0), WO4(4), WO4(8), WO4(12)
            : "r"(a0), "r"(a1), "r"(a2), "r"(a3), "l"(descb));
    } else {
        asm volatile(
            "wgmma.mma_async.sync.aligned.m64n32k16.f32.bf16.bf16 "
            "{%0, %1, %2, %3, %4, %5, %6, %7, %8, %9, %10, %11, %12, %13, %14, %15}, "
            "{%16, %17, %18, %19}, %20, 1, 1, 1, 0;"
            : RW4(0), RW4(4), RW4(8), RW4(12)
            : "r"(a0), "r"(a1), "r"(a2), "r"(a3), "l"(descb));
    }
}

template <bool FIRST, int SEL>
__device__ __forceinline__ void wgmma_sp_n192_tb(float (&d)[96], uint32_t a0, uint32_t a1, uint32_t a2, uint32_t a3, uint64_t descb, uint32_t meta) {
    if constexpr (FIRST) {
        asm volatile(
            "wgmma.mma_async.sp.sync.aligned.m64n192k32.f32.bf16.bf16 "
            "{%0, %1, %2, %3, %4, %5, %6, %7, %8, %9, %10, %11, %12, %13, %14, %15, %16, %17, %18, %19, %20, %21, %22, %23, "
            "%24, %25, %26, %27, %28, %29, %30, %31, %32, %33, %34, %35, %36, %37, %38, %39, %40, %41, %42, %43, %44, %45, %46, %47, "
            "%48, %49, %50, %51, %52, %53, %54, %55, %56, %57, %58, %59, %60, %61, %62, %63, %64, %65, %66, %67, %68, %69, %70, %71, "
            "%72, %73, %74, %75, %76, %77, %78, %79, %80, %81, %82, %83, %84, %85, %86, %87, %88, %89, %90, %91, %92, %93, %94, %95}, "
            "{%96, %97, %98, %99}, %100, %101, %102, 0, 1, 1, 1;"
            : WO4(0), WO4(4), WO4(8), WO4(12), WO4(16), WO4(20), WO4(24), WO4(28), WO4(32), WO4(36), WO4(40), WO4(44),
              WO4(48), WO4(52), WO4(56), WO4(60), WO4(64), WO4(68), WO4(72), WO4(76), WO4(80), WO4(84), WO4(88), WO4(92)
            : "r"(a0), "r"(a1), "r"(a2), "r"(a3), "l"(descb), "r"(meta), "n"(SEL));
    } else {
        asm volatile(
            "wgmma.mma_async.sp.sync.aligned.m64n192k32.f32.bf16.bf16 "
            "{%0, %1, %2, %3, %4, %5, %6, %7, %8, %9, %10, %11, %12, %13, %14, %15, %16, %17, %18, %19, %20, %21, %22, %23, "
            "%24, %25, %26, %27, %28, %29, %30, %31, %32, %33, %34, %35, %36, %37, %38, %39, %40, %41, %42, %43, %44, %45, %46, %47, "
            "%48, %49, %50, %51, %52, %53, %54, %55, %56, %57, %58, %59, %60, %61, %62, %63, %64, %65, %66, %67, %68, %69, %70, %71, "
            "%72, %73, %74, %75, %76, %77, %78, %79, %80, %81, %82, %83, %84, %85, %86, %87, %88, %89, %90, %91, %92, %93, %94, %95}, "
            "{%96, %97, %98, %99}, %100, %101, %102, 1, 1, 1, 1;"
            : RW4(0), RW4(4), RW4(8), RW4(12), RW4(16), RW4(20), RW4(24), RW4(28), RW4(32), RW4(36), RW4(40), RW4(44),
              RW4(48), RW4(52), RW4(56), RW4(60), RW4(64), RW4(68), RW4(72), RW4(76), RW4(80), RW4(84), RW4(88), RW4(92)
            : "r"(a0), "r"(a1), "r"(a2), "r"(a3), "l"(descb), "r"(meta), "n"(SEL));
    }
}

#define TR(slot)
#define TRX(slot)
#define TRE(slot)
#define TRT(slot)
#define TRF(slot)
#define TRW(slot)
#define TRG(slot)
#define TRDUMP()

__device__ __forceinline__ void wg_fence() { asm volatile("wgmma.fence.sync.aligned;" ::: "memory"); }
__device__ __forceinline__ void wg_commit() { asm volatile("wgmma.commit_group.sync.aligned;" ::: "memory"); }
template <int N>
__device__ __forceinline__ void wg_wait() { asm volatile("wgmma.wait_group.sync.aligned %0;" ::"n"(N) : "memory"); }

template <int N>
__device__ __forceinline__ void pin(float (&d)[N]) {
#pragma unroll
    for (int i = 0; i < N; i++) asm volatile("" : "+f"(d[i])::"memory");
}
template <int N>
__device__ __forceinline__ void pin(uint32_t (&d)[N]) {
#pragma unroll
    for (int i = 0; i < N; i++) asm volatile("" : "+r"(d[i])::"memory");
}

constexpr uint64_t kDescRing = ((uint64_t)((1u << 30) | (1024u >> 4)) << 32) | (1u << 16) | (s_ring >> 4);
constexpr uint32_t kToV = ((kRingChunk >> 4) - 1) << 20;
__device__ __forceinline__ uint64_t desc_at(uint64_t base, uint32_t byte_off) {
    uint64_t d;
    asm volatile("add.s64 %0, %1, %2;" : "=l"(d) : "l"(base), "l"((uint64_t)(byte_off >> 4)));
    return d;
}

__device__ __forceinline__ void mbar_init(uint32_t bar, uint32_t count) {
    asm volatile("mbarrier.init.shared::cta.b64 [%0], %1;" ::"r"(bar), "r"(count) : "memory");
}
__device__ __forceinline__ void mbar_expect_tx(uint32_t bar, uint32_t bytes) {
    asm volatile("mbarrier.arrive.expect_tx.shared::cta.b64 _, [%0], %1;" ::"r"(bar), "r"(bytes) : "memory");
}
__device__ __forceinline__ void expect_tx_only(uint32_t bar, uint32_t bytes) {
    asm volatile("mbarrier.expect_tx.relaxed.cta.shared::cta.b64 [%0], %1;" ::"r"(bar), "r"(bytes) : "memory");
}
__device__ __forceinline__ void mbar_arrive(uint32_t bar) {
    asm volatile("mbarrier.arrive.shared::cta.b64 _, [%0];" ::"r"(bar) : "memory");
}
__device__ __forceinline__ void mbar_wait(uint32_t bar, uint32_t parity) {
    asm volatile(
        "{\n.reg .pred p;\n"
        "W: mbarrier.try_wait.parity.shared::cta.b64 p, [%0], %1;\n"
        "@!p bra W;\n}\n"
        ::"r"(bar), "r"(parity) : "memory");
}
__device__ __forceinline__ uint32_t clock_now() {
    uint32_t c;
    asm volatile("mov.u32 %0, %%clock;" : "=r"(c)::"memory");
    return c;
}
__device__ __forceinline__ void wait_until(uint32_t t0, int t) {
    if (t == 0) return;
    while ((int)(clock_now() - t0) < t) {}
}
__device__ __forceinline__ bool elect() {
    uint32_t ok;
    asm volatile("{\n.reg .pred p;\nelect.sync _|p, 0xffffffff;\nselp.u32 %0, 1, 0, p;\n}\n" : "=r"(ok));
    return ok != 0;
}
__device__ __forceinline__ void turn_wait(int wg) { asm volatile("bar.sync %0, 256;" ::"r"(1 + wg) : "memory"); }
__device__ __forceinline__ void turn_pass(int wg) { asm volatile("bar.arrive %0, 256;" ::"r"(2 - wg) : "memory"); }

__device__ __forceinline__ void tma_box(uint32_t dst, const CUtensorMap* map, uint32_t bar, int c0, int c2, int c3, int c4) {
    asm volatile(
        "cp.async.bulk.tensor.5d.shared::cluster.global.mbarrier::complete_tx::bytes [%0], [%1, {%3, %4, %5, %6, %7}], [%2];"
        ::"r"(dst), "l"(map), "r"(bar), "r"(c0), "r"(0), "r"(c2), "r"(c3), "r"(c4)
        : "memory");
}
__device__ __forceinline__ void tma_3d(uint32_t dst, const CUtensorMap* map, uint32_t bar, int c1, int c2) {
    asm volatile("cp.async.bulk.tensor.3d.shared::cluster.global.mbarrier::complete_tx::bytes [%0], [%1, {%3, %4, %5}], [%2];"
                 ::"r"(dst), "l"(map), "r"(bar), "r"(0), "r"(c1), "r"(c2)
                 : "memory");
}
__device__ __forceinline__ void prefetch_map(const CUtensorMap* map) {
    asm volatile("prefetch.tensormap [%0];" ::"l"(map) : "memory");
}
__device__ __forceinline__ uint4 ldg(const void* p) {
    uint4 v;
    asm volatile("ld.global.v4.u32 {%0, %1, %2, %3}, [%4];" : "=r"(v.x), "=r"(v.y), "=r"(v.z), "=r"(v.w) : "l"(p) : "memory");
    return v;
}
__device__ __forceinline__ uint32_t pack_bf16(float lo, float hi) {
    uint32_t r;
    asm("cvt.rn.bf16x2.f32 %0, %1, %2;" : "=r"(r) : "f"(hi), "f"(lo));
    return r;
}
__device__ __forceinline__ float ex2(float x) {
    float y;
    asm("ex2.approx.ftz.f32 %0, %1;" : "=f"(y) : "f"(x));
    return y;
}
__device__ __forceinline__ float rcp(float x) {
    float y;
    asm("rcp.approx.ftz.f32 %0, %1;" : "=f"(y) : "f"(x));
    return y;
}
__device__ __forceinline__ void mma16816(float (&d)[4], uint32_t a0, uint32_t a1, uint32_t a2, uint32_t a3, uint32_t b0, uint32_t b1) {
    asm volatile("mma.sync.aligned.m16n8k16.row.col.f32.bf16.bf16.f32 {%0, %1, %2, %3}, {%4, %5, %6, %7}, {%8, %9}, {%0, %1, %2, %3};"
                 : "+f"(d[0]), "+f"(d[1]), "+f"(d[2]), "+f"(d[3])
                 : "r"(a0), "r"(a1), "r"(a2), "r"(a3), "r"(b0), "r"(b1));
}
__device__ __forceinline__ uint4 lds128(uint32_t addr) {
    uint4 v;
    asm volatile("ld.volatile.shared.v4.u32 {%0, %1, %2, %3}, [%4];" : "=r"(v.x), "=r"(v.y), "=r"(v.z), "=r"(v.w) : "r"(addr) : "memory");
    return v;
}
__device__ __forceinline__ uint32_t lds_volatile(uint32_t addr) {
    uint32_t v;
    asm volatile("ld.volatile.shared.u32 %0, [%1];" : "=r"(v) : "r"(addr) : "memory");
    return v;
}

__device__ __forceinline__ int window_start(int n) { return min(max(n, 0), 105); }
__device__ __forceinline__ int origin_u(int u) { return min(max(u, 0), 98); }

struct Work {
    int u, v;
    int step;
    uint32_t su, sv;
    uint32_t base;
    bool corner;
    int ntiles;
    __device__ __forceinline__ void pixel_offsets(int qu, int qv, int j, uint32_t& o0, uint32_t& o1) const {
        const uint32_t b = (qu + window_start(qu)) * su + j * 16 + base;
        o0 = b + (qv + window_start(qv)) * sv;
        o1 = b + (qv + 1 + window_start(qv + 1)) * sv;
    }
};

__device__ __forceinline__ Work decode_work(int c) {
    Work w;
    const bool transposed = (c >> 4) == 7;
    const int px = 6 * (c & 1), py = 3 * (c & 2);
    w.corner = c >= 128;
    w.step = 8 - 4 * (c & 4);
    w.u = (c < 112 ? c & ~7 : 96 + (c & 8)) + (transposed ? py : px) - 6;
    w.v = (w.corner ? 96 : 48 - 2 * (c & 4)) + (transposed ? px : py) - 6;
    w.su = transposed ? kHW * kPixBytes : kPixBytes;
    w.sv = transposed ? kPixBytes : kHW * kPixBytes;
    w.base = px * (kPixBytes / 6) + py * (kHW * kPixBytes / 6) + 6 * (kHW + 1) * kPixBytes;
    w.ntiles = w.corner ? 4 : 6;
    return w;
}

struct RawX { uint4 a[6], b[6]; };
__device__ __forceinline__ void load_raw(RawX& r, const uint8_t* base, uint32_t o0, uint32_t o1) {
    __syncwarp();
#pragma unroll
    for (int c = 0; c < 6; c++) { r.a[c] = ldg(base + o0 + c * 64); r.b[c] = ldg(base + o1 + c * 64); }
    __syncwarp();
}
__device__ __forceinline__ void raw_to_frags(const RawX& r, uint32_t zero, uint32_t (&f)[48]) {
#pragma unroll
    for (int c = 0; c < 6; c++) {
        asm volatile("{\n.reg .b32 t, u;\nadd.u32 t, %4, %8;\nadd.u32 u, %5, %8;\nxor.b32 %0, %6, %8;\nxor.b32 %1, %7, %8;\n"
                     "xor.b32 %2, t, %8;\nxor.b32 %3, u, %8;\n}\n"
                     : "=&r"(f[8 * c + 1]), "=&r"(f[8 * c + 3]), "=&r"(f[8 * c + 4]), "=&r"(f[8 * c + 6])
                     : "r"(r.a[c].y), "r"(r.a[c].w), "r"(r.b[c].x), "r"(r.b[c].z), "r"(zero));
        f[8 * c + 0] = r.a[c].x; f[8 * c + 2] = r.a[c].z; f[8 * c + 5] = r.b[c].y; f[8 * c + 7] = r.b[c].w;
    }
}
__device__ __forceinline__ void acc_to_frags(const float (&d)[96], uint32_t (&f)[48]) {
#pragma unroll
    for (int i = 0; i < 48; i++) f[i] = pack_bf16(d[2 * i], d[2 * i + 1]);
}

template <class F>
__device__ __forceinline__ void proj_gemm(float (&d)[96], const uint32_t (&a)[48], uint64_t dsc, uint32_t img, F after) {
#pragma unroll
    for (int s = 0; s < 12; s++) {
        if (s == 0) wgmma_n192<true>(d, a[4 * s], a[4 * s + 1], a[4 * s + 2], a[4 * s + 3], desc_at(dsc, img - s_ring + (s >> 2) * kWChunk + (s & 3) * 32));
        else wgmma_n192<false>(d, a[4 * s], a[4 * s + 1], a[4 * s + 2], a[4 * s + 3], desc_at(dsc, img - s_ring + (s >> 2) * kWChunk + (s & 3) * 32));
        if (s == 11) wg_commit();
        after(s);
    }
}
__device__ __forceinline__ void pack_out(const float (&acc)[96], uint32_t (&po)[48]) {
#pragma unroll
    for (int g = 0; g < 6; g++)
#pragma unroll
        for (int q = 0; q < 4; q++) {
            po[8 * g + q] = pack_bf16(acc[16 * g + 4 * q], acc[16 * g + 4 * q + 1]);
            po[8 * g + 4 + q] = pack_bf16(acc[16 * g + 4 * q + 2], acc[16 * g + 4 * q + 3]);
        }
}
template <bool PINNED = true>
__device__ __forceinline__ void store_one(bool on, uint8_t* p0, uint8_t* p1, const uint32_t (&po)[48], int n) {
    if (PINNED) __syncwarp();
    asm volatile("{\n.reg .pred p;\nsetp.ne.u32 p, %5, 0;\n@p st.global.v4.u32 [%0], {%1, %2, %3, %4};\n}\n"
                 ::"l"(((n & 1) ? p1 : p0) + (n >> 1) * 64), "r"(po[4 * n]), "r"(po[4 * n + 1]), "r"(po[4 * n + 2]), "r"(po[4 * n + 3]), "r"((uint32_t)on) : "memory");
}

template <int N>
__device__ __forceinline__ float tree_max(const float (&v)[N]) {
    float t[N];
#pragma unroll
    for (int i = 0; i < N; i++) t[i] = v[i];
#pragma unroll
    for (int w = 1; w < N; w *= 2)
#pragma unroll
        for (int i = 0; i + w < N; i += 2 * w) t[i] = fmaxf(t[i], t[i + w]);
    return t[0];
}
template <int N>
__device__ __forceinline__ float tree_sum(const float (&v)[N]) {
    float t[N];
#pragma unroll
    for (int i = 0; i < N; i++) t[i] = v[i];
#pragma unroll
    for (int w = 1; w < N; w *= 2)
#pragma unroll
        for (int i = 0; i + w < N; i += 2 * w) t[i] += t[i + w];
    return t[0];
}

template <int T, class F>
__device__ __forceinline__ void third_gemm(float (&d)[32], const uint32_t (&a)[48], uint64_t dsc, F after) {
#pragma unroll
    for (int s = 0; s < 12; s++) {
        if (s == 0) wgmma_n64<true>(d, a[4 * s], a[4 * s + 1], a[4 * s + 2], a[4 * s + 3], desc_at(dsc, s_wv - s_ring + T * 8192 + (s >> 2) * kWChunk + (s & 3) * 32));
        else wgmma_n64<false>(d, a[4 * s], a[4 * s + 1], a[4 * s + 2], a[4 * s + 3], desc_at(dsc, s_wv - s_ring + T * 8192 + (s >> 2) * kWChunk + (s & 3) * 32));
        if (s == 11) wg_commit();
        after(s);
    }
}
template <int T>
__device__ __forceinline__ void third_pack(float (&d)[32], float i0, float i1, uint32_t (&po)[48]) {
    pin(d);
#pragma unroll
    for (int g = 0; g < 2; g++)
#pragma unroll
        for (int q = 0; q < 4; q++) {
            po[16 * T + 8 * g + q] = pack_bf16(d[16 * g + 4 * q] * i0, d[16 * g + 4 * q + 1] * i0);
            po[16 * T + 8 * g + 4 + q] = pack_bf16(d[16 * g + 4 * q + 2] * i1, d[16 * g + 4 * q + 3] * i1);
        }
}

template <int B>
__device__ __forceinline__ void pick(uint32_t h, uint32_t ok, const float* s, float& v0, float& v1) {
    asm("{\n.reg .pred p, q0, q1;\n.reg .b32 t;\nand.b32 t, %6, %7;\nsetp.ne.u32 p, t, 0;\n"
        "and.b32 t, %8, %9;\nsetp.ne.u32 q0, t, 0;\nand.b32 t, %8, %10;\nsetp.ne.u32 q1, t, 0;\n"
        "@q0 selp.f32 %0, %3, %2, p;\n@q1 selp.f32 %1, %5, %4, p;\n}\n"
        : "+f"(v0), "+f"(v1)
        : "f"(s[0]), "f"(s[1]), "f"(s[2]), "f"(s[3]), "r"(h), "n"(1 << ((4 * B) % 7)), "r"(ok), "n"(1 << (2 * B)), "n"(2 << (2 * B)));
}
template <int B, class F>
__device__ __forceinline__ void for_blocks(F f) {
    if constexpr (B > 0) { for_blocks<B - 1>(f); f(std::integral_constant<int, B - 1>{}); }
}
__device__ __forceinline__ void gather_outer(const float (&s)[44], uint32_t h, uint32_t ok, float (&v0)[14], float (&v1)[14]) {
    for_blocks<11>([&](auto B) {
        constexpr int b = B.value < 8 ? (B.value >> 1) + 7 * (B.value & 1) : B.value - 4;
        pick<b>(h, ok, &s[4 * b], v0[b], v1[b]);
    });
}
__device__ __forceinline__ void gather_mid(const float (&sE)[16], uint32_t h, uint32_t ok, float (&v0)[14], float (&v1)[14]) {
    for_blocks<4>([&](auto B) { pick<10 + B.value>(h, ok, &sE[4 * B.value], v0[10 + B.value], v1[10 + B.value]); });
}
__device__ __forceinline__ float quad_max(float m) {
    m = fmaxf(m, __shfl_xor_sync(0xffffffffu, m, 1));
    return fmaxf(m, __shfl_xor_sync(0xffffffffu, m, 2));
}
__device__ __forceinline__ float quad_sum(float s) {
    s += __shfl_xor_sync(0xffffffffu, s, 1);
    return s + __shfl_xor_sync(0xffffffffu, s, 2);
}
template <int B0, int B1>
__device__ __forceinline__ void exp_route(float (&v0)[14], float (&v1)[14], float m0, float m1, const uint4& r, bool even, uint32_t (&y)[14]) {
#pragma unroll
    for (int b = B0; b < B1; b++) { v0[b] = ex2(v0[b] - m0); v1[b] = ex2(v1[b] - m1); }
#pragma unroll
    for (int b = B0; b < B1; b += 2) {
        const uint32_t x0 = pack_bf16(v0[b], v1[b]), x1 = pack_bf16(v0[b + 1], v1[b + 1]);
        const uint32_t u = __shfl_sync(0xffffffffu, even ? x0 : x1, r.x);
        const uint32_t w = __shfl_sync(0xffffffffu, even ? x1 : x0, r.y);
        y[b] = __byte_perm(u, w, r.z); y[b + 1] = __byte_perm(u, w, r.w);
    }
}
template <int BIT0, int N0, int N1>
__device__ __forceinline__ void unfold(const uint32_t (&y)[14], uint32_t fold, uint32_t (&p)[12]) {
    for_blocks<N1 - N0>([&](auto N) {
        constexpr int n = N0 + N.value;
        asm("{\n.reg .pred p;\n.reg .b32 t;\nand.b32 t, %4, %5;\nsetp.ne.u32 p, t, 0;\nselp.b32 %0, %2, 0, p;\nselp.b32 %1, %3, 0, p;\n}\n"
            : "=r"(p[2 * n]), "=r"(p[2 * n + 1]) : "r"(y[2 * n]), "r"(y[2 * n + 1]), "r"(fold), "n"(1 << (BIT0 + n)));
    });
}
__device__ __forceinline__ void keep(bool never, uint32_t a, uint32_t b, uint32_t c, uint32_t d) {
    asm volatile("{\n.reg .pred p;\nsetp.ne.u32 p, %4, 0;\n@p st.volatile.shared.v4.u32 [%5], {%0, %1, %2, %3};\n}\n"
                 ::"r"(a), "r"(b), "r"(c), "r"(d), "r"((uint32_t)never), "r"(s_trace) : "memory");
}

__device__ __forceinline__ uint32_t wimg_offset(uint32_t row, uint32_t s, uint32_t j) {
    return (s >> 2) * kWChunk + row * 128 + (((2 * (s & 3) + (j >> 1)) ^ (row & 7)) << 4) + (j & 1) * 8;
}

__device__ __forceinline__ void ldsm4(uint32_t (&r)[4], uint32_t addr) {
    asm volatile("ldmatrix.sync.aligned.m8n8.x4.shared.b16 {%0, %1, %2, %3}, [%4];" : "=r"(r[0]), "=r"(r[1]), "=r"(r[2]), "=r"(r[3]) : "r"(addr) : "memory");
}
__device__ __forceinline__ void ldsm4_t(uint32_t (&r)[4], uint32_t addr) {
    asm volatile("ldmatrix.sync.aligned.m8n8.x4.trans.shared.b16 {%0, %1, %2, %3}, [%4];" : "=r"(r[0]), "=r"(r[1]), "=r"(r[2]), "=r"(r[3]) : "r"(addr) : "memory");
}
struct MOperands { uint4 A[2][2], B[4][2]; };
__device__ __forceinline__ void m_load(MOperands& m, const uint8_t* wqkv, uint32_t mt, uint32_t s, uint32_t q, uint32_t lane) {
    const uint32_t r8 = lane >> 2, col = q * 128 + (lane & 3) * 16;
    const uint8_t* pa = wqkv + (16 * mt + r8) * 1152 + col;
    const uint8_t* pb = wqkv + (16 * s + 8 * (r8 & 2) + (r8 & 5)) * 1152 + col;
#pragma unroll
    for (int c = 0; c < 2; c++) {
#pragma unroll
        for (int h = 0; h < 2; h++) m.A[h][c] = ldg(pa + 384 + h * 8 * 1152 + c * 64);
#pragma unroll
        for (int n = 0; n < 4; n++) m.B[n][c] = ldg(pb + ((n & 1) * 8 + (n & 2)) * 1152 + c * 64);
    }
}
__device__ __forceinline__ void m_partial(MOperands& m, uint32_t q, uint32_t lane, uint32_t zero) {
    auto& A = m.A;
    auto& B = m.B;
#pragma unroll
    for (int i = 0; i < 4; i++) { uint4& a = A[i >> 1][i & 1]; a.x ^= zero; a.y ^= zero; a.z ^= zero; a.w ^= zero; }
#pragma unroll
    for (int n = 0; n < 4; n++) {
        float d[4] = {0.f, 0.f, 0.f, 0.f};
#pragma unroll
        for (int c = 0; c < 2; c++) {
            mma16816(d, A[0][c].x, A[1][c].x, A[0][c].y, A[1][c].y, B[n][c].x, B[n][c].y);
            mma16816(d, A[0][c].z, A[1][c].z, A[0][c].w, A[1][c].w, B[n][c].z, B[n][c].w);
        }
        asm volatile("st.shared.v4.f32 [%0], {%1, %2, %3, %4};" ::"r"(s_wv + q * 2048 + n * 512 + lane * 16), "f"(d[0]), "f"(d[1]), "f"(d[2]), "f"(d[3]) : "memory");
    }
}
__device__ __forceinline__ void m_reduce(uint32_t e, uint32_t lane, float (&d)[2][4]) {
#pragma unroll
    for (int n = 0; n < 2; n++) {
        float t[3][4];
#pragma unroll
        for (int q = 0; q < 3; q++)
            asm volatile("ld.shared.v4.f32 {%0, %1, %2, %3}, [%4];" : "=f"(t[q][0]), "=f"(t[q][1]), "=f"(t[q][2]), "=f"(t[q][3]) : "r"(s_wv + q * 2048 + e * 1024 + n * 512 + lane * 16) : "memory");
#pragma unroll
        for (int i = 0; i < 4; i++) d[n][i] = (t[0][i] + t[1][i] + t[2][i]) * kScaleLog2e;
    }
}
__device__ __forceinline__ void w_piece(uint32_t q, uint32_t lane, float (&d)[2][4]) {
    const uint32_t rr = lane & 7, mi = lane >> 3, kr = 4 * (rr >> 1) + (mi & 2) + (rr & 1);
    const uint32_t pa = s_wv + q * 32 + (4 * (mi & 2) + rr) * 96 + ((mi & 1) << 4);
    const uint32_t pb = s_wv + 3 * 6144 + kr * 128 + (((mi & 1) ^ (kr & 7)) << 4);
    float e[2][4];
#pragma unroll
    for (int i = 0; i < 8; i++) (&d[0][0])[i] = (&e[0][0])[i] = 0.f;
#pragma unroll
    for (int k = 0; k < 12; k++) {
        uint32_t aq[4], bq[4];
        ldsm4_t(aq, pa + k * 1536);
        ldsm4(bq, (pb ^ ((k & 3) << 5)) + (k >> 2) * 2048);
        mma16816(k & 1 ? e[0] : d[0], aq[0], aq[1], aq[2], aq[3], bq[0], bq[1]);
        mma16816(k & 1 ? e[1] : d[1], aq[0], aq[1], aq[2], aq[3], bq[2], bq[3]);
    }
#pragma unroll
    for (int i = 0; i < 8; i++) (&d[0][0])[i] += (&e[0][0])[i];
}
__device__ __forceinline__ uint32_t piece_offset(uint32_t which, uint32_t s, uint32_t mt, uint32_t lane) {
    const uint32_t r8 = lane >> 2;
    return which * kWBytes + wimg_offset(which ? 32 * (mt >> 1) + 8 * (r8 >> 1) + 4 * (mt & 1) + (r8 & 1) : 16 * mt + r8, s, lane & 3);
}
__device__ __forceinline__ void piece_store(Scratch* g, uint32_t par, uint32_t off0, uint32_t which, const float (&d)[2][4]) {
#pragma unroll
    for (int hf = 0; hf < 2; hf++) {
        const uint32_t off = off0 ^ (hf ? which ? 288 : 1024 : 0);
        const uint32_t a = pack_bf16(d[0][2 * hf], d[0][2 * hf + 1]), b = pack_bf16(d[1][2 * hf], d[1][2 * hf + 1]);
        asm volatile("st.relaxed.gpu.global.v2.u32 [%0], {%1, %2};" ::"l"(g->img[0][0] + (par + off)), "r"(a ? a : 0x8000u), "r"(b) : "memory");
    }
}
__device__ __forceinline__ void piece_clear(Scratch* g, uint32_t par, uint32_t off0, uint32_t which) {
#pragma unroll
    for (int hf = 0; hf < 2; hf++)
        asm volatile("st.relaxed.gpu.global.v2.u32 [%0], {%1, %1};" ::"l"(g->img[0][0] + (par + (off0 ^ (hf ? which ? 288 : 1024 : 0)))), "r"(0) : "memory");
}

__device__ __forceinline__ uint32_t ld_relaxed(const uint32_t* p) {
    uint32_t v;
    asm volatile("ld.relaxed.gpu.global.u32 %0, [%1];" : "=r"(v) : "l"(p) : "memory");
    return v;
}
__device__ __forceinline__ void count_up(uint32_t* p) {
    asm volatile("red.relaxed.gpu.global.add.u32 [%0], %1;" ::"l"(p), "r"(1) : "memory");
}
__device__ __forceinline__ void bulk_g2s(uint32_t dst, const void* src, uint32_t bytes, uint32_t bar) {
    asm volatile("cp.async.bulk.shared::cluster.global.mbarrier::complete_tx::bytes [%0], [%1], %2, [%3];"
                 ::"r"(dst), "l"(src), "r"(bytes), "r"(bar)
                 : "memory");
}

__global__ void __launch_bounds__(kThreads, 1)
nat_fused_kernel(const uint8_t* __restrict__ x, const uint8_t* __restrict__ wqkv, uint8_t* __restrict__ out, Scratch* g,
                 const uint8_t* wo, uint64_t dsc, const __grid_constant__ Maps maps) {
    const int tid = threadIdx.x, lane = tid & 31;
    const int warp = __shfl_sync(0xffffffffu, tid >> 5, 0);
    const int wg = warp >> 2, wq = warp & 3, r8 = lane >> 2, j = lane & 3;
    const int cta = blockIdx.x;
    const Work w = decode_work(cta);
    const uint32_t jq = (cta < 124 ? cta + 8 : cta - 124) / 11u, jr = (cta < 124 ? cta + 8 : cta - 124) - 11 * jq;
    const uint32_t which = jr >= 6, jhi = which ? jr - 6 : jq, jlo = which ? jq : 2 * jr;
    const bool has_job = jr < 10;
    if (wg == 2 && wq < 3) {
#pragma unroll
        for (int r = 0; r < 3; r++)
            asm volatile("st.shared.v4.u32 [%0], {%1, %1, %1, %1};" ::"r"(s_ring + wq * kRingChunk + (r == 0 ? 84 : r == 1 ? 88 : 204) * 128 + lane * 16), "r"(0) : "memory");
        asm volatile("fence.proxy.async.shared::cta;" ::: "memory");
    }
    MOperands mo;
    uint32_t launch = 0;
    if (wg == 1 && wq < 3 && !which) m_load(mo, wqkv, jhi, jlo, wq, lane);
    if (warp == 7) launch = ld_relaxed(g->launches[cta]);
    if (x == nullptr) return;
    const uint32_t t_start = clock_now();
    if (wg == 2) {
        asm volatile("setmaxnreg.dec.sync.aligned.u32 24;");
        if (wq < 3) {
            if (lane < 3 && cta < 128) {
                const uint32_t row = 3 * (cta >> 1) + wq;
                asm volatile("prefetch.global.L2 [%0];" ::"l"((cta & 1 ? wo + row * 384 : wqkv + row * 1152 + 768) + lane * 128));
            }
            asm volatile("bar.sync 7, 192;" ::: "memory");
            const uint32_t par = lds_volatile(s_par);
            uint32_t phase = 0;
#pragma unroll 1
            for (uint32_t c = 0; c < 6; c++) {
                const uint32_t part = c * kWChunk + wq * (kWChunk / 3);
                mbar_wait(bar_img + 8 * c, 0);
                if (c == 0 && lane == 0) mbar_arrive(bar_ok);
                if (wq == 0) TRW(10 + c);
#pragma unroll 1
                while (true) {
                    uint32_t lo = ~0u;
#pragma unroll
                    for (int q = 0; q < 8; q++) lo = min(lo, lds_volatile(s_m + part + lane * 32 + (lane & 12) * 2 + q * 1024));
                    if (__all_sync(0xffffffffu, lo) || phase > 65535) break;
                    if (elect()) {
                        mbar_expect_tx(bar_redo + 8 * wq, kWChunk / 3);
                        bulk_g2s(s_m + part, g->img[0][0] + par + part, kWChunk / 3, bar_redo + 8 * wq);
                    }
                    mbar_wait(bar_redo + 8 * wq, phase++ & 1);
                }
                if (c == 2 && phase) asm volatile("st.shared.u32 [%0], %1;" ::"r"(s_again), "r"(1) : "memory");
                if ((c == 2 || c == 5) && lane == 0) mbar_arrive(bar_ok + (c == 2 ? 8 : 16));
            }
        } else {
            const CUtensorMap* map = &maps.m[w.sv == kPixBytes ? 2 : 0];
            if (elect()) {
#pragma unroll
                for (int i = 0; i < 24; i++) mbar_init(s_bar + 8 * i, i < 15 ? 1 : i < 18 ? 3 : 4);
                asm volatile("fence.mbarrier_init.release.cluster;" ::: "memory");
                prefetch_map(map + 1);
                expect_tx_only(bar_a, sizeof(Table));
                bulk_g2s(s_tab, &maps.tables->t[w.step < 0], sizeof(Table), bar_a);
            }
            if (which && has_job && elect()) {
                mbar_expect_tx(bar_wop, 4 * 6144);
                tma_3d(s_wv, &maps.wo, bar_wop, 0, jhi);
                tma_3d(s_wv + 3 * 6144, &maps.wv, bar_wop, 16 * jlo, 6);
            }
            int u = w.u, v = w.v;
            uint32_t wait_bar = bar_use, wait_par = 1, slot = 0;
#pragma unroll 1
            for (int step = 0; step < 7 - w.corner; step++) {
                const bool first = step == 0 || (w.corner && step == 4);
                const int ou = origin_u(u);
                const bool final = step == 6 - w.corner;
                if (final) { wait_bar = bar_free; wait_par = 0; }
#pragma unroll 1
                for (uint32_t bar = first ? bar_a : bar_b; bar <= (first ? bar_a : bar_mid); bar += 8) {
                    mbar_wait(bar, first ? !step : slot != 0);
                    if (elect()) mbar_expect_tx(bar, first ? 3 * kSlotBytes : bar < bar_mid ? kSlotBytes : 3 * kMidBytes);
                }
                int row = v + 4 + (first ? -w.step : w.step) / 2;
                uint32_t dst = final ? s_m : s_ring + (first ? 0 : slot), bar = first ? bar_a : bar_b, dbar = first ? 0 : 8;
#pragma unroll 1
                for (int r = 0; r < 2 - first; r++) {
                    mbar_wait(wait_bar, wait_par);
                    if (r == 0) TRW(24 + step);
#pragma unroll
                    for (int n = 0; n < 3; n++) {
                        if (n && final) mbar_wait(bar_free + 8 * n, 0);
                        if (elect()) tma_box(dst + n * kRingChunk, map + r, bar + n * dbar, (cta & 1) * kC + 64 * n, ou, (cta >> 1) & 1, row);
                    }
                    row = v + 6; bar = bar_mid; dbar = 0;
                    dst = (final ? s_m : s_ring) + kOffMid + 512;
                    if (wait_bar == bar_use) wait_bar = bar_use + 16;
                }
                TRW(32 + 8 * step + 4);
                if (step == 0) {
                    asm volatile("st.shared.v2.u32 [%0], {%1, %1};" ::"r"(s_late), "r"(0) : "memory");
                    asm volatile("bar.arrive 3, 160;\nbar.arrive 4, 160;\nbar.arrive 8, 128;\nbar.sync 9, 64;" ::: "memory");
                }
                if (step < 2) {
                    if (step) {
                        asm volatile("bar.sync 6, 128;" ::: "memory");
                    }
                    const uint32_t par = __shfl_sync(0xffffffffu, lds_volatile(s_par), 0);
                    wait_until(t_start, step ? TN(5, kTimeW) : TN(6, kTimeM));
                    TRW(5 + 4 * step);
#pragma unroll 1
                    for (int c = 3 * step; c < 3 + 3 * step; c++)
                        if (elect()) {
                            mbar_expect_tx(bar_img + 8 * c, kWChunk);
                            bulk_g2s(s_m + c * kWChunk, g->img[0][0] + (par + c * kWChunk), kWChunk, bar_img + 8 * c);
                        }
                }
                const bool again = w.corner && step == 3;
                wait_bar = step == 0 ? bar_img + 8 * TN(1, 1) : again ? bar_use + 8 : bar_use;
                if (!again) {
                    wait_par = slot ? 0 : step != 0;
                    slot ^= kSlotStride;
                    if (w.corner && step == 2) { u += 8; v -= 8; } else if (step) v += w.step;
                }
            }
        }
        TRDUMP();
        return;
    }
    if (warp == 7) {
        asm volatile("st.shared.u32 [%0], %1;\nbar.arrive 9, 64;" ::"r"(s_par), "r"((launch & 1) * 2 * kWBytes) : "memory");
        g->launches[cta][lane] = launch + 1;
        asm volatile("bar.arrive 5, 128;" ::: "memory");
    }
    if (wg == 1 && wq < 3) {
        if (!which) m_partial(mo, wq, lane, (uint32_t)dsc & 1);
        const uint32_t off = piece_offset(which, which ? jlo : jlo + wq, which ? 3 * jhi + wq : jhi, lane);
        asm volatile("bar.sync %0, %1;" ::"r"(5 + (off >> 31)), "n"(128) : "memory");
        const uint32_t par = lds_volatile(s_par);
        if (which) asm volatile("bar.sync 8, 128;" ::: "memory");
        if (has_job && wq < 2 + which) {
            float d[2][4];
            if (wq == 0) TRX(which ? 1 : 18);
            if (which) {
                mbar_wait(bar_wop, 0);
                if (wq == 0) TRX(2);
                w_piece(wq, lane, d);
            } else {
                m_reduce(wq, lane, d);
            }
            piece_store(g, par, off, which, d);
            __syncwarp();
            piece_clear(g, 2 * kWBytes - par, off, which);
            if (wq == 0) TRX(which ? 3 : 0);
        }
        if (!which) asm volatile("bar.sync 8, 128;" ::: "memory");
        asm volatile("bar.arrive 7, 192;\nbar.arrive 6, 128;" ::: "memory");
    }
    const int order = w.step < 0 ? warp ^ 3 : warp;
    int tu = w.u, tv = w.v + w.step * wg;
    const int du2 = w.corner ? 8 : 0, dv2 = w.corner ? 0 : 2 * w.step;
    uint32_t o0, o1;
    wait_until(t_start, START_TIME);
    asm volatile("setmaxnreg.inc.sync.aligned.u32 240;");
    w.pixel_offsets(tu + r8, tv + 2 * wq, j, o0, o1);
    uint32_t fa[48];
    {
        RawX raw;
        load_raw(raw, x, o0, o1);
        asm volatile("bar.sync %0, 160;" ::"r"(3 + wg) : "memory");
        raw_to_frags(raw, 0, fa);
        pin(fa);
    }
    mbar_wait(bar_ok, 0);
    const uint64_t dA = dsc + wg * (kSlotStride >> 4), dB = dsc + (wg ^ 1) * (kSlotStride >> 4);

    float acc[96];
    uint32_t po[48];
    uint32_t c0 = 0, c1 = 0;
#pragma unroll
    for (int q = 0; q < 48; q++) asm volatile("" : "=r"(po[q]));
#pragma unroll 1
    for (int i = wg; i < w.ntiles; i += 2) {
        const bool first = i == 0, last = i == w.ntiles - 1;

        TRF(8 + 16 * k);
        uint8_t *p0 = out + c0, *p1 = out + c1;
#pragma unroll 1
        for (uint32_t seen = 0;;) {
        wg_fence();
        if (!first) turn_wait(wg);
        proj_gemm(acc, fa, dsc, s_m, [&](int s) {
            if (s == 11 && !first) turn_pass(wg);
            const int n = __builtin_popcount(QSLOTS & ((1 << s) - 1));
            if (((QSLOTS >> s) & 1) && n < 12) store_one(i >= 2, out + c0, out + c1, po, n);
            if (s == 3 || s == 7) { wg_commit(); mbar_wait(bar_img + 2 * s + 2, 0); wg_fence(); }
        });
        __syncwarp();
        TRF(9 + 16 * k);
            if (!first) break;
            mbar_wait(bar_ok + 8, 0);
            if (lds_volatile(s_again) == seen) break;
            wg_wait<0>();
            seen = 1;
        }
        c0 = o0; c1 = o1;
        w.pixel_offsets(tu + du2 + r8, tv + dv2 + 2 * wq, j, o0, o1);
        if (i + 2 >= w.ntiles) o0 = o1 = 0;
        mbar_wait(bar_a, w.corner ? i >> 1 : 0);
        wg_wait<2>();
        if (last && lane == 0) mbar_arrive(bar_free);
        wg_wait<1>();
        if (last && lane == 0) mbar_arrive(bar_free + 8);
#pragma unroll
        for (int s = 12; s < 14; s++)
            if ((QSLOTS >> s) & 1) { store_one(i >= 2, p0, p1, po, __builtin_popcount(QSLOTS & ((1 << s) - 1))); __syncwarp(); }
        wg_wait<0>();
        if (last && lane == 0) mbar_arrive(bar_free + 16);
        const uint64_t dE = last ? dsc + ((s_m - s_ring) >> 4) : dsc, dN = last ? dE : dB;
        pin(acc);
        TR(11 + 16 * k);
        TRT(80 + k);
#pragma unroll
        for (int n = __builtin_popcount(QSLOTS); n < 12 - __builtin_popcount(ASLOTS) - __builtin_popcount(BSLOTS); n++) store_one(i >= 2, p0, p1, po, n);
        acc_to_frags(acc, fa);
        pin(fa);

        float sA[44], sE[16], sB[44];
        RawX nxt;
        if (!first) turn_wait(wg);
        wg_fence();
#pragma unroll
        for (int s = 0; s < 12; s++) {
            if (s == 0) wgmma_n88<true>(sA, fa[4 * s], fa[4 * s + 1], fa[4 * s + 2], fa[4 * s + 3], desc_at(dA, (s >> 2) * kRingChunk + (s & 3) * 32));
            else wgmma_n88<false>(sA, fa[4 * s], fa[4 * s + 1], fa[4 * s + 2], fa[4 * s + 3], desc_at(dA, (s >> 2) * kRingChunk + (s & 3) * 32));
            if (s == 11) { wg_commit(); if (!first) turn_pass(wg); }
            if ((ASLOTS >> s) & 1) store_one(i >= 2, p0, p1, po, 12 - __builtin_popcount(BSLOTS) - __builtin_popcount(ASLOTS >> s));
        }
#pragma unroll
        for (int s = 12; s < 16; s++)
            if ((ASLOTS >> s) & 1) store_one(i >= 2, p0, p1, po, 12 - __builtin_popcount(BSLOTS) - __builtin_popcount(ASLOTS >> s));
        TRF(12 + 16 * k);
        const int vq = tv + 2 * wq;
        const uint4 tabu = lds128(s_tab + offsetof(Table, u) + (window_start(tu + r8) - origin_u(tu)) * 64 + j * 16);
        const uint4 tabv = lds128(s_tab + offsetof(Table, v) + (window_start(vq) + window_start(vq + 1) - 2 * tv) * 64 + j * 16);
        const uint4 route = lds128(s_tab + lane * 16);
        load_raw(nxt, x, o0, o1);
        float v0[14], v1[14];
#pragma unroll
        for (int b = 0; b < 14; b++) {
            v0[b] = __uint_as_float((b > 10 ? route.x >> (b + 2) : 0u) | 0xff800000u);
            v1[b] = __uint_as_float((b > 10 ? route.x >> (b + 5) : 0u) | 0xff800000u);
        }
        wg_wait<0>();
        pin(sA);
        gather_outer(sA, tabu.x, tabv.x, v0, v1);
        pin(v0); pin(v1);
        if (!first) turn_wait(wg);
#pragma unroll
        for (int c = 0; c < 3; c++) {
            mbar_wait(bar_b + 8 * c, wg);
            TRF(64 + 4 * k + c);
            wg_fence();
#pragma unroll
            for (int s = 4 * c; s < 4 * c + 4; s++) {
                if (s == 0) wgmma_n88<true>(sB, fa[4 * s], fa[4 * s + 1], fa[4 * s + 2], fa[4 * s + 3], desc_at(dN, c * kRingChunk + (s & 3) * 32));
                else wgmma_n88<false>(sB, fa[4 * s], fa[4 * s + 1], fa[4 * s + 2], fa[4 * s + 3], desc_at(dN, c * kRingChunk + (s & 3) * 32));
                if ((BSLOTS >> s) & 1) store_one(i >= 2, p0, p1, po, 12 - __builtin_popcount(BSLOTS >> s));
            }
        }
        wg_commit();
        mbar_wait(bar_mid, wg);
        wg_fence();
#pragma unroll
        for (int s = 0; s < 12; s++)
            if (s == 0) wgmma_n32<true>(sE, fa[4 * s], fa[4 * s + 1], fa[4 * s + 2], fa[4 * s + 3], desc_at(dE, kOffMid + (s >> 2) * kRingChunk + (s & 3) * 32));
            else wgmma_n32<false>(sE, fa[4 * s], fa[4 * s + 1], fa[4 * s + 2], fa[4 * s + 3], desc_at(dE, kOffMid + (s >> 2) * kRingChunk + (s & 3) * 32));
        wg_commit();
        turn_pass(wg);
        TRF(13 + 16 * k);
        wg_wait<1>();
        pin(sB);
        gather_outer(sB, tabu.w, tabv.y, v0, v1);
        wg_wait<0>();
        pin(sE);
        TRF(14 + 16 * k);
        gather_mid(sE, tabu.w, tabv.z, v0, v1);
        const float m0 = quad_max(tree_max(v0)), m1 = quad_max(tree_max(v1));

        uint32_t y[14], pa[12], pb[12];
        exp_route<0, 14>(v0, v1, m0, m1, route, (j & 1) == 0, y);
        float s0 = tree_sum(v0), s1 = tree_sum(v1);
        asm volatile("" : "+f"(s0), "+f"(s1));
        unfold<0, 0, 6>(y, tabv.w, pa);
        turn_wait(wg + (y[0] >> 31));
        TRF(15 + 16 * k + (y[13] >> 31));
        wg_fence();
        wgmma_sp_n192_tb<true, 0>(acc, pa[0], pa[1], pa[2], pa[3], desc_at(dA, kToV), tabu.y);
        wgmma_sp_n192_tb<false, 1>(acc, pa[4], pa[5], pa[6], pa[7], desc_at(dA, kToV + 4096), tabu.y);
        wgmma_sp_n192_tb<false, 0>(acc, pa[8], pa[9], pa[10], pa[11], desc_at(dA, kToV + 8192), tabu.z);
        wg_commit();
        wgmma_sp_n192_tb<false, 1>(acc, j == 0 ? 0u : y[10], j == 0 ? 0u : y[11], y[12], y[13], desc_at(dE, kToV + kOffMid), tabu.z);
        wg_commit();
        unfold<8, 0, 6>(y, tabv.w, pb);
        wg_fence();
        wgmma_sp_n192_tb<false, 0>(acc, pb[0], pb[1], pb[2], pb[3], desc_at(dN, kToV), tabu.y);
        wgmma_sp_n192_tb<false, 1>(acc, pb[4], pb[5], pb[6], pb[7], desc_at(dN, kToV + 4096), tabu.y);
        wgmma_sp_n192_tb<false, 0>(acc, pb[8], pb[9], pb[10], pb[11], desc_at(dN, kToV + 8192), tabu.z);
        wg_commit();
        if (!last) turn_pass(wg);
        TRF(16 + 16 * k);
        wg_wait<2>();
        if (lane == 0) mbar_arrive(bar_use);
        wg_wait<1>();
        if (lane == 0) mbar_arrive(bar_use + 16);
        TRF(17 + 16 * k);
        mbar_wait(bar_ok + 16, 0);
        wg_wait<0>();
        if (lane == 0) mbar_arrive(bar_use + 8);
        pin(acc);
        TR(18 + 16 * k);

        acc_to_frags(acc, po);
        pin(po);
        if (last) {
            const float inv0 = rcp(quad_sum(s0)), inv1 = rcp(quad_sum(s1));
            float t0[32], t1[32], t2[32];
            uint32_t pq[48];
            wg_fence();
            third_gemm<0>(t0, po, dsc, [](int) {});
            third_gemm<1>(t1, po, dsc, [&](int s) { if (s == 3) { keep(wqkv == nullptr, __float_as_uint(inv0), __float_as_uint(inv1), c0, c1); __syncwarp(); } });
            wg_wait<1>();
            third_pack<0>(t0, inv0, inv1, pq);
            store_one<false>(true, out + c0, out + c1, pq, 0);
            __syncwarp();
            third_gemm<2>(t2, po, dsc, [&](int s) { if (s == 3 || s == 7 || s == 9) store_one(true, out + c0, out + c1, pq, (s + 3) >> 2); });
            __syncwarp();
            wg_wait<1>();
            third_pack<1>(t1, inv0, inv1, pq);
#pragma unroll
            for (int n = 4; n < 8; n++) store_one<false>(true, out + c0, out + c1, pq, n);
            __syncwarp();
            wg_wait<0>();
            third_pack<2>(t2, inv0, inv1, pq);
#pragma unroll
            for (int n = 8; n < 12; n++) store_one<false>(true, out + c0, out + c1, pq, n);
            break;
        }
        turn_wait(wg);
        wg_fence();
        proj_gemm(acc, po, dsc, s_wv, [&](int s) {
            if (s + 1 == OSPLIT && i + 2 == w.ntiles) { turn_pass(wg); turn_wait(wg); }
        });
        turn_pass(wg);
        TRF(19 + 16 * k);
        const uint32_t zero = lds_volatile(s_late);
        const float inv0 = rcp(quad_sum(s0 + __uint_as_float(zero))), inv1 = rcp(quad_sum(s1 + __uint_as_float(zero)));
        raw_to_frags(nxt, zero, fa);
        pin(fa);
#pragma unroll
        for (int q = 0; q < 48; q += 4) keep(wqkv == nullptr, fa[q], fa[q + 1], fa[q + 2], fa[q + 3]);
        keep(wqkv == nullptr, __float_as_uint(inv0), __float_as_uint(inv1), zero, lane);
        TRF(20 + 16 * k);
        tu += du2; tv += dv2;
        wg_wait<0>();
        pin(acc);
        TR(21 + 16 * k);
#pragma unroll
        for (int q = 0; q < 96; q++) acc[q] *= q & 2 ? inv1 : inv0;
        pack_out(acc, po);
#pragma unroll
        for (int n = 0; n < INL; n++) store_one<false>(i + 2 == w.ntiles, out + c0, out + c1, po, n);
        pin(po);
    }
    if (wg == 0) {
#pragma unroll
        for (int n = INL; n < 12; n++) {
            __nanosleep(NAP);
            store_one<false>(true, out + c0, out + c1, po, n);
        }
    }
    TRE(7);
    TRG(1);
    TRDUMP();
}

typedef CUresult (*EncodeTiledFn)(CUtensorMap*, CUtensorMapDataType, cuuint32_t, void*, const cuuint64_t*, const cuuint64_t*,
                                  const cuuint32_t*, const cuuint32_t*, CUtensorMapInterleave, CUtensorMapSwizzle,
                                  CUtensorMapL2promotion, CUtensorMapFloatOOBfill);

bool make_maps(EncodeTiledFn fn, Maps* maps, void* x, void* wqkv, void* wo) {
    const cuuint64_t pix2 = 2 * kPixBytes, row = (cuuint64_t)kHW * kPixBytes;
    const cuuint32_t estr[5] = {1, 1, 1, 1, 1};
    bool ok = true;
    for (int tr = 0; tr < 2; tr++)
        for (int b = 0; b < 2; b++) {
            const cuuint64_t su = tr ? 2 * row : pix2, sv = tr ? pix2 : 2 * row;
            const cuuint64_t dims[5] = {2 * kC, 2, 105, 2, 112};
            const cuuint64_t strides[4] = {7 * su, su, row, sv};
            const cuuint32_t box[5] = {64, 2, 7, 1, b ? 2u : 6u};
            ok = ok && fn(&maps->m[2 * tr + b], CU_TENSOR_MAP_DATA_TYPE_BFLOAT16, 5, x, dims, strides, box, estr,
                          CU_TENSOR_MAP_INTERLEAVE_NONE, CU_TENSOR_MAP_SWIZZLE_128B, CU_TENSOR_MAP_L2_PROMOTION_L2_128B,
                          CU_TENSOR_MAP_FLOAT_OOB_FILL_NONE) == CUDA_SUCCESS;
        }
    for (int b = 0; b < 2; b++) {
        const cuuint64_t dims[3] = {b ? 64u : 48u, kC, b ? 9u : 4u}, strides[2] = {(b ? 3u : 1u) * kPixBytes, b ? 128u : 96u};
        const cuuint32_t box[3] = {b ? 64u : 48u, b ? 16u : 192u, b ? 3u : 1u};
        ok = ok && fn(b ? &maps->wv : &maps->wo, CU_TENSOR_MAP_DATA_TYPE_BFLOAT16, 3, b ? wqkv : wo, dims, strides, box, estr,
                      CU_TENSOR_MAP_INTERLEAVE_NONE, b ? CU_TENSOR_MAP_SWIZZLE_128B : CU_TENSOR_MAP_SWIZZLE_NONE, CU_TENSOR_MAP_L2_PROMOTION_L2_128B,
                      CU_TENSOR_MAP_FLOAT_OOB_FILL_NONE) == CUDA_SUCCESS;
    }
    return ok;
}

}

extern "C" void kernel_launch(void* const* d_in, const int* in_sizes, int n_in, void* d_out, int out_size) {
    static EncodeTiledFn encode = nullptr;
    static Scratch* scratch = nullptr;
    static Tables* tables = nullptr;
    if (!encode) {
        int dev = 0, reserved = 0;
        cudaFuncAttributes attr;
        cudaGetDevice(&dev);
        cudaDeviceGetAttribute(&reserved, cudaDevAttrReservedSharedMemoryPerBlock, dev);
        cudaFuncGetAttributes(&attr, nat_fused_kernel);
        if (reserved != (int)kSmemBase || attr.sharedSizeBytes != 0) return;
        cudaGetSymbolAddress((void**)&scratch, g_scratch);
        cudaGetSymbolAddress((void**)&tables, g_tables);
        void* fn = nullptr;
        cudaDriverEntryPointQueryResult st;
        cudaGetDriverEntryPoint("cuTensorMapEncodeTiled", &fn, cudaEnableDefault, &st);
        encode = (EncodeTiledFn)fn;
        cudaFuncSetAttribute(nat_fused_kernel, cudaFuncAttributeMaxDynamicSharedMemorySize, kSmemBytes);
    }
    Maps maps;
    maps.tables = tables;
    if (!encode || !make_maps(encode, &maps, d_in[0], d_in[1], d_in[2])) return;
    nat_fused_kernel<<<kGrid, kThreads, kSmemBytes>>>((const uint8_t*)d_in[0], (const uint8_t*)d_in[1], (uint8_t*)d_out, scratch, (const uint8_t*)d_in[2],
                                                      kDescRing, maps);
}
```

```cpp
#include <cuda_runtime.h>
#include <cuda_bf16.h>
#include <cuda.h>
#include <stdint.h>
#include <type_traits>
#include <stdlib.h>
#include <stdio.h>
#include <stddef.h>

#define ASLOTS 0x1800
#define BSLOTS 0x2
#define QSLOTS 0xfae
#define OSPLIT 2
#define INL 2
#define NAP 50

namespace {

constexpr int kC          = 192;
constexpr int kHW         = 224;
constexpr int kPixBytes   = kC * 2;
constexpr int kSlotBytes  = 84 * 128;
constexpr int kMidBytes   = 28 * 128;
constexpr int kOffMid     = 88 * 128;
constexpr int kSlotStride = 120 * 128;
constexpr int kRingChunk  = 208 * 128;
constexpr int kWChunk     = 192 * 128;
constexpr int kWBytes     = 3 * kWChunk;
constexpr uint32_t kSmemBase = 1024;
constexpr uint32_t s_ring = kSmemBase, s_m = s_ring + 3 * kRingChunk, s_wv = s_m + kWBytes, s_bar = s_wv + kWBytes;
constexpr uint32_t bar_b = s_bar, bar_mid = s_bar + 24, bar_a = s_bar + 32, bar_img = s_bar + 40, bar_redo = s_bar + 88,
                   bar_wop = s_bar + 112, bar_ok = s_bar + 120, bar_use = s_bar + 160, bar_free = s_bar + 184;
constexpr uint32_t s_par = s_bar + 208, s_late = s_bar + 216, s_again = s_bar + 220, s_tab = s_bar + 256, s_trace = s_tab + 2048;
constexpr int kSmemBytes  = s_trace + 2048 - kSmemBase;
constexpr int kThreads    = 384;
constexpr int kGrid       = 132;
constexpr int kTimeM = 2500, kTimeW = 5100;
constexpr float kScaleLog2e = 0.07216878364870322f * 1.4426950408889634f;

struct Maps {
    CUtensorMap m[4];
    CUtensorMap wo, wv;
    const struct Tables* tables;
};
#define TN(i, dflt) (dflt)
#define START_TIME (wg ? 900 + 450 * order : 250 + 560 * order)

struct Scratch {
    uint8_t img[2][2][kWBytes];
    uint32_t launches[kGrid][32];
};
__device__ __align__(1024) Scratch g_scratch;

struct Table {
    uint32_t route[32][4];
    uint32_t u[8][4][4];
    uint32_t v[16][4][4];
};
struct Tables { Table t[2]; };
constexpr Tables make_tables() {
    Tables r = {};
    for (int rev = 0; rev < 2; rev++)
        for (int j = 0; j < 4; j++) {
            Table& t = r.t[rev];
            for (int q = 0; q < 8; q++) {
                uint32_t* e = t.route[4 * q + j];
                e[0] = 4 * q + 2 * (j & 1) + (j >> 1); e[1] = e[0] ^ 1;
                e[2] = j < 2 ? 0x5410u : 0x1054u; e[3] = e[2] + 0x2222u;
                e = t.u[q][j];
                for (int n = 0; n < 7; n++) e[0] |= ((n + j) % 7 < q ? 1u : 0u) << n;
                e[3] = e[0];
                for (int k = 0; k < 2; k++) {
                    const int step = 2 * k + (j >> 1), p0 = (step < 3 ? 16 * step : 40) + 8 * (j & 1);
                    uint32_t m = 0x8888u;
                    for (int n = 0; n < 8; n++) m |= ((p0 + n) % 7 < q ? 1u : 0u) << (2 * n);
                    e[1 + k] = m * 0x10001u;
                }
            }
            for (int sum = 0; sum < 15; sum++) {
                uint32_t* e = t.v[sum][j];
                for (int row = 0; row < 2; row++)
                    for (int b = 0; b < 14; b++) {
                        const int off = (sum + row) / 2, p = 4 * b + j;
                        const uint32_t bit = 1u << (2 * b + row);
                        if (p < 42 && p >= 7 * off) e[rev] |= bit;
                        if (p < 7 * off - 7) e[1 - rev] |= bit;
                        if (p >= 42 && p >= 7 * off && p < 7 * off + 49) e[2] |= bit;
                    }
                for (int n = 0; n < 6; n++)
                    if (8 * n + 2 * j < 42) e[3] |= 1u << (n + ((8 * n + 2 * j >= 7 * (sum / 2 & ~1)) != rev ? 0 : 8));
            }
        }
    return r;
}
__device__ __align__(128) const Tables g_tables = make_tables();

#define WO4(i) "=f"(d[i]), "=f"(d[i + 1]), "=f"(d[i + 2]), "=f"(d[i + 3])
#define RW4(i) "+f"(d[i]), "+f"(d[i + 1]), "+f"(d[i + 2]), "+f"(d[i + 3])

template <bool FIRST>
__device__ __forceinline__ void wgmma_n192(float (&d)[96], uint32_t a0, uint32_t a1, uint32_t a2, uint32_t a3, uint64_t descb) {
    if constexpr (FIRST) {
        asm volatile(
            "wgmma.mma_async.sync.aligned.m64n192k16.f32.bf16.bf16 "
            "{%0, %1, %2, %3, %4, %5, %6, %7, %8, %9, %10, %11, %12, %13, %14, %15, %16, %17, %18, %19, %20, %21, %22, %23, "
            "%24, %25, %26, %27, %28, %29, %30, %31, %32, %33, %34, %35, %36, %37, %38, %39, %40, %41, %42, %43, %44, %45, %46, %47, "
            "%48, %49, %50, %51, %52, %53, %54, %55, %56, %57, %58, %59, %60, %61, %62, %63, %64, %65, %66, %67, %68, %69, %70, %71, "
            "%72, %73, %74, %75, %76, %77, %78, %79, %80, %81, %82, %83, %84, %85, %86, %87, %88, %89, %90, %91, %92, %93, %94, %95}, "
            "{%96, %97, %98, %99}, %100, 0, 1, 1, 0;"
            : WO4(0), WO4(4), WO4(8), WO4(12), WO4(16), WO4(20), WO4(24), WO4(28), WO4(32), WO4(36), WO4(40), WO4(44),
              WO4(48), WO4(52), WO4(56), WO4(60), WO4(64), WO4(68), WO4(72), WO4(76), WO4(80), WO4(84), WO4(88), WO4(92)
            : "r"(a0), "r"(a1), "r"(a2), "r"(a3), "l"(descb));
    } else {
        asm volatile(
            "wgmma.mma_async.sync.aligned.m64n192k16.f32.bf16.bf16 "
            "{%0, %1, %2, %3, %4, %5, %6, %7, %8, %9, %10, %11, %12, %13, %14, %15, %16, %17, %18, %19, %20, %21, %22, %23, "
            "%24, %25, %26, %27, %28, %29, %30, %31, %32, %33, %34, %35, %36, %37, %38, %39, %40, %41, %42, %43, %44, %45, %46, %47, "
            "%48, %49, %50, %51, %52, %53, %54, %55, %56, %57, %58, %59, %60, %61, %62, %63, %64, %65, %66, %67, %68, %69, %70, %71, "
            "%72, %73, %74, %75, %76, %77, %78, %79, %80, %81, %82, %83, %84, %85, %86, %87, %88, %89, %90, %91, %92, %93, %94, %95}, "
            "{%96, %97, %98, %99}, %100, 1, 1, 1, 0;"
            : RW4(0), RW4(4), RW4(8), RW4(12), RW4(16), RW4(20), RW4(24), RW4(28), RW4(32), RW4(36), RW4(40), RW4(44),
              RW4(48), RW4(52), RW4(56), RW4(60), RW4(64), RW4(68), RW4(72), RW4(76), RW4(80), RW4(84), RW4(88), RW4(92)
            : "r"(a0), "r"(a1), "r"(a2), "r"(a3), "l"(descb));
    }
}

template <bool FIRST>
__device__ __forceinline__ void wgmma_n64(float (&d)[32], uint32_t a0, uint32_t a1, uint32_t a2, uint32_t a3, uint64_t descb) {
    if constexpr (FIRST) {
        asm volatile(
            "wgmma.mma_async.sync.aligned.m64n64k16.f32.bf16.bf16 "
            "{%0, %1, %2, %3, %4, %5, %6, %7, %8, %9, %10, %11, %12, %13, %14, %15, %16, %17, %18, %19, %20, %21, %22, %23, "
            "%24, %25, %26, %27, %28, %29, %30, %31}, "
            "{%32, %33, %34, %35}, %36, 0, 1, 1, 0;"
            : WO4(0), WO4(4), WO4(8), WO4(12), WO4(16), WO4(20), WO4(24), WO4(28)
            : "r"(a0), "r"(a1), "r"(a2), "r"(a3), "l"(descb));
    } else {
        asm volatile(
            "wgmma.mma_async.sync.aligned.m64n64k16.f32.bf16.bf16 "
            "{%0, %1, %2, %3, %4, %5, %6, %7, %8, %9, %10, %11, %12, %13, %14, %15, %16, %17, %18, %19, %20, %21, %22, %23, "
            "%24, %25, %26, %27, %28, %29, %30, %31}, "
            "{%32, %33, %34, %35}, %36, 1, 1, 1, 0;"
            : RW4(0), RW4(4), RW4(8), RW4(12), RW4(16), RW4(20), RW4(24), RW4(28)
            : "r"(a0), "r"(a1), "r"(a2), "r"(a3), "l"(descb));
    }
}

template <bool FIRST>
__device__ __forceinline__ void wgmma_n88(float (&d)[44], uint32_t a0, uint32_t a1, uint32_t a2, uint32_t a3, uint64_t descb) {
    if constexpr (FIRST) {
        asm volatile(
            "wgmma.mma_async.sync.aligned.m64n88k16.f32.bf16.bf16 "
            "{%0, %1, %2, %3, %4, %5, %6, %7, %8, %9, %10, %11, %12, %13, %14, %15, %16, %17, %18, %19, %20, %21, %22, %23, "
            "%24, %25, %26, %27, %28, %29, %30, %31, %32, %33, %34, %35, %36, %37, %38, %39, %40, %41, %42, %43}, "
            "{%44, %45, %46, %47}, %48, 0, 1, 1, 0;"
            : WO4(0), WO4(4), WO4(8), WO4(12), WO4(16), WO4(20), WO4(24), WO4(28), WO4(32), WO4(36), WO4(40)
            : "r"(a0), "r"(a1), "r"(a2), "r"(a3), "l"(descb));
    } else {
        asm volatile(
            "wgmma.mma_async.sync.aligned.m64n88k16.f32.bf16.bf16 "
            "{%0, %1, %2, %3, %4, %5, %6, %7, %8, %9, %10, %11, %12, %13, %14, %15, %16, %17, %18, %19, %20, %21, %22, %23, "
            "%24, %25, %26, %27, %28, %29, %30, %31, %32, %33, %34, %35, %36, %37, %38, %39, %40, %41, %42, %43}, "
            "{%44, %45, %46, %47}, %48, 1, 1, 1, 0;"
            : RW4(0), RW4(4), RW4(8), RW4(12), RW4(16), RW4(20), RW4(24), RW4(28), RW4(32), RW4(36), RW4(40)
            : "r"(a0), "r"(a1), "r"(a2), "r"(a3), "l"(descb));
    }
}

template <bool FIRST>
__device__ __forceinline__ void wgmma_n32(float (&d)[16], uint32_t a0, uint32_t a1, uint32_t a2, uint32_t a3, uint64_t descb) {
    if constexpr (FIRST) {
        asm volatile(
            "wgmma.mma_async.sync.aligned.m64n32k16.f32.bf16.bf16 "
            "{%0, %1, %2, %3, %4, %5, %6, %7, %8, %9, %10, %11, %12, %13, %14, %15}, "
            "{%16, %17, %18, %19}, %20, 0, 1, 1, 0;"
            : WO4(0), WO4(4), WO4(8), WO4(12)
            : "r"(a0), "r"(a1), "r"(a2), "r"(a3), "l"(descb));
    } else {
        asm volatile(
            "wgmma.mma_async.sync.aligned.m64n32k16.f32.bf16.bf16 "
            "{%0, %1, %2, %3, %4, %5, %6, %7, %8, %9, %10, %11, %12, %13, %14, %15}, "
            "{%16, %17, %18, %19}, %20, 1, 1, 1, 0;"
            : RW4(0), RW4(4), RW4(8), RW4(12)
            : "r"(a0), "r"(a1), "r"(a2), "r"(a3), "l"(descb));
    }
}

template <bool FIRST, int SEL>
__device__ __forceinline__ void wgmma_sp_n192_tb(float (&d)[96], uint32_t a0, uint32_t a1, uint32_t a2, uint32_t a3, uint64_t descb, uint32_t meta) {
    if constexpr (FIRST) {
        asm volatile(
            "wgmma.mma_async.sp.sync.aligned.m64n192k32.f32.bf16.bf16 "
            "{%0, %1, %2, %3, %4, %5, %6, %7, %8, %9, %10, %11, %12, %13, %14, %15, %16, %17, %18, %19, %20, %21, %22, %23, "
            "%24, %25, %26, %27, %28, %29, %30, %31, %32, %33, %34, %35, %36, %37, %38, %39, %40, %41, %42, %43, %44, %45, %46, %47, "
            "%48, %49, %50, %51, %52, %53, %54, %55, %56, %57, %58, %59, %60, %61, %62, %63, %64, %65, %66, %67, %68, %69, %70, %71, "
            "%72, %73, %74, %75, %76, %77, %78, %79, %80, %81, %82, %83, %84, %85, %86, %87, %88, %89, %90, %91, %92, %93, %94, %95}, "
            "{%96, %97, %98, %99}, %100, %101, %102, 0, 1, 1, 1;"
            : WO4(0), WO4(4), WO4(8), WO4(12), WO4(16), WO4(20), WO4(24), WO4(28), WO4(32), WO4(36), WO4(40), WO4(44),
              WO4(48), WO4(52), WO4(56), WO4(60), WO4(64), WO4(68), WO4(72), WO4(76), WO4(80), WO4(84), WO4(88), WO4(92)
            : "r"(a0), "r"(a1), "r"(a2), "r"(a3), "l"(descb), "r"(meta), "n"(SEL));
    } else {
        asm volatile(
            "wgmma.mma_async.sp.sync.aligned.m64n192k32.f32.bf16.bf16 "
            "{%0, %1, %2, %3, %4, %5, %6, %7, %8, %9, %10, %11, %12, %13, %14, %15, %16, %17, %18, %19, %20, %21, %22, %23, "
            "%24, %25, %26, %27, %28, %29, %30, %31, %32, %33, %34, %35, %36, %37, %38, %39, %40, %41, %42, %43, %44, %45, %46, %47, "
            "%48, %49, %50, %51, %52, %53, %54, %55, %56, %57, %58, %59, %60, %61, %62, %63, %64, %65, %66, %67, %68, %69, %70, %71, "
            "%72, %73, %74, %75, %76, %77, %78, %79, %80, %81, %82, %83, %84, %85, %86, %87, %88, %89, %90, %91, %92, %93, %94, %95}, "
            "{%96, %97, %98, %99}, %100, %101, %102, 1, 1, 1, 1;"
            : RW4(0), RW4(4), RW4(8), RW4(12), RW4(16), RW4(20), RW4(24), RW4(28), RW4(32), RW4(36), RW4(40), RW4(44),
              RW4(48), RW4(52), RW4(56), RW4(60), RW4(64), RW4(68), RW4(72), RW4(76), RW4(80), RW4(84), RW4(88), RW4(92)
            : "r"(a0), "r"(a1), "r"(a2), "r"(a3), "l"(descb), "r"(meta), "n"(SEL));
    }
}

#define TR(slot)
#define TRX(slot)
#define TRE(slot)
#define TRT(slot)
#define TRF(slot)
#define TRW(slot)
#define TRG(slot)
#define TRDUMP()

__device__ __forceinline__ void wg_fence() { asm volatile("wgmma.fence.sync.aligned;" ::: "memory"); }
__device__ __forceinline__ void wg_commit() { asm volatile("wgmma.commit_group.sync.aligned;" ::: "memory"); }
template <int N>
__device__ __forceinline__ void wg_wait() { asm volatile("wgmma.wait_group.sync.aligned %0;" ::"n"(N) : "memory"); }

template <int N>
__device__ __forceinline__ void pin(float (&d)[N]) {
#pragma unroll
    for (int i = 0; i < N; i++) asm volatile("" : "+f"(d[i])::"memory");
}
template <int N>
__device__ __forceinline__ void pin(uint32_t (&d)[N]) {
#pragma unroll
    for (int i = 0; i < N; i++) asm volatile("" : "+r"(d[i])::"memory");
}

constexpr uint64_t kDescRing = ((uint64_t)((1u << 30) | (1024u >> 4)) << 32) | (1u << 16) | (s_ring >> 4);
constexpr uint32_t kToV = ((kRingChunk >> 4) - 1) << 20;
__device__ __forceinline__ uint64_t desc_at(uint64_t base, uint32_t byte_off) {
    uint64_t d;
    asm volatile("add.s64 %0, %1, %2;" : "=l"(d) : "l"(base), "l"((uint64_t)(byte_off >> 4)));
    return d;
}

__device__ __forceinline__ void mbar_init(uint32_t bar, uint32_t count) {
    asm volatile("mbarrier.init.shared::cta.b64 [%0], %1;" ::"r"(bar), "r"(count) : "memory");
}
__device__ __forceinline__ void mbar_expect_tx(uint32_t bar, uint32_t bytes) {
    asm volatile("mbarrier.arrive.expect_tx.shared::cta.b64 _, [%0], %1;" ::"r"(bar), "r"(bytes) : "memory");
}
__device__ __forceinline__ void expect_tx_only(uint32_t bar, uint32_t bytes) {
    asm volatile("mbarrier.expect_tx.relaxed.cta.shared::cta.b64 [%0], %1;" ::"r"(bar), "r"(bytes) : "memory");
}
__device__ __forceinline__ void mbar_arrive(uint32_t bar) {
    asm volatile("mbarrier.arrive.shared::cta.b64 _, [%0];" ::"r"(bar) : "memory");
}
__device__ __forceinline__ void mbar_wait(uint32_t bar, uint32_t parity) {
    asm volatile(
        "{\n.reg .pred p;\n"
        "W: mbarrier.try_wait.parity.shared::cta.b64 p, [%0], %1;\n"
        "@!p bra W;\n}\n"
        ::"r"(bar), "r"(parity) : "memory");
}
__device__ __forceinline__ uint32_t clock_now() {
    uint32_t c;
    asm volatile("mov.u32 %0, %%clock;" : "=r"(c)::"memory");
    return c;
}
__device__ __forceinline__ void wait_until(uint32_t t0, int t) {
    if (t == 0) return;
    while ((int)(clock_now() - t0) < t) {}
}
__device__ __forceinline__ bool elect() {
    uint32_t ok;
    asm volatile("{\n.reg .pred p;\nelect.sync _|p, 0xffffffff;\nselp.u32 %0, 1, 0, p;\n}\n" : "=r"(ok));
    return ok != 0;
}
__device__ __forceinline__ void turn_wait(int wg) { asm volatile("bar.sync %0, 256;" ::"r"(1 + wg) : "memory"); }
__device__ __forceinline__ void turn_pass(int wg) { asm volatile("bar.arrive %0, 256;" ::"r"(2 - wg) : "memory"); }

__device__ __forceinline__ void tma_box(uint32_t dst, const CUtensorMap* map, uint32_t bar, int c0, int c2, int c3, int c4) {
    asm volatile(
        "cp.async.bulk.tensor.5d.shared::cluster.global.mbarrier::complete_tx::bytes [%0], [%1, {%3, %4, %5, %6, %7}], [%2];"
        ::"r"(dst), "l"(map), "r"(bar), "r"(c0), "r"(0), "r"(c2), "r"(c3), "r"(c4)
        : "memory");
}
__device__ __forceinline__ void tma_3d(uint32_t dst, const CUtensorMap* map, uint32_t bar, int c1, int c2) {
    asm volatile("cp.async.bulk.tensor.3d.shared::cluster.global.mbarrier::complete_tx::bytes [%0], [%1, {%3, %4, %5}], [%2];"
                 ::"r"(dst), "l"(map), "r"(bar), "r"(0), "r"(c1), "r"(c2)
                 : "memory");
}
__device__ __forceinline__ void prefetch_map(const CUtensorMap* map) {
    asm volatile("prefetch.tensormap [%0];" ::"l"(map) : "memory");
}
__device__ __forceinline__ uint4 ldg(const void* p) {
    uint4 v;
    asm volatile("ld.global.v4.u32 {%0, %1, %2, %3}, [%4];" : "=r"(v.x), "=r"(v.y), "=r"(v.z), "=r"(v.w) : "l"(p) : "memory");
    return v;
}
__device__ __forceinline__ uint32_t pack_bf16(float lo, float hi) {
    uint32_t r;
    asm("cvt.rn.bf16x2.f32 %0, %1, %2;" : "=r"(r) : "f"(hi), "f"(lo));
    return r;
}
__device__ __forceinline__ float ex2(float x) {
    float y;
    asm("ex2.approx.ftz.f32 %0, %1;" : "=f"(y) : "f"(x));
    return y;
}
__device__ __forceinline__ float rcp(float x) {
    float y;
    asm("rcp.approx.ftz.f32 %0, %1;" : "=f"(y) : "f"(x));
    return y;
}
__device__ __forceinline__ void mma16816(float (&d)[4], uint32_t a0, uint32_t a1, uint32_t a2, uint32_t a3, uint32_t b0, uint32_t b1) {
    asm volatile("mma.sync.aligned.m16n8k16.row.col.f32.bf16.bf16.f32 {%0, %1, %2, %3}, {%4, %5, %6, %7}, {%8, %9}, {%0, %1, %2, %3};"
                 : "+f"(d[0]), "+f"(d[1]), "+f"(d[2]), "+f"(d[3])
                 : "r"(a0), "r"(a1), "r"(a2), "r"(a3), "r"(b0), "r"(b1));
}
__device__ __forceinline__ uint4 lds128(uint32_t addr) {
    uint4 v;
    asm volatile("ld.volatile.shared.v4.u32 {%0, %1, %2, %3}, [%4];" : "=r"(v.x), "=r"(v.y), "=r"(v.z), "=r"(v.w) : "r"(addr) : "memory");
    return v;
}
__device__ __forceinline__ uint32_t lds_volatile(uint32_t addr) {
    uint32_t v;
    asm volatile("ld.volatile.shared.u32 %0, [%1];" : "=r"(v) : "r"(addr) : "memory");
    return v;
}

__device__ __forceinline__ int window_start(int n) { return min(max(n, 0), 105); }
__device__ __forceinline__ int origin_u(int u) { return min(max(u, 0), 98); }

struct Work {
    int u, v;
    int step;
    uint32_t su, sv;
    uint32_t base;
    bool corner;
    int ntiles;
    __device__ __forceinline__ void pixel_offsets(int qu, int qv, int j, uint32_t& o0, uint32_t& o1) const {
        const uint32_t b = (qu + window_start(qu)) * su + j * 16 + base;
        o0 = b + (qv + window_start(qv)) * sv;
        o1 = b + (qv + 1 + window_start(qv + 1)) * sv;
    }
};

__device__ __forceinline__ Work decode_work(int c) {
    Work w;
    const bool transposed = (c >> 4) == 7;
    const int px = 6 * (c & 1), py = 3 * (c & 2);
    w.corner = c >= 128;
    w.step = 8 - 4 * (c & 4);
    w.u = (c < 112 ? c & ~7 : 96 + (c & 8)) + (transposed ? py : px) - 6;
    w.v = (w.corner ? 96 : 48 - 2 * (c & 4)) + (transposed ? px : py) - 6;
    w.su = transposed ? kHW * kPixBytes : kPixBytes;
    w.sv = transposed ? kPixBytes : kHW * kPixBytes;
    w.base = px * (kPixBytes / 6) + py * (kHW * kPixBytes / 6) + 6 * (kHW + 1) * kPixBytes;
    w.ntiles = w.corner ? 4 : 6;
    return w;
}

struct RawX { uint4 a[6], b[6]; };
__device__ __forceinline__ void load_raw(RawX& r, const uint8_t* base, uint32_t o0, uint32_t o1) {
    __syncwarp();
#pragma unroll
    for (int c = 0; c < 6; c++) { r.a[c] = ldg(base + o0 + c * 64); r.b[c] = ldg(base + o1 + c * 64); }
    __syncwarp();
}
__device__ __forceinline__ void raw_to_frags(const RawX& r, uint32_t zero, uint32_t (&f)[48]) {
#pragma unroll
    for (int c = 0; c < 6; c++) {
        asm volatile("{\n.reg .b32 t, u;\nadd.u32 t, %4, %8;\nadd.u32 u, %5, %8;\nxor.b32 %0, %6, %8;\nxor.b32 %1, %7, %8;\n"
                     "xor.b32 %2, t, %8;\nxor.b32 %3, u, %8;\n}\n"
                     : "=&r"(f[8 * c + 1]), "=&r"(f[8 * c + 3]), "=&r"(f[8 * c + 4]), "=&r"(f[8 * c + 6])
                     : "r"(r.a[c].y), "r"(r.a[c].w), "r"(r.b[c].x), "r"(r.b[c].z), "r"(zero));
        f[8 * c + 0] = r.a[c].x; f[8 * c + 2] = r.a[c].z; f[8 * c + 5] = r.b[c].y; f[8 * c + 7] = r.b[c].w;
    }
}
__device__ __forceinline__ void acc_to_frags(const float (&d)[96], uint32_t (&f)[48]) {
#pragma unroll
    for (int i = 0; i < 48; i++) f[i] = pack_bf16(d[2 * i], d[2 * i + 1]);
}

template <class F>
__device__ __forceinline__ void proj_gemm(float (&d)[96], const uint32_t (&a)[48], uint64_t dsc, uint32_t img, F after) {
#pragma unroll
    for (int s = 0; s < 12; s++) {
        if (s == 0) wgmma_n192<true>(d, a[4 * s], a[4 * s + 1], a[4 * s + 2], a[4 * s + 3], desc_at(dsc, img - s_ring + (s >> 2) * kWChunk + (s & 3) * 32));
        else wgmma_n192<false>(d, a[4 * s], a[4 * s + 1], a[4 * s + 2], a[4 * s + 3], desc_at(dsc, img - s_ring + (s >> 2) * kWChunk + (s & 3) * 32));
        if (s == 11) wg_commit();
        after(s);
    }
}
__device__ __forceinline__ void pack_out(const float (&acc)[96], uint32_t (&po)[48]) {
#pragma unroll
    for (int g = 0; g < 6; g++)
#pragma unroll
        for (int q = 0; q < 4; q++) {
            po[8 * g + q] = pack_bf16(acc[16 * g + 4 * q], acc[16 * g + 4 * q + 1]);
            po[8 * g + 4 + q] = pack_bf16(acc[16 * g + 4 * q + 2], acc[16 * g + 4 * q + 3]);
        }
}
template <bool PINNED = true>
__device__ __forceinline__ void store_one(bool on, uint8_t* p0, uint8_t* p1, const uint32_t (&po)[48], int n) {
    if (PINNED) __syncwarp();
    asm volatile("{\n.reg .pred p;\nsetp.ne.u32 p, %5, 0;\n@p st.global.v4.u32 [%0], {%1, %2, %3, %4};\n}\n"
                 ::"l"(((n & 1) ? p1 : p0) + (n >> 1) * 64), "r"(po[4 * n]), "r"(po[4 * n + 1]), "r"(po[4 * n + 2]), "r"(po[4 * n + 3]), "r"((uint32_t)on) : "memory");
}

template <int N>
__device__ __forceinline__ float tree_max(const float (&v)[N]) {
    float t[N];
#pragma unroll
    for (int i = 0; i < N; i++) t[i] = v[i];
#pragma unroll
    for (int w = 1; w < N; w *= 2)
#pragma unroll
        for (int i = 0; i + w < N; i += 2 * w) t[i] = fmaxf(t[i], t[i + w]);
    return t[0];
}
template <int N>
__device__ __forceinline__ float tree_sum(const float (&v)[N]) {
    float t[N];
#pragma unroll
    for (int i = 0; i < N; i++) t[i] = v[i];
#pragma unroll
    for (int w = 1; w < N; w *= 2)
#pragma unroll
        for (int i = 0; i + w < N; i += 2 * w) t[i] += t[i + w];
    return t[0];
}

template <int T, class F>
__device__ __forceinline__ void third_gemm(float (&d)[32], const uint32_t (&a)[48], uint64_t dsc, F after) {
#pragma unroll
    for (int s = 0; s < 12; s++) {
        if (s == 0) wgmma_n64<true>(d, a[4 * s], a[4 * s + 1], a[4 * s + 2], a[4 * s + 3], desc_at(dsc, s_wv - s_ring + T * 8192 + (s >> 2) * kWChunk + (s & 3) * 32));
        else wgmma_n64<false>(d, a[4 * s], a[4 * s + 1], a[4 * s + 2], a[4 * s + 3], desc_at(dsc, s_wv - s_ring + T * 8192 + (s >> 2) * kWChunk + (s & 3) * 32));
        if (s == 11) wg_commit();
        after(s);
    }
}
template <int T>
__device__ __forceinline__ void third_pack(float (&d)[32], float i0, float i1, uint32_t (&po)[48]) {
    pin(d);
#pragma unroll
    for (int g = 0; g < 2; g++)
#pragma unroll
        for (int q = 0; q < 4; q++) {
            po[16 * T + 8 * g + q] = pack_bf16(d[16 * g + 4 * q] * i0, d[16 * g + 4 * q + 1] * i0);
            po[16 * T + 8 * g + 4 + q] = pack_bf16(d[16 * g + 4 * q + 2] * i1, d[16 * g + 4 * q + 3] * i1);
        }
}

template <int B>
__device__ __forceinline__ void pick(uint32_t h, uint32_t ok, const float* s, float& v0, float& v1) {
    asm("{\n.reg .pred p, q0, q1;\n.reg .b32 t;\nand.b32 t, %6, %7;\nsetp.ne.u32 p, t, 0;\n"
        "and.b32 t, %8, %9;\nsetp.ne.u32 q0, t, 0;\nand.b32 t, %8, %10;\nsetp.ne.u32 q1, t, 0;\n"
        "@q0 selp.f32 %0, %3, %2, p;\n@q1 selp.f32 %1, %5, %4, p;\n}\n"
        : "+f"(v0), "+f"(v1)
        : "f"(s[0]), "f"(s[1]), "f"(s[2]), "f"(s[3]), "r"(h), "n"(1 << ((4 * B) % 7)), "r"(ok), "n"(1 << (2 * B)), "n"(2 << (2 * B)));
}
template <int B, class F>
__device__ __forceinline__ void for_blocks(F f) {
    if constexpr (B > 0) { for_blocks<B - 1>(f); f(std::integral_constant<int, B - 1>{}); }
}
__device__ __forceinline__ void gather_outer(const float (&s)[44], uint32_t h, uint32_t ok, float (&v0)[14], float (&v1)[14]) {
    for_blocks<11>([&](auto B) {
        constexpr int b = B.value < 8 ? (B.value >> 1) + 7 * (B.value & 1) : B.value - 4;
        pick<b>(h, ok, &s[4 * b], v0[b], v1[b]);
    });
}
__device__ __forceinline__ void gather_mid(const float (&sE)[16], uint32_t h, uint32_t ok, float (&v0)[14], float (&v1)[14]) {
    for_blocks<4>([&](auto B) { pick<10 + B.value>(h, ok, &sE[4 * B.value], v0[10 + B.value], v1[10 + B.value]); });
}
__device__ __forceinline__ float quad_max(float m) {
    m = fmaxf(m, __shfl_xor_sync(0xffffffffu, m, 1));
    return fmaxf(m, __shfl_xor_sync(0xffffffffu, m, 2));
}
__device__ __forceinline__ float quad_sum(float s) {
    s += __shfl_xor_sync(0xffffffffu, s, 1);
    return s + __shfl_xor_sync(0xffffffffu, s, 2);
}
template <int B0, int B1>
__device__ __forceinline__ void exp_route(float (&v0)[14], float (&v1)[14], float m0, float m1, const uint4& r, bool even, uint32_t (&y)[14]) {
#pragma unroll
    for (int b = B0; b < B1; b++) { v0[b] = ex2(v0[b] - m0); v1[b] = ex2(v1[b] - m1); }
#pragma unroll
    for (int b = B0; b < B1; b += 2) {
        const uint32_t x0 = pack_bf16(v0[b], v1[b]), x1 = pack_bf16(v0[b + 1], v1[b + 1]);
        const uint32_t u = __shfl_sync(0xffffffffu, even ? x0 : x1, r.x);
        const uint32_t w = __shfl_sync(0xffffffffu, even ? x1 : x0, r.y);
        y[b] = __byte_perm(u, w, r.z); y[b + 1] = __byte_perm(u, w, r.w);
    }
}
template <int BIT0, int N0, int N1>
__device__ __forceinline__ void unfold(const uint32_t (&y)[14], uint32_t fold, uint32_t (&p)[12]) {
    for_blocks<N1 - N0>([&](auto N) {
        constexpr int n = N0 + N.value;
        asm("{\n.reg .pred p;\n.reg .b32 t;\nand.b32 t, %4, %5;\nsetp.ne.u32 p, t, 0;\nselp.b32 %0, %2, 0, p;\nselp.b32 %1, %3, 0, p;\n}\n"
            : "=r"(p[2 * n]), "=r"(p[2 * n + 1]) : "r"(y[2 * n]), "r"(y[2 * n + 1]), "r"(fold), "n"(1 << (BIT0 + n)));
    });
}
__device__ __forceinline__ void keep(bool never, uint32_t a, uint32_t b, uint32_t c, uint32_t d) {
    asm volatile("{\n.reg .pred p;\nsetp.ne.u32 p, %4, 0;\n@p st.volatile.shared.v4.u32 [%5], {%0, %1, %2, %3};\n}\n"
                 ::"r"(a), "r"(b), "r"(c), "r"(d), "r"((uint32_t)never), "r"(s_trace) : "memory");
}

__device__ __forceinline__ uint32_t wimg_offset(uint32_t row, uint32_t s, uint32_t j) {
    return (s >> 2) * kWChunk + row * 128 + (((2 * (s & 3) + (j >> 1)) ^ (row & 7)) << 4) + (j & 1) * 8;
}

__device__ __forceinline__ void ldsm4(uint32_t (&r)[4], uint32_t addr) {
    asm volatile("ldmatrix.sync.aligned.m8n8.x4.shared.b16 {%0, %1, %2, %3}, [%4];" : "=r"(r[0]), "=r"(r[1]), "=r"(r[2]), "=r"(r[3]) : "r"(addr) : "memory");
}
__device__ __forceinline__ void ldsm4_t(uint32_t (&r)[4], uint32_t addr) {
    asm volatile("ldmatrix.sync.aligned.m8n8.x4.trans.shared.b16 {%0, %1, %2, %3}, [%4];" : "=r"(r[0]), "=r"(r[1]), "=r"(r[2]), "=r"(r[3]) : "r"(addr) : "memory");
}
struct MOperands { uint4 A[2][2], B[4][2]; };
__device__ __forceinline__ void m_load(MOperands& m, const uint8_t* wqkv, uint32_t mt, uint32_t s, uint32_t q, uint32_t lane) {
    const uint32_t r8 = lane >> 2, col = q * 128 + (lane & 3) * 16;
    const uint8_t* pa = wqkv + (16 * mt + r8) * 1152 + col;
    const uint8_t* pb = wqkv + (16 * s + 8 * (r8 & 2) + (r8 & 5)) * 1152 + col;
#pragma unroll
    for (int c = 0; c < 2; c++) {
#pragma unroll
        for (int h = 0; h < 2; h++) m.A[h][c] = ldg(pa + 384 + h * 8 * 1152 + c * 64);
#pragma unroll
        for (int n = 0; n < 4; n++) m.B[n][c] = ldg(pb + ((n & 1) * 8 + (n & 2)) * 1152 + c * 64);
    }
}
__device__ __forceinline__ void m_partial(MOperands& m, uint32_t q, uint32_t lane, uint32_t zero) {
    auto& A = m.A;
    auto& B = m.B;
#pragma unroll
    for (int i = 0; i < 4; i++) { uint4& a = A[i >> 1][i & 1]; a.x ^= zero; a.y ^= zero; a.z ^= zero; a.w ^= zero; }
#pragma unroll
    for (int n = 0; n < 4; n++) {
        float d[4] = {0.f, 0.f, 0.f, 0.f};
#pragma unroll
        for (int c = 0; c < 2; c++) {
            mma16816(d, A[0][c].x, A[1][c].x, A[0][c].y, A[1][c].y, B[n][c].x, B[n][c].y);
            mma16816(d, A[0][c].z, A[1][c].z, A[0][c].w, A[1][c].w, B[n][c].z, B[n][c].w);
        }
        asm volatile("st.shared.v4.f32 [%0], {%1, %2, %3, %4};" ::"r"(s_wv + q * 2048 + n * 512 + lane * 16), "f"(d[0]), "f"(d[1]), "f"(d[2]), "f"(d[3]) : "memory");
    }
}
__device__ __forceinline__ void m_reduce(uint32_t e, uint32_t lane, float (&d)[2][4]) {
#pragma unroll
    for (int n = 0; n < 2; n++) {
        float t[3][4];
#pragma unroll
        for (int q = 0; q < 3; q++)
            asm volatile("ld.shared.v4.f32 {%0, %1, %2, %3}, [%4];" : "=f"(t[q][0]), "=f"(t[q][1]), "=f"(t[q][2]), "=f"(t[q][3]) : "r"(s_wv + q * 2048 + e * 1024 + n * 512 + lane * 16) : "memory");
#pragma unroll
        for (int i = 0; i < 4; i++) d[n][i] = (t[0][i] + t[1][i] + t[2][i]) * kScaleLog2e;
    }
}
__device__ __forceinline__ void w_piece(uint32_t q, uint32_t lane, float (&d)[2][4]) {
    const uint32_t rr = lane & 7, mi = lane >> 3, kr = 4 * (rr >> 1) + (mi & 2) + (rr & 1);
    const uint32_t pa = s_wv + q * 32 + (4 * (mi & 2) + rr) * 96 + ((mi & 1) << 4);
    const uint32_t pb = s_wv + 3 * 6144 + kr * 128 + (((mi & 1) ^ (kr & 7)) << 4);
    float e[2][4];
#pragma unroll
    for (int i = 0; i < 8; i++) (&d[0][0])[i] = (&e[0][0])[i] = 0.f;
#pragma unroll
    for (int k = 0; k < 12; k++) {
        uint32_t aq[4], bq[4];
        ldsm4_t(aq, pa + k * 1536);
        ldsm4(bq, (pb ^ ((k & 3) << 5)) + (k >> 2) * 2048);
        mma16816(k & 1 ? e[0] : d[0], aq[0], aq[1], aq[2], aq[3], bq[0], bq[1]);
        mma16816(k & 1 ? e[1] : d[1], aq[0], aq[1], aq[2], aq[3], bq[2], bq[3]);
    }
#pragma unroll
    for (int i = 0; i < 8; i++) (&d[0][0])[i] += (&e[0][0])[i];
}
__device__ __forceinline__ uint32_t piece_offset(uint32_t which, uint32_t s, uint32_t mt, uint32_t lane) {
    const uint32_t r8 = lane >> 2;
    return which * kWBytes + wimg_offset(which ? 32 * (mt >> 1) + 8 * (r8 >> 1) + 4 * (mt & 1) + (r8 & 1) : 16 * mt + r8, s, lane & 3);
}
__device__ __forceinline__ void piece_store(Scratch* g, uint32_t par, uint32_t off0, uint32_t which, const float (&d)[2][4]) {
#pragma unroll
    for (int hf = 0; hf < 2; hf++) {
        const uint32_t off = off0 ^ (hf ? which ? 288 : 1024 : 0);
        const uint32_t a = pack_bf16(d[0][2 * hf], d[0][2 * hf + 1]), b = pack_bf16(d[1][2 * hf], d[1][2 * hf + 1]);
        asm volatile("st.relaxed.gpu.global.v2.u32 [%0], {%1, %2};" ::"l"(g->img[0][0] + (par + off)), "r"(a ? a : 0x8000u), "r"(b) : "memory");
    }
}
__device__ __forceinline__ void piece_clear(Scratch* g, uint32_t par, uint32_t off0, uint32_t which) {
#pragma unroll
    for (int hf = 0; hf < 2; hf++)
        asm volatile("st.relaxed.gpu.global.v2.u32 [%0], {%1, %1};" ::"l"(g->img[0][0] + (par + (off0 ^ (hf ? which ? 288 : 1024 : 0)))), "r"(0) : "memory");
}

__device__ __forceinline__ uint32_t ld_relaxed(const uint32_t* p) {
    uint32_t v;
    asm volatile("ld.relaxed.gpu.global.u32 %0, [%1];" : "=r"(v) : "l"(p) : "memory");
    return v;
}
__device__ __forceinline__ void count_up(uint32_t* p) {
    asm volatile("red.relaxed.gpu.global.add.u32 [%0], %1;" ::"l"(p), "r"(1) : "memory");
}
__device__ __forceinline__ void bulk_g2s(uint32_t dst, const void* src, uint32_t bytes, uint32_t bar) {
    asm volatile("cp.async.bulk.shared::cluster.global.mbarrier::complete_tx::bytes [%0], [%1], %2, [%3];"
                 ::"r"(dst), "l"(src), "r"(bytes), "r"(bar)
                 : "memory");
}

__global__ void __launch_bounds__(kThreads, 1)
nat_fused_kernel(const uint8_t* __restrict__ x, const uint8_t* __restrict__ wqkv, uint8_t* __restrict__ out, Scratch* g,
                 const uint8_t* wo, uint64_t dsc, const __grid_constant__ Maps maps) {
    const int tid = threadIdx.x, lane = tid & 31;
    const int warp = __shfl_sync(0xffffffffu, tid >> 5, 0);
    const int wg = warp >> 2, wq = warp & 3, r8 = lane >> 2, j = lane & 3;
    const int cta = blockIdx.x;
    const Work w = decode_work(cta);
    const uint32_t jq = (cta < 124 ? cta + 8 : cta - 124) / 11u, jr = (cta < 124 ? cta + 8 : cta - 124) - 11 * jq;
    const uint32_t which = jr >= 6, jhi = which ? jr - 6 : jq, jlo = which ? jq : 2 * jr;
    const bool has_job = jr < 10;
    if (wg == 2 && wq < 3) {
#pragma unroll
        for (int r = 0; r < 3; r++)
            asm volatile("st.shared.v4.u32 [%0], {%1, %1, %1, %1};" ::"r"(s_ring + wq * kRingChunk + (r == 0 ? 84 : r == 1 ? 88 : 204) * 128 + lane * 16), "r"(0) : "memory");
        asm volatile("fence.proxy.async.shared::cta;" ::: "memory");
    }
    MOperands mo;
    uint32_t launch = 0;
    if (wg == 1 && wq < 3 && !which) m_load(mo, wqkv, jhi, jlo, wq, lane);
    if (warp == 7) launch = ld_relaxed(g->launches[cta]);
    if (x == nullptr) return;
    const uint32_t t_start = clock_now();
    if (wg == 2) {
        asm volatile("setmaxnreg.dec.sync.aligned.u32 24;");
        if (wq < 3) {
            if (lane < 3 && cta < 128) {
                const uint32_t row = 3 * (cta >> 1) + wq;
                asm volatile("prefetch.global.L2 [%0];" ::"l"((cta & 1 ? wo + row * 384 : wqkv + row * 1152 + 768) + lane * 128));
            }
            asm volatile("bar.sync 7, 192;" ::: "memory");
            const uint32_t par = lds_volatile(s_par);
            uint32_t phase = 0;
#pragma unroll 1
            for (uint32_t c = 0; c < 6; c++) {
                const uint32_t part = c * kWChunk + wq * (kWChunk / 3);
                mbar_wait(bar_img + 8 * c, 0);
                if (c == 0 && lane == 0) mbar_arrive(bar_ok);
                if (wq == 0) TRW(10 + c);
#pragma unroll 1
                while (true) {
                    uint32_t lo = ~0u;
#pragma unroll
                    for (int q = 0; q < 8; q++) lo = min(lo, lds_volatile(s_m + part + lane * 32 + (lane & 12) * 2 + q * 1024));
                    if (__all_sync(0xffffffffu, lo) || phase > 65535) break;
                    if (elect()) {
                        mbar_expect_tx(bar_redo + 8 * wq, kWChunk / 3);
                        bulk_g2s(s_m + part, g->img[0][0] + par + part, kWChunk / 3, bar_redo + 8 * wq);
                    }
                    mbar_wait(bar_redo + 8 * wq, phase++ & 1);
                }
                if (c == 2 && phase) asm volatile("st.shared.u32 [%0], %1;" ::"r"(s_again), "r"(1) : "memory");
                if (c >= 2 && lane == 0) mbar_arrive(bar_ok + 8 * c - 8);
            }
        } else {
            const CUtensorMap* map = &maps.m[w.sv == kPixBytes ? 2 : 0];
            if (elect()) {
#pragma unroll
                for (int i = 0; i < 26; i++) mbar_init(s_bar + 8 * i, i < 15 ? 1 : i < 20 ? 3 : 4);
                asm volatile("fence.mbarrier_init.release.cluster;" ::: "memory");
                prefetch_map(map + 1);
                expect_tx_only(bar_a, sizeof(Table));
                bulk_g2s(s_tab, &maps.tables->t[w.step < 0], sizeof(Table), bar_a);
            }
            if (which && has_job && elect()) {
                mbar_expect_tx(bar_wop, 4 * 6144);
                tma_3d(s_wv, &maps.wo, bar_wop, 0, jhi);
                tma_3d(s_wv + 3 * 6144, &maps.wv, bar_wop, 16 * jlo, 6);
            }
            int u = w.u, v = w.v;
            uint32_t wait_bar = bar_use, wait_par = 1, slot = 0;
#pragma unroll 1
            for (int step = 0; step < 7 - w.corner; step++) {
                const bool first = step == 0 || (w.corner && step == 4);
                const int ou = origin_u(u);
                const bool final = step == 6 - w.corner;
                if (final) { wait_bar = bar_free; wait_par = 0; }
#pragma unroll 1
                for (uint32_t bar = first ? bar_a : bar_b; bar <= (first ? bar_a : bar_mid); bar += 8) {
                    mbar_wait(bar, first ? !step : slot != 0);
                    if (elect()) mbar_expect_tx(bar, first ? 3 * kSlotBytes : bar < bar_mid ? kSlotBytes : 3 * kMidBytes);
                }
                int row = v + 4 + (first ? -w.step : w.step) / 2;
                uint32_t dst = final ? s_m : s_ring + (first ? 0 : slot), bar = first ? bar_a : bar_b, dbar = first ? 0 : 8;
#pragma unroll 1
                for (int r = 0; r < 2 - first; r++) {
                    mbar_wait(wait_bar, wait_par);
                    if (r == 0) TRW(24 + step);
#pragma unroll
                    for (int n = 0; n < 3; n++) {
                        if (n && final) mbar_wait(bar_free + 8 * n, 0);
                        if (elect()) tma_box(dst + n * kRingChunk, map + r, bar + n * dbar, (cta & 1) * kC + 64 * n, ou, (cta >> 1) & 1, row);
                    }
                    row = v + 6; bar = bar_mid; dbar = 0;
                    dst = (final ? s_m : s_ring) + kOffMid + 512;
                    if (wait_bar == bar_use) wait_bar = bar_use + 16;
                }
                TRW(32 + 8 * step + 4);
                if (step == 0) {
                    asm volatile("st.shared.v2.u32 [%0], {%1, %1};" ::"r"(s_late), "r"(0) : "memory");
                    asm volatile("bar.arrive 3, 160;\nbar.arrive 4, 160;\nbar.arrive 8, 128;\nbar.sync 9, 64;" ::: "memory");
                }
                if (step < 2) {
                    if (step) {
                        asm volatile("bar.sync 6, 128;" ::: "memory");
                    }
                    const uint32_t par = __shfl_sync(0xffffffffu, lds_volatile(s_par), 0);
                    wait_until(t_start, step ? TN(5, kTimeW) : TN(6, kTimeM));
                    TRW(5 + 4 * step);
#pragma unroll 1
                    for (int c = 3 * step; c < 3 + 3 * step; c++)
                        if (elect()) {
                            mbar_expect_tx(bar_img + 8 * c, kWChunk);
                            bulk_g2s(s_m + c * kWChunk, g->img[0][0] + (par + c * kWChunk), kWChunk, bar_img + 8 * c);
                        }
                }
                const bool again = w.corner && step == 3;
                wait_bar = step == 0 ? bar_img + 8 * TN(1, 1) : again ? bar_use + 8 : bar_use;
                if (!again) {
                    wait_par = slot ? 0 : step != 0;
                    slot ^= kSlotStride;
                    if (w.corner && step == 2) { u += 8; v -= 8; } else if (step) v += w.step;
                }
            }
        }
        TRDUMP();
        return;
    }
    if (warp == 7) {
        asm volatile("st.shared.u32 [%0], %1;\nbar.arrive 9, 64;" ::"r"(s_par), "r"((launch & 1) * 2 * kWBytes) : "memory");
        g->launches[cta][lane] = launch + 1;
        asm volatile("bar.arrive 5, 128;" ::: "memory");
    }
    if (wg == 1 && wq < 3) {
        if (!which) m_partial(mo, wq, lane, (uint32_t)dsc & 1);
        const uint32_t off = piece_offset(which, which ? jlo : jlo + wq, which ? 3 * jhi + wq : jhi, lane);
        asm volatile("bar.sync %0, %1;" ::"r"(5 + (off >> 31)), "n"(128) : "memory");
        const uint32_t par = lds_volatile(s_par);
        if (which) asm volatile("bar.sync 8, 128;" ::: "memory");
        if (has_job && wq < 2 + which) {
            float d[2][4];
            if (wq == 0) TRX(which ? 1 : 18);
            if (which) {
                mbar_wait(bar_wop, 0);
                if (wq == 0) TRX(2);
                w_piece(wq, lane, d);
            } else {
                m_reduce(wq, lane, d);
            }
            piece_store(g, par, off, which, d);
            __syncwarp();
            piece_clear(g, 2 * kWBytes - par, off, which);
            if (wq == 0) TRX(which ? 3 : 0);
        }
        if (!which) asm volatile("bar.sync 8, 128;" ::: "memory");
        asm volatile("bar.arrive 7, 192;\nbar.arrive 6, 128;" ::: "memory");
    }
    const int order = w.step < 0 ? warp ^ 3 : warp;
    int tu = w.u, tv = w.v + w.step * wg;
    const int du2 = w.corner ? 8 : 0, dv2 = w.corner ? 0 : 2 * w.step;
    uint32_t o0, o1;
    wait_until(t_start, START_TIME);
    asm volatile("setmaxnreg.inc.sync.aligned.u32 240;");
    w.pixel_offsets(tu + r8, tv + 2 * wq, j, o0, o1);
    uint32_t fa[48];
    {
        RawX raw;
        load_raw(raw, x, o0, o1);
        asm volatile("bar.sync %0, 160;" ::"r"(3 + wg) : "memory");
        raw_to_frags(raw, 0, fa);
        pin(fa);
    }
    mbar_wait(bar_ok, 0);
    const uint64_t dA = dsc + wg * (kSlotStride >> 4), dB = dsc + (wg ^ 1) * (kSlotStride >> 4);

    float acc[96];
    uint32_t po[48];
    uint32_t c0 = 0, c1 = 0;
#pragma unroll
    for (int q = 0; q < 48; q++) asm volatile("" : "=r"(po[q]));
#pragma unroll 1
    for (int i = wg; i < w.ntiles; i += 2) {
        const bool first = i == 0, last = i == w.ntiles - 1;

        TRF(8 + 16 * k);
        uint8_t *p0 = out + c0, *p1 = out + c1;
#pragma unroll 1
        for (uint32_t seen = 0;;) {
        wg_fence();
        if (!first) turn_wait(wg);
        proj_gemm(acc, fa, dsc, s_m, [&](int s) {
            if (s == 11 && !first) turn_pass(wg);
            const int n = __builtin_popcount(QSLOTS & ((1 << s) - 1));
            if (((QSLOTS >> s) & 1) && n < 12) store_one(i >= 2, out + c0, out + c1, po, n);
            if (s == 3 || s == 7) { wg_commit(); mbar_wait(bar_img + 2 * s + 2, 0); wg_fence(); }
        });
        __syncwarp();
        TRF(9 + 16 * k);
            if (!first) break;
            mbar_wait(bar_ok + 8, 0);
            if (lds_volatile(s_again) == seen) break;
            wg_wait<0>();
            seen = 1;
        }
        c0 = o0; c1 = o1;
        w.pixel_offsets(tu + du2 + r8, tv + dv2 + 2 * wq, j, o0, o1);
        if (i + 2 >= w.ntiles) o0 = o1 = 0;
        mbar_wait(bar_a, w.corner ? i >> 1 : 0);
        wg_wait<2>();
        if (last && lane == 0) mbar_arrive(bar_free);
        wg_wait<1>();
        if (last && lane == 0) mbar_arrive(bar_free + 8);
#pragma unroll
        for (int s = 12; s < 14; s++)
            if ((QSLOTS >> s) & 1) { store_one(i >= 2, p0, p1, po, __builtin_popcount(QSLOTS & ((1 << s) - 1))); __syncwarp(); }
        wg_wait<0>();
        if (last && lane == 0) mbar_arrive(bar_free + 16);
        const uint64_t dE = last ? dsc + ((s_m - s_ring) >> 4) : dsc, dN = last ? dE : dB;
        pin(acc);
        TR(11 + 16 * k);
        TRT(80 + k);
#pragma unroll
        for (int n = __builtin_popcount(QSLOTS); n < 12 - __builtin_popcount(ASLOTS) - __builtin_popcount(BSLOTS); n++) store_one(i >= 2, p0, p1, po, n);
        acc_to_frags(acc, fa);
        pin(fa);

        float sA[44], sE[16], sB[44];
        RawX nxt;
        if (!first) turn_wait(wg);
        wg_fence();
#pragma unroll
        for (int s = 0; s < 12; s++) {
            if (s == 0) wgmma_n88<true>(sA, fa[4 * s], fa[4 * s + 1], fa[4 * s + 2], fa[4 * s + 3], desc_at(dA, (s >> 2) * kRingChunk + (s & 3) * 32));
            else wgmma_n88<false>(sA, fa[4 * s], fa[4 * s + 1], fa[4 * s + 2], fa[4 * s + 3], desc_at(dA, (s >> 2) * kRingChunk + (s & 3) * 32));
            if (s == 11) { wg_commit(); if (!first) turn_pass(wg); }
            if ((ASLOTS >> s) & 1) store_one(i >= 2, p0, p1, po, 12 - __builtin_popcount(BSLOTS) - __builtin_popcount(ASLOTS >> s));
        }
#pragma unroll
        for (int s = 12; s < 16; s++)
            if ((ASLOTS >> s) & 1) store_one(i >= 2, p0, p1, po, 12 - __builtin_popcount(BSLOTS) - __builtin_popcount(ASLOTS >> s));
        TRF(12 + 16 * k);
        const int vq = tv + 2 * wq;
        const uint4 tabu = lds128(s_tab + offsetof(Table, u) + (window_start(tu + r8) - origin_u(tu)) * 64 + j * 16);
        const uint4 tabv = lds128(s_tab + offsetof(Table, v) + (window_start(vq) + window_start(vq + 1) - 2 * tv) * 64 + j * 16);
        const uint4 route = lds128(s_tab + lane * 16);
        load_raw(nxt, x, o0, o1);
        float v0[14], v1[14];
#pragma unroll
        for (int b = 0; b < 14; b++) {
            v0[b] = __uint_as_float((b > 10 ? route.x >> (b + 2) : 0u) | 0xff800000u);
            v1[b] = __uint_as_float((b > 10 ? route.x >> (b + 5) : 0u) | 0xff800000u);
        }
        wg_wait<0>();
        pin(sA);
        gather_outer(sA, tabu.x, tabv.x, v0, v1);
        pin(v0); pin(v1);
        if (!first) turn_wait(wg);
#pragma unroll
        for (int c = 0; c < 3; c++) {
            mbar_wait(bar_b + 8 * c, wg);
            TRF(64 + 4 * k + c);
            wg_fence();
#pragma unroll
            for (int s = 4 * c; s < 4 * c + 4; s++) {
                if (s == 0) wgmma_n88<true>(sB, fa[4 * s], fa[4 * s + 1], fa[4 * s + 2], fa[4 * s + 3], desc_at(dN, c * kRingChunk + (s & 3) * 32));
                else wgmma_n88<false>(sB, fa[4 * s], fa[4 * s + 1], fa[4 * s + 2], fa[4 * s + 3], desc_at(dN, c * kRingChunk + (s & 3) * 32));
                if ((BSLOTS >> s) & 1) store_one(i >= 2, p0, p1, po, 12 - __builtin_popcount(BSLOTS >> s));
            }
        }
        wg_commit();
        mbar_wait(bar_mid, wg);
        wg_fence();
#pragma unroll
        for (int s = 0; s < 12; s++)
            if (s == 0) wgmma_n32<true>(sE, fa[4 * s], fa[4 * s + 1], fa[4 * s + 2], fa[4 * s + 3], desc_at(dE, kOffMid + (s >> 2) * kRingChunk + (s & 3) * 32));
            else wgmma_n32<false>(sE, fa[4 * s], fa[4 * s + 1], fa[4 * s + 2], fa[4 * s + 3], desc_at(dE, kOffMid + (s >> 2) * kRingChunk + (s & 3) * 32));
        wg_commit();
        turn_pass(wg);
        TRF(13 + 16 * k);
        wg_wait<1>();
        pin(sB);
        gather_outer(sB, tabu.w, tabv.y, v0, v1);
        wg_wait<0>();
        pin(sE);
        TRF(14 + 16 * k);
        gather_mid(sE, tabu.w, tabv.z, v0, v1);
        const float m0 = quad_max(tree_max(v0)), m1 = quad_max(tree_max(v1));

        uint32_t y[14], pa[12], pb[12];
        exp_route<0, 14>(v0, v1, m0, m1, route, (j & 1) == 0, y);
        float s0 = tree_sum(v0), s1 = tree_sum(v1);
        asm volatile("" : "+f"(s0), "+f"(s1));
        unfold<0, 0, 6>(y, tabv.w, pa);
        turn_wait(wg + (y[0] >> 31));
        TRF(15 + 16 * k + (y[13] >> 31));
        wg_fence();
        wgmma_sp_n192_tb<true, 0>(acc, pa[0], pa[1], pa[2], pa[3], desc_at(dA, kToV), tabu.y);
        wgmma_sp_n192_tb<false, 1>(acc, pa[4], pa[5], pa[6], pa[7], desc_at(dA, kToV + 4096), tabu.y);
        wgmma_sp_n192_tb<false, 0>(acc, pa[8], pa[9], pa[10], pa[11], desc_at(dA, kToV + 8192), tabu.z);
        wg_commit();
        wgmma_sp_n192_tb<false, 1>(acc, j == 0 ? 0u : y[10], j == 0 ? 0u : y[11], y[12], y[13], desc_at(dE, kToV + kOffMid), tabu.z);
        wg_commit();
        unfold<8, 0, 6>(y, tabv.w, pb);
        wg_fence();
        wgmma_sp_n192_tb<false, 0>(acc, pb[0], pb[1], pb[2], pb[3], desc_at(dN, kToV), tabu.y);
        wgmma_sp_n192_tb<false, 1>(acc, pb[4], pb[5], pb[6], pb[7], desc_at(dN, kToV + 4096), tabu.y);
        wgmma_sp_n192_tb<false, 0>(acc, pb[8], pb[9], pb[10], pb[11], desc_at(dN, kToV + 8192), tabu.z);
        wg_commit();
        if (!last) turn_pass(wg);
        TRF(16 + 16 * k);
        wg_wait<2>();
        if (lane == 0) mbar_arrive(bar_use);
        wg_wait<1>();
        if (lane == 0) mbar_arrive(bar_use + 16);
        TRF(17 + 16 * k);
        mbar_wait(bar_ok + 16, 0);
        wg_wait<0>();
        if (lane == 0) mbar_arrive(bar_use + 8);
        pin(acc);
        TR(18 + 16 * k);

        acc_to_frags(acc, po);
        pin(po);
        if (last) {
            const float inv0 = rcp(quad_sum(s0)), inv1 = rcp(quad_sum(s1));
            float t0[32], t1[32], t2[32];
            uint32_t pq[48];
            wg_fence();
            third_gemm<0>(t0, po, dsc, [](int) {});
            third_gemm<1>(t1, po, dsc, [&](int s) { if (s == 3) { keep(wqkv == nullptr, __float_as_uint(inv0), __float_as_uint(inv1), c0, c1); __syncwarp(); } });
            wg_wait<1>();
            third_pack<0>(t0, inv0, inv1, pq);
            store_one<false>(true, out + c0, out + c1, pq, 0);
            __syncwarp();
            third_gemm<2>(t2, po, dsc, [&](int s) { if (s == 3 || s == 7 || s == 9) store_one(true, out + c0, out + c1, pq, (s + 3) >> 2); });
            __syncwarp();
            wg_wait<1>();
            third_pack<1>(t1, inv0, inv1, pq);
#pragma unroll
            for (int n = 4; n < 8; n++) store_one<false>(true, out + c0, out + c1, pq, n);
            __syncwarp();
            wg_wait<0>();
            third_pack<2>(t2, inv0, inv1, pq);
#pragma unroll
            for (int n = 8; n < 12; n++) store_one<false>(true, out + c0, out + c1, pq, n);
            break;
        }
        turn_wait(wg);
        wg_fence();
        proj_gemm(acc, po, dsc, s_wv, [&](int s) {
            if (s == 3 || s == 7) { mbar_wait(bar_ok + 2 * s + 18, 0); wg_fence(); }
            if (s + 1 == OSPLIT && i + 2 == w.ntiles) { turn_pass(wg); turn_wait(wg); }
        });
        turn_pass(wg);
        TRF(19 + 16 * k);
        const uint32_t zero = lds_volatile(s_late);
        const float inv0 = rcp(quad_sum(s0 + __uint_as_float(zero))), inv1 = rcp(quad_sum(s1 + __uint_as_float(zero)));
        raw_to_frags(nxt, zero, fa);
        pin(fa);
#pragma unroll
        for (int q = 0; q < 48; q += 4) keep(wqkv == nullptr, fa[q], fa[q + 1], fa[q + 2], fa[q + 3]);
        keep(wqkv == nullptr, __float_as_uint(inv0), __float_as_uint(inv1), zero, lane);
        TRF(20 + 16 * k);
        tu += du2; tv += dv2;
        wg_wait<0>();
        pin(acc);
        TR(21 + 16 * k);
#pragma unroll
        for (int q = 0; q < 96; q++) acc[q] *= q & 2 ? inv1 : inv0;
        pack_out(acc, po);
#pragma unroll
        for (int n = 0; n < INL; n++) store_one<false>(i + 2 == w.ntiles, out + c0, out + c1, po, n);
        pin(po);
    }
    if (wg == 0) {
#pragma unroll
        for (int n = INL; n < 12; n++) {
            __nanosleep(NAP);
            store_one<false>(true, out + c0, out + c1, po, n);
        }
    }
    TRE(7);
    TRG(1);
    TRDUMP();
}

typedef CUresult (*EncodeTiledFn)(CUtensorMap*, CUtensorMapDataType, cuuint32_t, void*, const cuuint64_t*, const cuuint64_t*,
                                  const cuuint32_t*, const cuuint32_t*, CUtensorMapInterleave, CUtensorMapSwizzle,
                                  CUtensorMapL2promotion, CUtensorMapFloatOOBfill);

bool make_maps(EncodeTiledFn fn, Maps* maps, void* x, void* wqkv, void* wo) {
    const cuuint64_t pix2 = 2 * kPixBytes, row = (cuuint64_t)kHW * kPixBytes;
    const cuuint32_t estr[5] = {1, 1, 1, 1, 1};
    bool ok = true;
    for (int tr = 0; tr < 2; tr++)
        for (int b = 0; b < 2; b++) {
            const cuuint64_t su = tr ? 2 * row : pix2, sv = tr ? pix2 : 2 * row;
            const cuuint64_t dims[5] = {2 * kC, 2, 105, 2, 112};
            const cuuint64_t strides[4] = {7 * su, su, row, sv};
            const cuuint32_t box[5] = {64, 2, 7, 1, b ? 2u : 6u};
            ok = ok && fn(&maps->m[2 * tr + b], CU_TENSOR_MAP_DATA_TYPE_BFLOAT16, 5, x, dims, strides, box, estr,
                          CU_TENSOR_MAP_INTERLEAVE_NONE, CU_TENSOR_MAP_SWIZZLE_128B, CU_TENSOR_MAP_L2_PROMOTION_L2_128B,
                          CU_TENSOR_MAP_FLOAT_OOB_FILL_NONE) == CUDA_SUCCESS;
        }
    for (int b = 0; b < 2; b++) {
        const cuuint64_t dims[3] = {b ? 64u : 48u, kC, b ? 9u : 4u}, strides[2] = {(b ? 3u : 1u) * kPixBytes, b ? 128u : 96u};
        const cuuint32_t box[3] = {b ? 64u : 48u, b ? 16u : 192u, b ? 3u : 1u};
        ok = ok && fn(b ? &maps->wv : &maps->wo, CU_TENSOR_MAP_DATA_TYPE_BFLOAT16, 3, b ? wqkv : wo, dims, strides, box, estr,
                      CU_TENSOR_MAP_INTERLEAVE_NONE, b ? CU_TENSOR_MAP_SWIZZLE_128B : CU_TENSOR_MAP_SWIZZLE_NONE, CU_TENSOR_MAP_L2_PROMOTION_L2_128B,
                      CU_TENSOR_MAP_FLOAT_OOB_FILL_NONE) == CUDA_SUCCESS;
    }
    return ok;
}

}

extern "C" void kernel_launch(void* const* d_in, const int* in_sizes, int n_in, void* d_out, int out_size) {
    static EncodeTiledFn encode = nullptr;
    static Scratch* scratch = nullptr;
    static Tables* tables = nullptr;
    if (!encode) {
        int dev = 0, reserved = 0;
        cudaFuncAttributes attr;
        cudaGetDevice(&dev);
        cudaDeviceGetAttribute(&reserved, cudaDevAttrReservedSharedMemoryPerBlock, dev);
        cudaFuncGetAttributes(&attr, nat_fused_kernel);
        if (reserved != (int)kSmemBase || attr.sharedSizeBytes != 0) return;
        cudaGetSymbolAddress((void**)&scratch, g_scratch);
        cudaGetSymbolAddress((void**)&tables, g_tables);
        void* fn = nullptr;
        cudaDriverEntryPointQueryResult st;
        cudaGetDriverEntryPoint("cuTensorMapEncodeTiled", &fn, cudaEnableDefault, &st);
        encode = (EncodeTiledFn)fn;
        cudaFuncSetAttribute(nat_fused_kernel, cudaFuncAttributeMaxDynamicSharedMemorySize, kSmemBytes);
    }
    Maps maps;
    maps.tables = tables;
    if (!encode || !make_maps(encode, &maps, d_in[0], d_in[1], d_in[2])) return;
    nat_fused_kernel<<<kGrid, kThreads, kSmemBytes>>>((const uint8_t*)d_in[0], (const uint8_t*)d_in[1], (uint8_t*)d_out, scratch, (const uint8_t*)d_in[2],
                                                      kDescRing, maps);
}
```

```cpp
#include <cuda_runtime.h>
#include <cuda_bf16.h>
#include <cuda.h>
#include <stdint.h>
#include <type_traits>
#include <stdlib.h>
#include <stdio.h>
#include <stddef.h>

#define ASLOTS 0x1800
#define BSLOTS 0x2
#define QSLOTS 0xfae
#define OSPLIT 2
#define INL 2
#define NAP 50

namespace {

constexpr int kC          = 192;
constexpr int kHW         = 224;
constexpr int kPixBytes   = kC * 2;
constexpr int kSlotBytes  = 84 * 128;
constexpr int kMidBytes   = 28 * 128;
constexpr int kOffMid     = 88 * 128;
constexpr int kSlotStride = 120 * 128;
constexpr int kRingChunk  = 208 * 128;
constexpr int kWChunk     = 192 * 128;
constexpr int kWBytes     = 3 * kWChunk;
constexpr uint32_t kSmemBase = 1024;
constexpr uint32_t s_ring = kSmemBase, s_m = s_ring + 3 * kRingChunk, s_wv = s_m + kWBytes, s_bar = s_wv + kWBytes;
constexpr uint32_t bar_b = s_bar, bar_mid = s_bar + 24, bar_a = s_bar + 32, bar_img = s_bar + 40, bar_redo = s_bar + 88,
                   bar_wop = s_bar + 112, bar_ok = s_bar + 120, bar_use = s_bar + 160, bar_free = s_bar + 184;
constexpr uint32_t s_par = s_bar + 208, s_late = s_bar + 216, s_again = s_bar + 220, s_tab = s_bar + 256, s_trace = s_tab + 2048;
constexpr int kSmemBytes  = s_trace + 2048 - kSmemBase;
constexpr int kThreads    = 384;
constexpr int kGrid       = 132;
constexpr int kTimeM = 2500, kTimeW = 5100;
constexpr float kScaleLog2e = 0.07216878364870322f * 1.4426950408889634f;

struct Maps {
    CUtensorMap m[4];
    CUtensorMap wo, wv;
    const struct Tables* tables;
};
#define TN(i, dflt) (dflt)
#define START_TIME (wg ? 900 + 450 * order : 250 + 560 * order)

struct Scratch {
    uint8_t img[2][2][kWBytes];
    uint32_t launches[kGrid][32];
};
__device__ __align__(1024) Scratch g_scratch;

__host__ __device__ constexpr int entry_bit(int k) { return 8 * ((k >> 1) & 3) + 3 * (k & 1); }
struct Table {
    uint32_t route[32][4];
    uint32_t u[8][4][4];
    uint32_t v[16][4][4];
};
struct Tables { Table t[2]; };
constexpr Tables make_tables() {
    Tables r = {};
    for (int rev = 0; rev < 2; rev++)
        for (int j = 0; j < 4; j++) {
            Table& t = r.t[rev];
            for (int q = 0; q < 8; q++) {
                uint32_t* e = t.route[4 * q + j];
                e[0] = 4 * q + 2 * (j & 1) + (j >> 1); e[1] = e[0] ^ 1;
                e[2] = j < 2 ? 0x5410u : 0x1054u; e[3] = e[2] + 0x2222u;
                e = t.u[q][j];
                for (int k = 0; k < 16; k++) e[k >> 3] |= ((4 * (k < 12 ? k : k - 2) + j) % 7 < q ? 1u : 0u) << entry_bit(k);
                for (int k = 0; k < 2; k++) {
                    const int step = 2 * k + (j >> 1), p0 = (step < 3 ? 16 * step : 40) + 8 * (j & 1);
                    uint32_t m = 0x8888u;
                    for (int n = 0; n < 8; n++) m |= ((p0 + n) % 7 < q ? 1u : 0u) << (2 * n);
                    e[2 + k] = m * 0x10001u;
                }
            }
            for (int sum = 0; sum < 15; sum++) {
                uint32_t* e = t.v[sum][j];
                for (int row = 0; row < 2; row++)
                    for (int b = 0; b < 14; b++) {
                        const int off = (sum + row) / 2, p = 4 * b + j;
                        if (p < 42 && p >= 7 * off) e[2 * rev + (b >> 3)] |= 2u << (entry_bit(b) + row);
                        if (p < 7 * off - 7) e[2 - 2 * rev + (b >> 3)] |= 2u << (entry_bit(b) + row);
                        if (p >= 42 && p >= 7 * off && p < 7 * off + 49) e[3] |= 2u << (entry_bit(b + 2) + row);
                    }
                for (int n = 0; n < 6; n++)
                    if (8 * n + 2 * j < 42) e[1] |= 0x10000u << (n + ((8 * n + 2 * j >= 7 * (sum / 2 & ~1)) != rev ? 0 : 8));
            }
        }
    return r;
}
__device__ __align__(128) const Tables g_tables = make_tables();

#define WO4(i) "=f"(d[i]), "=f"(d[i + 1]), "=f"(d[i + 2]), "=f"(d[i + 3])
#define RW4(i) "+f"(d[i]), "+f"(d[i + 1]), "+f"(d[i + 2]), "+f"(d[i + 3])

template <bool FIRST>
__device__ __forceinline__ void wgmma_n192(float (&d)[96], uint32_t a0, uint32_t a1, uint32_t a2, uint32_t a3, uint64_t descb) {
    if constexpr (FIRST) {
        asm volatile(
            "wgmma.mma_async.sync.aligned.m64n192k16.f32.bf16.bf16 "
            "{%0, %1, %2, %3, %4, %5, %6, %7, %8, %9, %10, %11, %12, %13, %14, %15, %16, %17, %18, %19, %20, %21, %22, %23, "
            "%24, %25, %26, %27, %28, %29, %30, %31, %32, %33, %34, %35, %36, %37, %38, %39, %40, %41, %42, %43, %44, %45, %46, %47, "
            "%48, %49, %50, %51, %52, %53, %54, %55, %56, %57, %58, %59, %60, %61, %62, %63, %64, %65, %66, %67, %68, %69, %70, %71, "
            "%72, %73, %74, %75, %76, %77, %78, %79, %80, %81, %82, %83, %84, %85, %86, %87, %88, %89, %90, %91, %92, %93, %94, %95}, "
            "{%96, %97, %98, %99}, %100, 0, 1, 1, 0;"
            : WO4(0), WO4(4), WO4(8), WO4(12), WO4(16), WO4(20), WO4(24), WO4(28), WO4(32), WO4(36), WO4(40), WO4(44),
              WO4(48), WO4(52), WO4(56), WO4(60), WO4(64), WO4(68), WO4(72), WO4(76), WO4(80), WO4(84), WO4(88), WO4(92)
            : "r"(a0), "r"(a1), "r"(a2), "r"(a3), "l"(descb));
    } else {
        asm volatile(
            "wgmma.mma_async.sync.aligned.m64n192k16.f32.bf16.bf16 "
            "{%0, %1, %2, %3, %4, %5, %6, %7, %8, %9, %10, %11, %12, %13, %14, %15, %16, %17, %18, %19, %20, %21, %22, %23, "
            "%24, %25, %26, %27, %28, %29, %30, %31, %32, %33, %34, %35, %36, %37, %38, %39, %40, %41, %42, %43, %44, %45, %46, %47, "
            "%48, %49, %50, %51, %52, %53, %54, %55, %56, %57, %58, %59, %60, %61, %62, %63, %64, %65, %66, %67, %68, %69, %70, %71, "
            "%72, %73, %74, %75, %76, %77, %78, %79, %80, %81, %82, %83, %84, %85, %86, %87, %88, %89, %90, %91, %92, %93, %94, %95}, "
            "{%96, %97, %98, %99}, %100, 1, 1, 1, 0;"
            : RW4(0), RW4(4), RW4(8), RW4(12), RW4(16), RW4(20), RW4(24), RW4(28), RW4(32), RW4(36), RW4(40), RW4(44),
              RW4(48), RW4(52), RW4(56), RW4(60), RW4(64), RW4(68), RW4(72), RW4(76), RW4(80), RW4(84), RW4(88), RW4(92)
            : "r"(a0), "r"(a1), "r"(a2), "r"(a3), "l"(descb));
    }
}

template <bool FIRST>
__device__ __forceinline__ void wgmma_n64(float (&d)[32], uint32_t a0, uint32_t a1, uint32_t a2, uint32_t a3, uint64_t descb) {
    if constexpr (FIRST) {
        asm volatile(
            "wgmma.mma_async.sync.aligned.m64n64k16.f32.bf16.bf16 "
            "{%0, %1, %2, %3, %4, %5, %6, %7, %8, %9, %10, %11, %12, %13, %14, %15, %16, %17, %18, %19, %20, %21, %22, %23, "
            "%24, %25, %26, %27, %28, %29, %30, %31}, "
            "{%32, %33, %34, %35}, %36, 0, 1, 1, 0;"
            : WO4(0), WO4(4), WO4(8), WO4(12), WO4(16), WO4(20), WO4(24), WO4(28)
            : "r"(a0), "r"(a1), "r"(a2), "r"(a3), "l"(descb));
    } else {
        asm volatile(
            "wgmma.mma_async.sync.aligned.m64n64k16.f32.bf16.bf16 "
            "{%0, %1, %2, %3, %4, %5, %6, %7, %8, %9, %10, %11, %12, %13, %14, %15, %16, %17, %18, %19, %20, %21, %22, %23, "
            "%24, %25, %26, %27, %28, %29, %30, %31}, "
            "{%32, %33, %34, %35}, %36, 1, 1, 1, 0;"
            : RW4(0), RW4(4), RW4(8), RW4(12), RW4(16), RW4(20), RW4(24), RW4(28)
            : "r"(a0), "r"(a1), "r"(a2), "r"(a3), "l"(descb));
    }
}

template <bool FIRST>
__device__ __forceinline__ void wgmma_n88(float (&d)[44], uint32_t a0, uint32_t a1, uint32_t a2, uint32_t a3, uint64_t descb) {
    if constexpr (FIRST) {
        asm volatile(
            "wgmma.mma_async.sync.aligned.m64n88k16.f32.bf16.bf16 "
            "{%0, %1, %2, %3, %4, %5, %6, %7, %8, %9, %10, %11, %12, %13, %14, %15, %16, %17, %18, %19, %20, %21, %22, %23, "
            "%24, %25, %26, %27, %28, %29, %30, %31, %32, %33, %34, %35, %36, %37, %38, %39, %40, %41, %42, %43}, "
            "{%44, %45, %46, %47}, %48, 0, 1, 1, 0;"
            : WO4(0), WO4(4), WO4(8), WO4(12), WO4(16), WO4(20), WO4(24), WO4(28), WO4(32), WO4(36), WO4(40)
            : "r"(a0), "r"(a1), "r"(a2), "r"(a3), "l"(descb));
    } else {
        asm volatile(
            "wgmma.mma_async.sync.aligned.m64n88k16.f32.bf16.bf16 "
            "{%0, %1, %2, %3, %4, %5, %6, %7, %8, %9, %10, %11, %12, %13, %14, %15, %16, %17, %18, %19, %20, %21, %22, %23, "
            "%24, %25, %26, %27, %28, %29, %30, %31, %32, %33, %34, %35, %36, %37, %38, %39, %40, %41, %42, %43}, "
            "{%44, %45, %46, %47}, %48, 1, 1, 1, 0;"
            : RW4(0), RW4(4), RW4(8), RW4(12), RW4(16), RW4(20), RW4(24), RW4(28), RW4(32), RW4(36), RW4(40)
            : "r"(a0), "r"(a1), "r"(a2), "r"(a3), "l"(descb));
    }
}

template <bool FIRST>
__device__ __forceinline__ void wgmma_n32(float (&d)[16], uint32_t a0, uint32_t a1, uint32_t a2, uint32_t a3, uint64_t descb) {
    if constexpr (FIRST) {
        asm volatile(
            "wgmma.mma_async.sync.aligned.m64n32k16.f32.bf16.bf16 "
            "{%0, %1, %2, %3, %4, %5, %6, %7, %8, %9, %10, %11, %12, %13, %14, %15}, "
            "{%16, %17, %18, %19}, %20, 0, 1, 1, 0;"
            : WO4(0), WO4(4), WO4(8), WO4(12)
            : "r"(a0), "r"(a1), "r"(a2), "r"(a3), "l"(descb));
    } else {
        asm volatile(
            "wgmma.mma_async.sync.aligned.m64n32k16.f32.bf16.bf16 "
            "{%0, %1, %2, %3, %4, %5, %6, %7, %8, %9, %10, %11, %12, %13, %14, %15}, "
            "{%16, %17, %18, %19}, %20, 1, 1, 1, 0;"
            : RW4(0), RW4(4), RW4(8), RW4(12)
            : "r"(a0), "r"(a1), "r"(a2), "r"(a3), "l"(descb));
    }
}

template <bool FIRST, int SEL>
__device__ __forceinline__ void wgmma_sp_n192_tb(float (&d)[96], uint32_t a0, uint32_t a1, uint32_t a2, uint32_t a3, uint64_t descb, uint32_t meta) {
    if constexpr (FIRST) {
        asm volatile(
            "wgmma.mma_async.sp.sync.aligned.m64n192k32.f32.bf16.bf16 "
            "{%0, %1, %2, %3, %4, %5, %6, %7, %8, %9, %10, %11, %12, %13, %14, %15, %16, %17, %18, %19, %20, %21, %22, %23, "
            "%24, %25, %26, %27, %28, %29, %30, %31, %32, %33, %34, %35, %36, %37, %38, %39, %40, %41, %42, %43, %44, %45, %46, %47, "
            "%48, %49, %50, %51, %52, %53, %54, %55, %56, %57, %58, %59, %60, %61, %62, %63, %64, %65, %66, %67, %68, %69, %70, %71, "
            "%72, %73, %74, %75, %76, %77, %78, %79, %80, %81, %82, %83, %84, %85, %86, %87, %88, %89, %90, %91, %92, %93, %94, %95}, "
            "{%96, %97, %98, %99}, %100, %101, %102, 0, 1, 1, 1;"
            : WO4(0), WO4(4), WO4(8), WO4(12), WO4(16), WO4(20), WO4(24), WO4(28), WO4(32), WO4(36), WO4(40), WO4(44),
              WO4(48), WO4(52), WO4(56), WO4(60), WO4(64), WO4(68), WO4(72), WO4(76), WO4(80), WO4(84), WO4(88), WO4(92)
            : "r"(a0), "r"(a1), "r"(a2), "r"(a3), "l"(descb), "r"(meta), "n"(SEL));
    } else {
        asm volatile(
            "wgmma.mma_async.sp.sync.aligned.m64n192k32.f32.bf16.bf16 "
            "{%0, %1, %2, %3, %4, %5, %6, %7, %8, %9, %10, %11, %12, %13, %14, %15, %16, %17, %18, %19, %20, %21, %22, %23, "
            "%24, %25, %26, %27, %28, %29, %30, %31, %32, %33, %34, %35, %36, %37, %38, %39, %40, %41, %42, %43, %44, %45, %46, %47, "
            "%48, %49, %50, %51, %52, %53, %54, %55, %56, %57, %58, %59, %60, %61, %62, %63, %64, %65, %66, %67, %68, %69, %70, %71, "
            "%72, %73, %74, %75, %76, %77, %78, %79, %80, %81, %82, %83, %84, %85, %86, %87, %88, %89, %90, %91, %92, %93, %94, %95}, "
            "{%96, %97, %98, %99}, %100, %101, %102, 1, 1, 1, 1;"
            : RW4(0), RW4(4), RW4(8), RW4(12), RW4(16), RW4(20), RW4(24), RW4(28), RW4(32), RW4(36), RW4(40), RW4(44),
              RW4(48), RW4(52), RW4(56), RW4(60), RW4(64), RW4(68), RW4(72), RW4(76), RW4(80), RW4(84), RW4(88), RW4(92)
            : "r"(a0), "r"(a1), "r"(a2), "r"(a3), "l"(descb), "r"(meta), "n"(SEL));
    }
}

#define TR(slot)
#define TRX(slot)
#define TRE(slot)
#define TRT(slot)
#define TRF(slot)
#define TRW(slot)
#define TRG(slot)
#define TRDUMP()

__device__ __forceinline__ void wg_fence() { asm volatile("wgmma.fence.sync.aligned;" ::: "memory"); }
__device__ __forceinline__ void wg_commit() { asm volatile("wgmma.commit_group.sync.aligned;" ::: "memory"); }
template <int N>
__device__ __forceinline__ void wg_wait() { asm volatile("wgmma.wait_group.sync.aligned %0;" ::"n"(N) : "memory"); }

template <int N>
__device__ __forceinline__ void pin(float (&d)[N]) {
#pragma unroll
    for (int i = 0; i < N; i++) asm volatile("" : "+f"(d[i])::"memory");
}
template <int N>
__device__ __forceinline__ void pin(uint32_t (&d)[N]) {
#pragma unroll
    for (int i = 0; i < N; i++) asm volatile("" : "+r"(d[i])::"memory");
}

constexpr uint64_t kDescRing = ((uint64_t)((1u << 30) | (1024u >> 4)) << 32) | (1u << 16) | (s_ring >> 4);
constexpr uint32_t kToV = ((kRingChunk >> 4) - 1) << 20;
__device__ __forceinline__ uint64_t desc_at(uint64_t base, uint32_t byte_off) {
    uint64_t d;
    asm volatile("add.s64 %0, %1, %2;" : "=l"(d) : "l"(base), "l"((uint64_t)(byte_off >> 4)));
    return d;
}

__device__ __forceinline__ void mbar_init(uint32_t bar, uint32_t count) {
    asm volatile("mbarrier.init.shared::cta.b64 [%0], %1;" ::"r"(bar), "r"(count) : "memory");
}
__device__ __forceinline__ void mbar_expect_tx(uint32_t bar, uint32_t bytes) {
    asm volatile("mbarrier.arrive.expect_tx.shared::cta.b64 _, [%0], %1;" ::"r"(bar), "r"(bytes) : "memory");
}
__device__ __forceinline__ void expect_tx_only(uint32_t bar, uint32_t bytes) {
    asm volatile("mbarrier.expect_tx.relaxed.cta.shared::cta.b64 [%0], %1;" ::"r"(bar), "r"(bytes) : "memory");
}
__device__ __forceinline__ void mbar_arrive(uint32_t bar) {
    asm volatile("mbarrier.arrive.shared::cta.b64 _, [%0];" ::"r"(bar) : "memory");
}
__device__ __forceinline__ void mbar_wait(uint32_t bar, uint32_t parity) {
    asm volatile(
        "{\n.reg .pred p;\n"
        "W: mbarrier.try_wait.parity.shared::cta.b64 p, [%0], %1;\n"
        "@!p bra W;\n}\n"
        ::"r"(bar), "r"(parity) : "memory");
}
__device__ __forceinline__ uint32_t clock_now() {
    uint32_t c;
    asm volatile("mov.u32 %0, %%clock;" : "=r"(c)::"memory");
    return c;
}
__device__ __forceinline__ void wait_until(uint32_t t0, int t) {
    if (t == 0) return;
    while ((int)(clock_now() - t0) < t) {}
}
__device__ __forceinline__ bool elect() {
    uint32_t ok;
    asm volatile("{\n.reg .pred p;\nelect.sync _|p, 0xffffffff;\nselp.u32 %0, 1, 0, p;\n}\n" : "=r"(ok));
    return ok != 0;
}
__device__ __forceinline__ void turn_wait(int wg) { asm volatile("bar.sync %0, 256;" ::"r"(1 + wg) : "memory"); }
__device__ __forceinline__ void turn_pass(int wg) { asm volatile("bar.arrive %0, 256;" ::"r"(2 - wg) : "memory"); }

__device__ __forceinline__ void tma_box(uint32_t dst, const CUtensorMap* map, uint32_t bar, int c0, int c2, int c3, int c4) {
    asm volatile(
        "cp.async.bulk.tensor.5d.shared::cluster.global.mbarrier::complete_tx::bytes [%0], [%1, {%3, %4, %5, %6, %7}], [%2];"
        ::"r"(dst), "l"(map), "r"(bar), "r"(c0), "r"(0), "r"(c2), "r"(c3), "r"(c4)
        : "memory");
}
__device__ __forceinline__ void tma_3d(uint32_t dst, const CUtensorMap* map, uint32_t bar, int c1, int c2) {
    asm volatile("cp.async.bulk.tensor.3d.shared::cluster.global.mbarrier::complete_tx::bytes [%0], [%1, {%3, %4, %5}], [%2];"
                 ::"r"(dst), "l"(map), "r"(bar), "r"(0), "r"(c1), "r"(c2)
                 : "memory");
}
__device__ __forceinline__ void prefetch_map(const CUtensorMap* map) {
    asm volatile("prefetch.tensormap [%0];" ::"l"(map) : "memory");
}
__device__ __forceinline__ uint4 ldg(const void* p) {
    uint4 v;
    asm volatile("ld.global.v4.u32 {%0, %1, %2, %3}, [%4];" : "=r"(v.x), "=r"(v.y), "=r"(v.z), "=r"(v.w) : "l"(p) : "memory");
    return v;
}
__device__ __forceinline__ uint32_t pack_bf16(float lo, float hi) {
    uint32_t r;
    asm("cvt.rn.bf16x2.f32 %0, %1, %2;" : "=r"(r) : "f"(hi), "f"(lo));
    return r;
}
__device__ __forceinline__ float ex2(float x) {
    float y;
    asm("ex2.approx.ftz.f32 %0, %1;" : "=f"(y) : "f"(x));
    return y;
}
__device__ __forceinline__ float rcp(float x) {
    float y;
    asm("rcp.approx.ftz.f32 %0, %1;" : "=f"(y) : "f"(x));
    return y;
}
__device__ __forceinline__ void mma16816(float (&d)[4], uint32_t a0, uint32_t a1, uint32_t a2, uint32_t a3, uint32_t b0, uint32_t b1) {
    asm volatile("mma.sync.aligned.m16n8k16.row.col.f32.bf16.bf16.f32 {%0, %1, %2, %3}, {%4, %5, %6, %7}, {%8, %9}, {%0, %1, %2, %3};"
                 : "+f"(d[0]), "+f"(d[1]), "+f"(d[2]), "+f"(d[3])
                 : "r"(a0), "r"(a1), "r"(a2), "r"(a3), "r"(b0), "r"(b1));
}
__device__ __forceinline__ uint4 lds128(uint32_t addr) {
    uint4 v;
    asm volatile("ld.volatile.shared.v4.u32 {%0, %1, %2, %3}, [%4];" : "=r"(v.x), "=r"(v.y), "=r"(v.z), "=r"(v.w) : "r"(addr) : "memory");
    return v;
}
__device__ __forceinline__ uint32_t lds_volatile(uint32_t addr) {
    uint32_t v;
    asm volatile("ld.volatile.shared.u32 %0, [%1];" : "=r"(v) : "r"(addr) : "memory");
    return v;
}

__device__ __forceinline__ int window_start(int n) { return min(max(n, 0), 105); }
__device__ __forceinline__ int origin_u(int u) { return min(max(u, 0), 98); }

struct Work {
    int u, v;
    int step;
    uint32_t su, sv;
    uint32_t base;
    bool corner;
    int ntiles;
    __device__ __forceinline__ void pixel_offsets(int qu, int qv, int j, uint32_t& o0, uint32_t& o1) const {
        const uint32_t b = (qu + window_start(qu)) * su + j * 16 + base;
        o0 = b + (qv + window_start(qv)) * sv;
        o1 = b + (qv + 1 + window_start(qv + 1)) * sv;
    }
};

__device__ __forceinline__ Work decode_work(int c) {
    Work w;
    const bool transposed = (c >> 4) == 7;
    const int px = 6 * (c & 1), py = 3 * (c & 2);
    w.corner = c >= 128;
    w.step = 8 - 4 * (c & 4);
    w.u = (c < 112 ? c & ~7 : 96 + (c & 8)) + (transposed ? py : px) - 6;
    w.v = (w.corner ? 96 : 48 - 2 * (c & 4)) + (transposed ? px : py) - 6;
    w.su = transposed ? kHW * kPixBytes : kPixBytes;
    w.sv = transposed ? kPixBytes : kHW * kPixBytes;
    w.base = px * (kPixBytes / 6) + py * (kHW * kPixBytes / 6) + 6 * (kHW + 1) * kPixBytes;
    w.ntiles = w.corner ? 4 : 6;
    return w;
}

struct RawX { uint4 a[6], b[6]; };
__device__ __forceinline__ void load_raw(RawX& r, const uint8_t* base, uint32_t o0, uint32_t o1) {
    __syncwarp();
#pragma unroll
    for (int c = 0; c < 6; c++) { r.a[c] = ldg(base + o0 + c * 64); r.b[c] = ldg(base + o1 + c * 64); }
    __syncwarp();
}
__device__ __forceinline__ void raw_to_frags(const RawX& r, uint32_t zero, uint32_t (&f)[48]) {
#pragma unroll
    for (int c = 0; c < 6; c++) {
        asm volatile("{\n.reg .b32 t, u;\nadd.u32 t, %4, %8;\nadd.u32 u, %5, %8;\nxor.b32 %0, %6, %8;\nxor.b32 %1, %7, %8;\n"
                     "xor.b32 %2, t, %8;\nxor.b32 %3, u, %8;\n}\n"
                     : "=&r"(f[8 * c + 1]), "=&r"(f[8 * c + 3]), "=&r"(f[8 * c + 4]), "=&r"(f[8 * c + 6])
                     : "r"(r.a[c].y), "r"(r.a[c].w), "r"(r.b[c].x), "r"(r.b[c].z), "r"(zero));
        f[8 * c + 0] = r.a[c].x; f[8 * c + 2] = r.a[c].z; f[8 * c + 5] = r.b[c].y; f[8 * c + 7] = r.b[c].w;
    }
}
__device__ __forceinline__ void acc_to_frags(const float (&d)[96], uint32_t (&f)[48]) {
#pragma unroll
    for (int i = 0; i < 48; i++) f[i] = pack_bf16(d[2 * i], d[2 * i + 1]);
}

template <class F>
__device__ __forceinline__ void proj_gemm(float (&d)[96], const uint32_t (&a)[48], uint64_t dsc, uint32_t img, F after) {
#pragma unroll
    for (int s = 0; s < 12; s++) {
        if (s == 0) wgmma_n192<true>(d, a[4 * s], a[4 * s + 1], a[4 * s + 2], a[4 * s + 3], desc_at(dsc, img - s_ring + (s >> 2) * kWChunk + (s & 3) * 32));
        else wgmma_n192<false>(d, a[4 * s], a[4 * s + 1], a[4 * s + 2], a[4 * s + 3], desc_at(dsc, img - s_ring + (s >> 2) * kWChunk + (s & 3) * 32));
        if (s == 11) wg_commit();
        after(s);
    }
}
__device__ __forceinline__ void pack_out(const float (&acc)[96], uint32_t (&po)[48]) {
#pragma unroll
    for (int g = 0; g < 6; g++)
#pragma unroll
        for (int q = 0; q < 4; q++) {
            po[8 * g + q] = pack_bf16(acc[16 * g + 4 * q], acc[16 * g + 4 * q + 1]);
            po[8 * g + 4 + q] = pack_bf16(acc[16 * g + 4 * q + 2], acc[16 * g + 4 * q + 3]);
        }
}
template <bool PINNED = true>
__device__ __forceinline__ void store_one(bool on, uint8_t* p0, uint8_t* p1, const uint32_t (&po)[48], int n) {
    if (PINNED) __syncwarp();
    asm volatile("{\n.reg .pred p;\nsetp.ne.u32 p, %5, 0;\n@p st.global.v4.u32 [%0], {%1, %2, %3, %4};\n}\n"
                 ::"l"(((n & 1) ? p1 : p0) + (n >> 1) * 64), "r"(po[4 * n]), "r"(po[4 * n + 1]), "r"(po[4 * n + 2]), "r"(po[4 * n + 3]), "r"((uint32_t)on) : "memory");
}

template <int N>
__device__ __forceinline__ float tree_max(const float (&v)[N]) {
    float t[N];
#pragma unroll
    for (int i = 0; i < N; i++) t[i] = v[i];
#pragma unroll
    for (int w = 1; w < N; w *= 2)
#pragma unroll
        for (int i = 0; i + w < N; i += 2 * w) t[i] = fmaxf(t[i], t[i + w]);
    return t[0];
}
template <int N>
__device__ __forceinline__ float tree_sum(const float (&v)[N]) {
    float t[N];
#pragma unroll
    for (int i = 0; i < N; i++) t[i] = v[i];
#pragma unroll
    for (int w = 1; w < N; w *= 2)
#pragma unroll
        for (int i = 0; i + w < N; i += 2 * w) t[i] += t[i + w];
    return t[0];
}

template <int T, class F>
__device__ __forceinline__ void third_gemm(float (&d)[32], const uint32_t (&a)[48], uint64_t dsc, F after) {
#pragma unroll
    for (int s = 0; s < 12; s++) {
        if (s == 0) wgmma_n64<true>(d, a[4 * s], a[4 * s + 1], a[4 * s + 2], a[4 * s + 3], desc_at(dsc, s_wv - s_ring + T * 8192 + (s >> 2) * kWChunk + (s & 3) * 32));
        else wgmma_n64<false>(d, a[4 * s], a[4 * s + 1], a[4 * s + 2], a[4 * s + 3], desc_at(dsc, s_wv - s_ring + T * 8192 + (s >> 2) * kWChunk + (s & 3) * 32));
        if (s == 11) wg_commit();
        after(s);
    }
}
template <int T>
__device__ __forceinline__ void third_pack(float (&d)[32], float i0, float i1, uint32_t (&po)[48]) {
    pin(d);
#pragma unroll
    for (int g = 0; g < 2; g++)
#pragma unroll
        for (int q = 0; q < 4; q++) {
            po[16 * T + 8 * g + q] = pack_bf16(d[16 * g + 4 * q] * i0, d[16 * g + 4 * q + 1] * i0);
            po[16 * T + 8 * g + 4 + q] = pack_bf16(d[16 * g + 4 * q + 2] * i1, d[16 * g + 4 * q + 3] * i1);
        }
}

template <int K>
__device__ __forceinline__ void pick(uint32_t m0, uint32_t m1, const float* s, float& v0, float& v1) {
    asm("{\n.reg .pred p, q0, q1;\n.reg .b32 t;\nand.b32 t, %6, %7;\nsetp.ne.u32 p, t, 0;\n"
        "and.b32 t, %6, %8;\nsetp.ne.u32 q0, t, 0;\nand.b32 t, %6, %9;\nsetp.ne.u32 q1, t, 0;\n"
        "@q0 selp.f32 %0, %3, %2, p;\n@q1 selp.f32 %1, %5, %4, p;\n}\n"
        : "+f"(v0), "+f"(v1)
        : "f"(s[0]), "f"(s[1]), "f"(s[2]), "f"(s[3]), "r"(K < 8 ? m0 : m1), "n"(1 << entry_bit(K)), "n"(2 << entry_bit(K)), "n"(4 << entry_bit(K)));
}
template <int B, class F>
__device__ __forceinline__ void for_blocks(F f) {
    if constexpr (B > 0) { for_blocks<B - 1>(f); f(std::integral_constant<int, B - 1>{}); }
}
__device__ __forceinline__ void gather_outer(const float (&s)[44], uint32_t m0, uint32_t m1, float (&v0)[14], float (&v1)[14]) {
    for_blocks<11>([&](auto B) {
        constexpr int b = B.value;
        pick<b>(m0, m1, &s[4 * b], v0[b], v1[b]);
    });
}
__device__ __forceinline__ void gather_mid(const float (&sE)[16], uint32_t m1, float (&v0)[14], float (&v1)[14]) {
    for_blocks<4>([&](auto B) {
        constexpr int b = B.value;
        pick<12 + b>(0, m1, &sE[4 * b], v0[10 + b], v1[10 + b]);
    });
}
__device__ __forceinline__ float quad_max(float m) {
    m = fmaxf(m, __shfl_xor_sync(0xffffffffu, m, 1));
    return fmaxf(m, __shfl_xor_sync(0xffffffffu, m, 2));
}
__device__ __forceinline__ float quad_sum(float s) {
    s += __shfl_xor_sync(0xffffffffu, s, 1);
    return s + __shfl_xor_sync(0xffffffffu, s, 2);
}
template <int B0, int B1>
__device__ __forceinline__ void exp_route(float (&v0)[14], float (&v1)[14], float m0, float m1, const uint4& r, bool even, uint32_t (&y)[14]) {
#pragma unroll
    for (int b = B0; b < B1; b++) { v0[b] = ex2(v0[b] - m0); v1[b] = ex2(v1[b] - m1); }
#pragma unroll
    for (int b = B0; b < B1; b += 2) {
        const uint32_t x0 = pack_bf16(v0[b], v1[b]), x1 = pack_bf16(v0[b + 1], v1[b + 1]);
        const uint32_t u = __shfl_sync(0xffffffffu, even ? x0 : x1, r.x);
        const uint32_t w = __shfl_sync(0xffffffffu, even ? x1 : x0, r.y);
        y[b] = __byte_perm(u, w, r.z); y[b + 1] = __byte_perm(u, w, r.w);
    }
}
template <int BIT0, int N0, int N1>
__device__ __forceinline__ void unfold(const uint32_t (&y)[14], uint32_t fold, uint32_t (&p)[12]) {
    for_blocks<N1 - N0>([&](auto N) {
        constexpr int n = N0 + N.value;
        asm("{\n.reg .pred p;\n.reg .b32 t;\nand.b32 t, %4, %5;\nsetp.ne.u32 p, t, 0;\nselp.b32 %0, %2, 0, p;\nselp.b32 %1, %3, 0, p;\n}\n"
            : "=r"(p[2 * n]), "=r"(p[2 * n + 1]) : "r"(y[2 * n]), "r"(y[2 * n + 1]), "r"(fold), "n"(1 << (BIT0 + n)));
    });
}
__device__ __forceinline__ void keep(bool never, uint32_t a, uint32_t b, uint32_t c, uint32_t d) {
    asm volatile("{\n.reg .pred p;\nsetp.ne.u32 p, %4, 0;\n@p st.volatile.shared.v4.u32 [%5], {%0, %1, %2, %3};\n}\n"
                 ::"r"(a), "r"(b), "r"(c), "r"(d), "r"((uint32_t)never), "r"(s_trace) : "memory");
}

__device__ __forceinline__ uint32_t wimg_offset(uint32_t row, uint32_t s, uint32_t j) {
    return (s >> 2) * kWChunk + row * 128 + (((2 * (s & 3) + (j >> 1)) ^ (row & 7)) << 4) + (j & 1) * 8;
}

__device__ __forceinline__ void ldsm4(uint32_t (&r)[4], uint32_t addr) {
    asm volatile("ldmatrix.sync.aligned.m8n8.x4.shared.b16 {%0, %1, %2, %3}, [%4];" : "=r"(r[0]), "=r"(r[1]), "=r"(r[2]), "=r"(r[3]) : "r"(addr) : "memory");
}
__device__ __forceinline__ void ldsm4_t(uint32_t (&r)[4], uint32_t addr) {
    asm volatile("ldmatrix.sync.aligned.m8n8.x4.trans.shared.b16 {%0, %1, %2, %3}, [%4];" : "=r"(r[0]), "=r"(r[1]), "=r"(r[2]), "=r"(r[3]) : "r"(addr) : "memory");
}
struct MOperands { uint4 A[2][2], B[4][2]; };
__device__ __forceinline__ void m_load(MOperands& m, const uint8_t* wqkv, uint32_t mt, uint32_t s, uint32_t q, uint32_t lane) {
    const uint32_t r8 = lane >> 2, col = q * 128 + (lane & 3) * 16;
    const uint8_t* pa = wqkv + (16 * mt + r8) * 1152 + col;
    const uint8_t* pb = wqkv + (16 * s + 8 * (r8 & 2) + (r8 & 5)) * 1152 + col;
#pragma unroll
    for (int c = 0; c < 2; c++) {
#pragma unroll
        for (int h = 0; h < 2; h++) m.A[h][c] = ldg(pa + 384 + h * 8 * 1152 + c * 64);
#pragma unroll
        for (int n = 0; n < 4; n++) m.B[n][c] = ldg(pb + ((n & 1) * 8 + (n & 2)) * 1152 + c * 64);
    }
}
__device__ __forceinline__ void m_partial(MOperands& m, uint32_t q, uint32_t lane, uint32_t zero) {
    auto& A = m.A;
    auto& B = m.B;
#pragma unroll
    for (int i = 0; i < 4; i++) { uint4& a = A[i >> 1][i & 1]; a.x ^= zero; a.y ^= zero; a.z ^= zero; a.w ^= zero; }
#pragma unroll
    for (int n = 0; n < 4; n++) {
        float d[4] = {0.f, 0.f, 0.f, 0.f};
#pragma unroll
        for (int c = 0; c < 2; c++) {
            mma16816(d, A[0][c].x, A[1][c].x, A[0][c].y, A[1][c].y, B[n][c].x, B[n][c].y);
            mma16816(d, A[0][c].z, A[1][c].z, A[0][c].w, A[1][c].w, B[n][c].z, B[n][c].w);
        }
        asm volatile("st.shared.v4.f32 [%0], {%1, %2, %3, %4};" ::"r"(s_wv + q * 2048 + n * 512 + lane * 16), "f"(d[0]), "f"(d[1]), "f"(d[2]), "f"(d[3]) : "memory");
    }
}
__device__ __forceinline__ void m_reduce(uint32_t e, uint32_t lane, float (&d)[2][4]) {
#pragma unroll
    for (int n = 0; n < 2; n++) {
        float t[3][4];
#pragma unroll
        for (int q = 0; q < 3; q++)
            asm volatile("ld.shared.v4.f32 {%0, %1, %2, %3}, [%4];" : "=f"(t[q][0]), "=f"(t[q][1]), "=f"(t[q][2]), "=f"(t[q][3]) : "r"(s_wv + q * 2048 + e * 1024 + n * 512 + lane * 16) : "memory");
#pragma unroll
        for (int i = 0; i < 4; i++) d[n][i] = (t[0][i] + t[1][i] + t[2][i]) * kScaleLog2e;
    }
}
__device__ __forceinline__ void w_piece(uint32_t q, uint32_t lane, float (&d)[2][4]) {
    const uint32_t rr = lane & 7, mi = lane >> 3, kr = 4 * (rr >> 1) + (mi & 2) + (rr & 1);
    const uint32_t pa = s_wv + q * 32 + (4 * (mi & 2) + rr) * 96 + ((mi & 1) << 4);
    const uint32_t pb = s_wv + 3 * 6144 + kr * 128 + (((mi & 1) ^ (kr & 7)) << 4);
    float e[2][4];
#pragma unroll
    for (int i = 0; i < 8; i++) (&d[0][0])[i] = (&e[0][0])[i] = 0.f;
#pragma unroll
    for (int k = 0; k < 12; k++) {
        uint32_t aq[4], bq[4];
        ldsm4_t(aq, pa + k * 1536);
        ldsm4(bq, (pb ^ ((k & 3) << 5)) + (k >> 2) * 2048);
        mma16816(k & 1 ? e[0] : d[0], aq[0], aq[1], aq[2], aq[3], bq[0], bq[1]);
        mma16816(k & 1 ? e[1] : d[1], aq[0], aq[1], aq[2], aq[3], bq[2], bq[3]);
    }
#pragma unroll
    for (int i = 0; i < 8; i++) (&d[0][0])[i] += (&e[0][0])[i];
}
__device__ __forceinline__ uint32_t piece_offset(uint32_t which, uint32_t s, uint32_t mt, uint32_t lane) {
    const uint32_t r8 = lane >> 2;
    return which * kWBytes + wimg_offset(which ? 32 * (mt >> 1) + 8 * (r8 >> 1) + 4 * (mt & 1) + (r8 & 1) : 16 * mt + r8, s, lane & 3);
}
__device__ __forceinline__ void piece_store(Scratch* g, uint32_t par, uint32_t off0, uint32_t which, const float (&d)[2][4]) {
#pragma unroll
    for (int hf = 0; hf < 2; hf++) {
        const uint32_t off = off0 ^ (hf ? which ? 288 : 1024 : 0);
        const uint32_t a = pack_bf16(d[0][2 * hf], d[0][2 * hf + 1]), b = pack_bf16(d[1][2 * hf], d[1][2 * hf + 1]);
        asm volatile("st.relaxed.gpu.global.v2.u32 [%0], {%1, %2};" ::"l"(g->img[0][0] + (par + off)), "r"(a ? a : 0x8000u), "r"(b) : "memory");
    }
}
__device__ __forceinline__ void piece_clear(Scratch* g, uint32_t par, uint32_t off0, uint32_t which) {
#pragma unroll
    for (int hf = 0; hf < 2; hf++)
        asm volatile("st.relaxed.gpu.global.v2.u32 [%0], {%1, %1};" ::"l"(g->img[0][0] + (par + (off0 ^ (hf ? which ? 288 : 1024 : 0)))), "r"(0) : "memory");
}

__device__ __forceinline__ uint32_t ld_relaxed(const uint32_t* p) {
    uint32_t v;
    asm volatile("ld.relaxed.gpu.global.u32 %0, [%1];" : "=r"(v) : "l"(p) : "memory");
    return v;
}
__device__ __forceinline__ void count_up(uint32_t* p) {
    asm volatile("red.relaxed.gpu.global.add.u32 [%0], %1;" ::"l"(p), "r"(1) : "memory");
}
__device__ __forceinline__ void bulk_g2s(uint32_t dst, const void* src, uint32_t bytes, uint32_t bar) {
    asm volatile("cp.async.bulk.shared::cluster.global.mbarrier::complete_tx::bytes [%0], [%1], %2, [%3];"
                 ::"r"(dst), "l"(src), "r"(bytes), "r"(bar)
                 : "memory");
}

__global__ void __launch_bounds__(kThreads, 1)
nat_fused_kernel(const uint8_t* __restrict__ x, const uint8_t* __restrict__ wqkv, uint8_t* __restrict__ out, Scratch* g,
                 const uint8_t* wo, uint64_t dsc, const __grid_constant__ Maps maps) {
    const int tid = threadIdx.x, lane = tid & 31;
    const int warp = __shfl_sync(0xffffffffu, tid >> 5, 0);
    const int wg = warp >> 2, wq = warp & 3, r8 = lane >> 2, j = lane & 3;
    const int cta = blockIdx.x;
    const Work w = decode_work(cta);
    const uint32_t jq = (cta < 124 ? cta + 8 : cta - 124) / 11u, jr = (cta < 124 ? cta + 8 : cta - 124) - 11 * jq;
    const uint32_t which = jr >= 6, jhi = which ? jr - 6 : jq, jlo = which ? jq : 2 * jr;
    const bool has_job = jr < 10;
    if (wg == 2 && wq < 3) {
#pragma unroll
        for (int r = 0; r < 3; r++)
            asm volatile("st.shared.v4.u32 [%0], {%1, %1, %1, %1};" ::"r"(s_ring + wq * kRingChunk + (r == 0 ? 84 : r == 1 ? 88 : 204) * 128 + lane * 16), "r"(0) : "memory");
        asm volatile("fence.proxy.async.shared::cta;" ::: "memory");
    }
    MOperands mo;
    uint32_t launch = 0;
    if (wg == 1 && wq < 3 && !which) m_load(mo, wqkv, jhi, jlo, wq, lane);
    if (warp == 7) launch = ld_relaxed(g->launches[cta]);
    if (x == nullptr) return;
    const uint32_t t_start = clock_now();
    if (wg == 2) {
        asm volatile("setmaxnreg.dec.sync.aligned.u32 24;");
        if (wq < 3) {
            if (lane < 3 && cta < 128) {
                const uint32_t row = 3 * (cta >> 1) + wq;
                asm volatile("prefetch.global.L2 [%0];" ::"l"((cta & 1 ? wo + row * 384 : wqkv + row * 1152 + 768) + lane * 128));
            }
            asm volatile("bar.sync 7, 192;" ::: "memory");
            const uint32_t par = lds_volatile(s_par);
            uint32_t phase = 0;
#pragma unroll 1
            for (uint32_t c = 0; c < 6; c++) {
                const uint32_t part = c * kWChunk + wq * (kWChunk / 3);
                mbar_wait(bar_img + 8 * c, 0);
                if (c == 0 && lane == 0) mbar_arrive(bar_ok);
                if (wq == 0) TRW(10 + c);
#pragma unroll 1
                while (true) {
                    uint32_t lo = ~0u;
#pragma unroll
                    for (int q = 0; q < 8; q++) lo = min(lo, lds_volatile(s_m + part + lane * 32 + (lane & 12) * 2 + q * 1024));
                    if (__all_sync(0xffffffffu, lo) || phase > 65535) break;
                    if (elect()) {
                        mbar_expect_tx(bar_redo + 8 * wq, kWChunk / 3);
                        bulk_g2s(s_m + part, g->img[0][0] + par + part, kWChunk / 3, bar_redo + 8 * wq);
                    }
                    mbar_wait(bar_redo + 8 * wq, phase++ & 1);
                }
                if (c == 2 && phase) asm volatile("st.shared.u32 [%0], %1;" ::"r"(s_again), "r"(1) : "memory");
                if (c >= 2 && lane == 0) mbar_arrive(bar_ok + 8 * c - 8);
            }
        } else {
            const CUtensorMap* map = &maps.m[w.sv == kPixBytes ? 2 : 0];
            if (elect()) {
#pragma unroll
                for (int i = 0; i < 26; i++) mbar_init(s_bar + 8 * i, i < 15 ? 1 : i < 20 ? 3 : 4);
                asm volatile("fence.mbarrier_init.release.cluster;" ::: "memory");
                prefetch_map(map + 1);
                expect_tx_only(bar_a, sizeof(Table));
                bulk_g2s(s_tab, &maps.tables->t[w.step < 0], sizeof(Table), bar_a);
            }
            if (which && has_job && elect()) {
                mbar_expect_tx(bar_wop, 4 * 6144);
                tma_3d(s_wv, &maps.wo, bar_wop, 0, jhi);
                tma_3d(s_wv + 3 * 6144, &maps.wv, bar_wop, 16 * jlo, 6);
            }
            int u = w.u, v = w.v;
            uint32_t wait_bar = bar_use, wait_par = 1, slot = 0;
#pragma unroll 1
            for (int step = 0; step < 7 - w.corner; step++) {
                const bool first = step == 0 || (w.corner && step == 4);
                const int ou = origin_u(u);
                const bool final = step == 6 - w.corner;
                if (final) { wait_bar = bar_free; wait_par = 0; }
#pragma unroll 1
                for (uint32_t bar = first ? bar_a : bar_b; bar <= (first ? bar_a : bar_mid); bar += 8) {
                    mbar_wait(bar, first ? !step : slot != 0);
                    if (elect()) mbar_expect_tx(bar, first ? 3 * kSlotBytes : bar < bar_mid ? kSlotBytes : 3 * kMidBytes);
                }
                int row = v + 4 + (first ? -w.step : w.step) / 2;
                uint32_t dst = final ? s_m : s_ring + (first ? 0 : slot), bar = first ? bar_a : bar_b, dbar = first ? 0 : 8;
#pragma unroll 1
                for (int r = 0; r < 2 - first; r++) {
                    mbar_wait(wait_bar, wait_par);
                    if (r == 0) TRW(24 + step);
#pragma unroll
                    for (int n = 0; n < 3; n++) {
                        if (n && final) mbar_wait(bar_free + 8 * n, 0);
                        if (elect()) tma_box(dst + n * kRingChunk, map + r, bar + n * dbar, (cta & 1) * kC + 64 * n, ou, (cta >> 1) & 1, row);
                    }
                    row = v + 6; bar = bar_mid; dbar = 0;
                    dst = (final ? s_m : s_ring) + kOffMid + 512;
                    if (wait_bar == bar_use) wait_bar = bar_use + 16;
                }
                TRW(32 + 8 * step + 4);
                if (step == 0) {
                    asm volatile("st.shared.v2.u32 [%0], {%1, %1};" ::"r"(s_late), "r"(0) : "memory");
                    asm volatile("bar.arrive 3, 160;\nbar.arrive 4, 160;\nbar.arrive 8, 128;\nbar.sync 9, 64;" ::: "memory");
                }
                if (step < 2) {
                    if (step) {
                        asm volatile("bar.sync 6, 128;" ::: "memory");
                    }
                    const uint32_t par = __shfl_sync(0xffffffffu, lds_volatile(s_par), 0);
                    wait_until(t_start, step ? TN(5, kTimeW) : TN(6, kTimeM));
                    TRW(5 + 4 * step);
#pragma unroll 1
                    for (int c = 3 * step; c < 3 + 3 * step; c++)
                        if (elect()) {
                            mbar_expect_tx(bar_img + 8 * c, kWChunk);
                            bulk_g2s(s_m + c * kWChunk, g->img[0][0] + (par + c * kWChunk), kWChunk, bar_img + 8 * c);
                        }
                }
                const bool again = w.corner && step == 3;
                wait_bar = step == 0 ? bar_img + 8 * TN(1, 1) : again ? bar_use + 8 : bar_use;
                if (!again) {
                    wait_par = slot ? 0 : step != 0;
                    slot ^= kSlotStride;
                    if (w.corner && step == 2) { u += 8; v -= 8; } else if (step) v += w.step;
                }
            }
        }
        TRDUMP();
        return;
    }
    if (warp == 7) {
        asm volatile("st.shared.u32 [%0], %1;\nbar.arrive 9, 64;" ::"r"(s_par), "r"((launch & 1) * 2 * kWBytes) : "memory");
        g->launches[cta][lane] = launch + 1;
        asm volatile("bar.arrive 5, 128;" ::: "memory");
    }
    if (wg == 1 && wq < 3) {
        if (!which) m_partial(mo, wq, lane, (uint32_t)dsc & 1);
        const uint32_t off = piece_offset(which, which ? jlo : jlo + wq, which ? 3 * jhi + wq : jhi, lane);
        asm volatile("bar.sync %0, %1;" ::"r"(5 + (off >> 31)), "n"(128) : "memory");
        const uint32_t par = lds_volatile(s_par);
        if (which) asm volatile("bar.sync 8, 128;" ::: "memory");
        if (has_job && wq < 2 + which) {
            float d[2][4];
            if (wq == 0) TRX(which ? 1 : 18);
            if (which) {
                mbar_wait(bar_wop, 0);
                if (wq == 0) TRX(2);
                w_piece(wq, lane, d);
            } else {
                m_reduce(wq, lane, d);
            }
            piece_store(g, par, off, which, d);
            __syncwarp();
            piece_clear(g, 2 * kWBytes - par, off, which);
            if (wq == 0) TRX(which ? 3 : 0);
        }
        if (!which) asm volatile("bar.sync 8, 128;" ::: "memory");
        asm volatile("bar.arrive 7, 192;\nbar.arrive 6, 128;" ::: "memory");
    }
    const int order = w.step < 0 ? warp ^ 3 : warp;
    int tu = w.u, tv = w.v + w.step * wg;
    const int du2 = w.corner ? 8 : 0, dv2 = w.corner ? 0 : 2 * w.step;
    uint32_t o0, o1;
    wait_until(t_start, START_TIME);
    asm volatile("setmaxnreg.inc.sync.aligned.u32 240;");
    w.pixel_offsets(tu + r8, tv + 2 * wq, j, o0, o1);
    uint32_t fa[48];
    {
        RawX raw;
        load_raw(raw, x, o0, o1);
        asm volatile("bar.sync %0, 160;" ::"r"(3 + wg) : "memory");
        raw_to_frags(raw, 0, fa);
        pin(fa);
    }
    mbar_wait(bar_ok, 0);
    const uint64_t dA = dsc + wg * (kSlotStride >> 4), dB = dsc + (wg ^ 1) * (kSlotStride >> 4);

    float acc[96];
    uint32_t po[48];
    uint32_t c0 = 0, c1 = 0;
#pragma unroll
    for (int q = 0; q < 48; q++) asm volatile("" : "=r"(po[q]));
#pragma unroll 1
    for (int i = wg; i < w.ntiles; i += 2) {
        const bool first = i == 0, last = i == w.ntiles - 1;

        TRF(8 + 16 * k);
        uint8_t *p0 = out + c0, *p1 = out + c1;
#pragma unroll 1
        for (uint32_t seen = 0;;) {
        wg_fence();
        if (!first) turn_wait(wg);
        proj_gemm(acc, fa, dsc, s_m, [&](int s) {
            if (s == 11 && !first) turn_pass(wg);
            const int n = __builtin_popcount(QSLOTS & ((1 << s) - 1));
            if (((QSLOTS >> s) & 1) && n < 12) store_one(i >= 2, out + c0, out + c1, po, n);
            if (s == 3 || s == 7) { wg_commit(); mbar_wait(bar_img + 2 * s + 2, 0); wg_fence(); }
        });
        __syncwarp();
        TRF(9 + 16 * k);
            if (!first) break;
            mbar_wait(bar_ok + 8, 0);
            if (lds_volatile(s_again) == seen) break;
            wg_wait<0>();
            seen = 1;
        }
        c0 = o0; c1 = o1;
        w.pixel_offsets(tu + du2 + r8, tv + dv2 + 2 * wq, j, o0, o1);
        if (i + 2 >= w.ntiles) o0 = o1 = 0;
        mbar_wait(bar_a, w.corner ? i >> 1 : 0);
        wg_wait<2>();
        if (last && lane == 0) mbar_arrive(bar_free);
        wg_wait<1>();
        if (last && lane == 0) mbar_arrive(bar_free + 8);
#pragma unroll
        for (int s = 12; s < 14; s++)
            if ((QSLOTS >> s) & 1) { store_one(i >= 2, p0, p1, po, __builtin_popcount(QSLOTS & ((1 << s) - 1))); __syncwarp(); }
        wg_wait<0>();
        if (last && lane == 0) mbar_arrive(bar_free + 16);
        const uint64_t dE = last ? dsc + ((s_m - s_ring) >> 4) : dsc, dN = last ? dE : dB;
        pin(acc);
        TR(11 + 16 * k);
        TRT(80 + k);
#pragma unroll
        for (int n = __builtin_popcount(QSLOTS); n < 12 - __builtin_popcount(ASLOTS) - __builtin_popcount(BSLOTS); n++) store_one(i >= 2, p0, p1, po, n);
        acc_to_frags(acc, fa);
        pin(fa);

        float sA[44], sE[16], sB[44];
        RawX nxt;
        if (!first) turn_wait(wg);
        wg_fence();
#pragma unroll
        for (int s = 0; s < 12; s++) {
            if (s == 0) wgmma_n88<true>(sA, fa[4 * s], fa[4 * s + 1], fa[4 * s + 2], fa[4 * s + 3], desc_at(dA, (s >> 2) * kRingChunk + (s & 3) * 32));
            else wgmma_n88<false>(sA, fa[4 * s], fa[4 * s + 1], fa[4 * s + 2], fa[4 * s + 3], desc_at(dA, (s >> 2) * kRingChunk + (s & 3) * 32));
            if (s == 11) { wg_commit(); if (!first) turn_pass(wg); }
            if ((ASLOTS >> s) & 1) store_one(i >= 2, p0, p1, po, 12 - __builtin_popcount(BSLOTS) - __builtin_popcount(ASLOTS >> s));
        }
#pragma unroll
        for (int s = 12; s < 16; s++)
            if ((ASLOTS >> s) & 1) store_one(i >= 2, p0, p1, po, 12 - __builtin_popcount(BSLOTS) - __builtin_popcount(ASLOTS >> s));
        TRF(12 + 16 * k);
        const int vq = tv + 2 * wq;
        const uint4 tabu = lds128(s_tab + offsetof(Table, u) + (window_start(tu + r8) - origin_u(tu)) * 64 + j * 16);
        const uint4 tabv = lds128(s_tab + offsetof(Table, v) + (window_start(vq) + window_start(vq + 1) - 2 * tv) * 64 + j * 16);
        const uint4 route = lds128(s_tab + lane * 16);
        load_raw(nxt, x, o0, o1);
        float v0[14], v1[14];
#pragma unroll
        for (int b = 0; b < 14; b++) {
            v0[b] = __uint_as_float((route.x >> (b + 6)) + 0xff800000u);
            v1[b] = __uint_as_float((route.y >> (b + 6)) + 0xff800000u);
        }
        const uint32_t m0 = tabu.x | tabv.z, m1 = tabu.y | tabv.w;
        if (!first) turn_wait(wg);
#pragma unroll
        for (int c = 0; c < 3; c++) {
            mbar_wait(bar_b + 8 * c, wg);
            TRF(64 + 4 * k + c);
            wg_fence();
#pragma unroll
            for (int s = 4 * c; s < 4 * c + 4; s++) {
                if (s == 0) wgmma_n88<true>(sB, fa[4 * s], fa[4 * s + 1], fa[4 * s + 2], fa[4 * s + 3], desc_at(dN, c * kRingChunk + (s & 3) * 32));
                else wgmma_n88<false>(sB, fa[4 * s], fa[4 * s + 1], fa[4 * s + 2], fa[4 * s + 3], desc_at(dN, c * kRingChunk + (s & 3) * 32));
                if (s == 3) {
                    wg_commit();
                    wg_wait<1>();
                    pin(sA);
                    gather_outer(sA, tabu.x | tabv.x, tabu.y | tabv.y, v0, v1);
                    pin(v0); pin(v1);
                }
                if ((BSLOTS >> s) & 1) store_one(i >= 2, p0, p1, po, 12 - __builtin_popcount(BSLOTS >> s));
            }
        }
        wg_commit();
        mbar_wait(bar_mid, wg);
        wg_fence();
#pragma unroll
        for (int s = 0; s < 12; s++)
            if (s == 0) wgmma_n32<true>(sE, fa[4 * s], fa[4 * s + 1], fa[4 * s + 2], fa[4 * s + 3], desc_at(dE, kOffMid + (s >> 2) * kRingChunk + (s & 3) * 32));
            else wgmma_n32<false>(sE, fa[4 * s], fa[4 * s + 1], fa[4 * s + 2], fa[4 * s + 3], desc_at(dE, kOffMid + (s >> 2) * kRingChunk + (s & 3) * 32));
        wg_commit();
        turn_pass(wg);
        TRF(13 + 16 * k);
        wg_wait<1>();
        pin(sB);
        gather_outer(sB, m0, m1, v0, v1);
        wg_wait<0>();
        pin(sE);
        TRF(14 + 16 * k);
        gather_mid(sE, m1, v0, v1);
        const float mx0 = quad_max(tree_max(v0)), mx1 = quad_max(tree_max(v1));

        uint32_t y[14], pa[12], pb[12];
        exp_route<0, 14>(v0, v1, mx0, mx1, route, (j & 1) == 0, y);
        float s0 = tree_sum(v0), s1 = tree_sum(v1);
        asm volatile("" : "+f"(s0), "+f"(s1));
        unfold<16, 0, 6>(y, tabv.y, pa);
        turn_wait(wg + (y[0] >> 31));
        TRF(15 + 16 * k + (y[13] >> 31));
        wg_fence();
        wgmma_sp_n192_tb<true, 0>(acc, pa[0], pa[1], pa[2], pa[3], desc_at(dA, kToV), tabu.z);
        wgmma_sp_n192_tb<false, 1>(acc, pa[4], pa[5], pa[6], pa[7], desc_at(dA, kToV + 4096), tabu.z);
        wgmma_sp_n192_tb<false, 0>(acc, pa[8], pa[9], pa[10], pa[11], desc_at(dA, kToV + 8192), tabu.w);
        wg_commit();
        wgmma_sp_n192_tb<false, 1>(acc, j == 0 ? 0u : y[10], j == 0 ? 0u : y[11], y[12], y[13], desc_at(dE, kToV + kOffMid), tabu.w);
        wg_commit();
        unfold<24, 0, 6>(y, tabv.y, pb);
        wg_fence();
        wgmma_sp_n192_tb<false, 0>(acc, pb[0], pb[1], pb[2], pb[3], desc_at(dN, kToV), tabu.z);
        wgmma_sp_n192_tb<false, 1>(acc, pb[4], pb[5], pb[6], pb[7], desc_at(dN, kToV + 4096), tabu.z);
        wgmma_sp_n192_tb<false, 0>(acc, pb[8], pb[9], pb[10], pb[11], desc_at(dN, kToV + 8192), tabu.w);
        wg_commit();
        if (!last) turn_pass(wg);
        TRF(16 + 16 * k);
        wg_wait<2>();
        if (lane == 0) mbar_arrive(bar_use);
        wg_wait<1>();
        if (lane == 0) mbar_arrive(bar_use + 16);
        TRF(17 + 16 * k);
        mbar_wait(bar_ok + 16, 0);
        wg_wait<0>();
        if (lane == 0) mbar_arrive(bar_use + 8);
        pin(acc);
        TR(18 + 16 * k);

        acc_to_frags(acc, po);
        pin(po);
        if (last) {
            const float inv0 = rcp(quad_sum(s0)), inv1 = rcp(quad_sum(s1));
            float t0[32], t1[32], t2[32];
            uint32_t pq[48];
            wg_fence();
            third_gemm<0>(t0, po, dsc, [](int) {});
            third_gemm<1>(t1, po, dsc, [&](int s) { if (s == 3) { keep(wqkv == nullptr, __float_as_uint(inv0), __float_as_uint(inv1), c0, c1); __syncwarp(); } });
            wg_wait<1>();
            third_pack<0>(t0, inv0, inv1, pq);
            store_one<false>(true, out + c0, out + c1, pq, 0);
            __syncwarp();
            third_gemm<2>(t2, po, dsc, [&](int s) { if (s == 3 || s == 7 || s == 9) store_one(true, out + c0, out + c1, pq, (s + 3) >> 2); });
            __syncwarp();
            wg_wait<1>();
            third_pack<1>(t1, inv0, inv1, pq);
#pragma unroll
            for (int n = 4; n < 8; n++) store_one<false>(true, out + c0, out + c1, pq, n);
            __syncwarp();
            wg_wait<0>();
            third_pack<2>(t2, inv0, inv1, pq);
#pragma unroll
            for (int n = 8; n < 12; n++) store_one<false>(true, out + c0, out + c1, pq, n);
            break;
        }
        turn_wait(wg);
        wg_fence();
        proj_gemm(acc, po, dsc, s_wv, [&](int s) {
            if (s == 3 || s == 7) { mbar_wait(bar_ok + 2 * s + 18, 0); wg_fence(); }
            if (s + 1 == OSPLIT && i + 2 == w.ntiles) { turn_pass(wg); turn_wait(wg); }
        });
        turn_pass(wg);
        TRF(19 + 16 * k);
        const uint32_t zero = lds_volatile(s_late);
        const float inv0 = rcp(quad_sum(s0 + __uint_as_float(zero))), inv1 = rcp(quad_sum(s1 + __uint_as_float(zero)));
        raw_to_frags(nxt, zero, fa);
        pin(fa);
#pragma unroll
        for (int q = 0; q < 48; q += 4) keep(wqkv == nullptr, fa[q], fa[q + 1], fa[q + 2], fa[q + 3]);
        keep(wqkv == nullptr, __float_as_uint(inv0), __float_as_uint(inv1), zero, lane);
        TRF(20 + 16 * k);
        tu += du2; tv += dv2;
        wg_wait<0>();
        pin(acc);
        TR(21 + 16 * k);
#pragma unroll
        for (int q = 0; q < 96; q++) acc[q] *= q & 2 ? inv1 : inv0;
        pack_out(acc, po);
#pragma unroll
        for (int n = 0; n < INL; n++) store_one<false>(i + 2 == w.ntiles, out + c0, out + c1, po, n);
        pin(po);
    }
    if (wg == 0) {
#pragma unroll
        for (int n = INL; n < 12; n++) {
            __nanosleep(NAP);
            store_one<false>(true, out + c0, out + c1, po, n);
        }
    }
    TRE(7);
    TRG(1);
    TRDUMP();
}

typedef CUresult (*EncodeTiledFn)(CUtensorMap*, CUtensorMapDataType, cuuint32_t, void*, const cuuint64_t*, const cuuint64_t*,
                                  const cuuint32_t*, const cuuint32_t*, CUtensorMapInterleave, CUtensorMapSwizzle,
                                  CUtensorMapL2promotion, CUtensorMapFloatOOBfill);

bool make_maps(EncodeTiledFn fn, Maps* maps, void* x, void* wqkv, void* wo) {
    const cuuint64_t pix2 = 2 * kPixBytes, row = (cuuint64_t)kHW * kPixBytes;
    const cuuint32_t estr[5] = {1, 1, 1, 1, 1};
    bool ok = true;
    for (int tr = 0; tr < 2; tr++)
        for (int b = 0; b < 2; b++) {
            const cuuint64_t su = tr ? 2 * row : pix2, sv = tr ? pix2 : 2 * row;
            const cuuint64_t dims[5] = {2 * kC, 2, 105, 2, 112};
            const cuuint64_t strides[4] = {7 * su, su, row, sv};
            const cuuint32_t box[5] = {64, 2, 7, 1, b ? 2u : 6u};
            ok = ok && fn(&maps->m[2 * tr + b], CU_TENSOR_MAP_DATA_TYPE_BFLOAT16, 5, x, dims, strides, box, estr,
                          CU_TENSOR_MAP_INTERLEAVE_NONE, CU_TENSOR_MAP_SWIZZLE_128B, CU_TENSOR_MAP_L2_PROMOTION_L2_128B,
                          CU_TENSOR_MAP_FLOAT_OOB_FILL_NONE) == CUDA_SUCCESS;
        }
    for (int b = 0; b < 2; b++) {
        const cuuint64_t dims[3] = {b ? 64u : 48u, kC, b ? 9u : 4u}, strides[2] = {(b ? 3u : 1u) * kPixBytes, b ? 128u : 96u};
        const cuuint32_t box[3] = {b ? 64u : 48u, b ? 16u : 192u, b ? 3u : 1u};
        ok = ok && fn(b ? &maps->wv : &maps->wo, CU_TENSOR_MAP_DATA_TYPE_BFLOAT16, 3, b ? wqkv : wo, dims, strides, box, estr,
                      CU_TENSOR_MAP_INTERLEAVE_NONE, b ? CU_TENSOR_MAP_SWIZZLE_128B : CU_TENSOR_MAP_SWIZZLE_NONE, CU_TENSOR_MAP_L2_PROMOTION_L2_128B,
                      CU_TENSOR_MAP_FLOAT_OOB_FILL_NONE) == CUDA_SUCCESS;
    }
    return ok;
}

}

extern "C" void kernel_launch(void* const* d_in, const int* in_sizes, int n_in, void* d_out, int out_size) {
    static EncodeTiledFn encode = nullptr;
    static Scratch* scratch = nullptr;
    static Tables* tables = nullptr;
    if (!encode) {
        int dev = 0, reserved = 0;
        cudaFuncAttributes attr;
        cudaGetDevice(&dev);
        cudaDeviceGetAttribute(&reserved, cudaDevAttrReservedSharedMemoryPerBlock, dev);
        cudaFuncGetAttributes(&attr, nat_fused_kernel);
        if (reserved != (int)kSmemBase || attr.sharedSizeBytes != 0) return;
        cudaGetSymbolAddress((void**)&scratch, g_scratch);
        cudaGetSymbolAddress((void**)&tables, g_tables);
        void* fn = nullptr;
        cudaDriverEntryPointQueryResult st;
        cudaGetDriverEntryPoint("cuTensorMapEncodeTiled", &fn, cudaEnableDefault, &st);
        encode = (EncodeTiledFn)fn;
        cudaFuncSetAttribute(nat_fused_kernel, cudaFuncAttributeMaxDynamicSharedMemorySize, kSmemBytes);
    }
    Maps maps;
    maps.tables = tables;
    if (!encode || !make_maps(encode, &maps, d_in[0], d_in[1], d_in[2])) return;
    nat_fused_kernel<<<kGrid, kThreads, kSmemBytes>>>((const uint8_t*)d_in[0], (const uint8_t*)d_in[1], (uint8_t*)d_out, scratch, (const uint8_t*)d_in[2],
                                                      kDescRing, maps);
}
```

```cpp
#include <cuda_runtime.h>
#include <cuda_bf16.h>
#include <cuda.h>
#include <stdint.h>
#include <type_traits>
#include <stdlib.h>
#include <stdio.h>
#include <stddef.h>

#define QSLOTS 0x16fae
#define OSPLIT 2
#define INL 2
#define NAP 50

namespace {

constexpr int kC          = 192;
constexpr int kHW         = 224;
constexpr int kPixBytes   = kC * 2;
constexpr int kSlotBytes  = 84 * 128;
constexpr int kMidBytes   = 28 * 128;
constexpr int kOffMid     = 88 * 128;
constexpr int kSlotStride = 120 * 128;
constexpr int kRingChunk  = 208 * 128;
constexpr int kWChunk     = 192 * 128;
constexpr int kWBytes     = 3 * kWChunk;
constexpr uint32_t kSmemBase = 1024;
constexpr uint32_t s_ring = kSmemBase, s_m = s_ring + 3 * kRingChunk, s_wv = s_m + kWBytes, s_bar = s_wv + kWBytes;
constexpr uint32_t bar_b = s_bar, bar_mid = s_bar + 24, bar_a = s_bar + 32, bar_img = s_bar + 40, bar_redo = s_bar + 88,
                   bar_wop = s_bar + 112, bar_ok = s_bar + 120, bar_use = s_bar + 160, bar_free = s_bar + 184;
constexpr uint32_t s_par = s_bar + 208, s_late = s_bar + 216, s_again = s_bar + 220, s_tab = s_bar + 256, s_trace = s_tab + 2048;
constexpr int kSmemBytes  = s_trace + 2048 - kSmemBase;
constexpr int kThreads    = 384;
constexpr int kGrid       = 132;
constexpr int kTimeM = 2500, kTimeW = 5100;
constexpr float kScaleLog2e = 0.07216878364870322f * 1.4426950408889634f;

struct Maps {
    CUtensorMap m[4];
    CUtensorMap wo, wv;
    const struct Tables* tables;
};
#define TN(i, dflt) (dflt)
#define START_TIME (wg ? 900 + 450 * order : 250 + 560 * order)

struct Scratch {
    uint8_t img[2][2][kWBytes];
    uint32_t launches[kGrid][32];
};
__device__ __align__(1024) Scratch g_scratch;

__host__ __device__ constexpr int entry_bit(int k) { return 8 * ((k >> 1) & 3) + 3 * (k & 1); }
struct Table {
    uint32_t route[32][4];
    uint32_t u[8][4][4];
    uint32_t v[16][4][4];
};
struct Tables { Table t[2]; };
constexpr Tables make_tables() {
    Tables r = {};
    for (int rev = 0; rev < 2; rev++)
        for (int j = 0; j < 4; j++) {
            Table& t = r.t[rev];
            for (int q = 0; q < 8; q++) {
                uint32_t* e = t.route[4 * q + j];
                e[0] = 4 * q + 2 * (j & 1) + (j >> 1); e[1] = e[0] ^ 1;
                e[2] = j < 2 ? 0x5410u : 0x1054u; e[3] = e[2] + 0x2222u;
                e = t.u[q][j];
                for (int k = 0; k < 16; k++) e[k >> 3] |= ((4 * (k < 12 ? k : k - 2) + j) % 7 < q ? 1u : 0u) << entry_bit(k);
                for (int k = 0; k < 2; k++) {
                    const int step = 2 * k + (j >> 1), p0 = (step < 3 ? 16 * step : 40) + 8 * (j & 1);
                    uint32_t m = 0x8888u;
                    for (int n = 0; n < 8; n++) m |= ((p0 + n) % 7 < q ? 1u : 0u) << (2 * n);
                    e[2 + k] = m * 0x10001u;
                }
            }
            for (int sum = 0; sum < 15; sum++) {
                uint32_t* e = t.v[sum][j];
                for (int row = 0; row < 2; row++)
                    for (int b = 0; b < 14; b++) {
                        const int off = (sum + row) / 2, p = 4 * b + j;
                        if (p < 42 && p >= 7 * off) e[2 * rev + (b >> 3)] |= 2u << (entry_bit(b) + row);
                        if (p < 7 * off - 7) e[2 - 2 * rev + (b >> 3)] |= 2u << (entry_bit(b) + row);
                        if (p >= 42 && p >= 7 * off && p < 7 * off + 49) e[3] |= 2u << (entry_bit(b + 2) + row);
                    }
                for (int n = 0; n < 6; n++)
                    if (8 * n + 2 * j < 42) e[1] |= 0x10000u << (n + ((8 * n + 2 * j >= 7 * (sum / 2 & ~1)) != rev ? 0 : 8));
            }
        }
    return r;
}
__device__ __align__(128) const Tables g_tables = make_tables();

#define WO4(i) "=f"(d[i]), "=f"(d[i + 1]), "=f"(d[i + 2]), "=f"(d[i + 3])
#define RW4(i) "+f"(d[i]), "+f"(d[i + 1]), "+f"(d[i + 2]), "+f"(d[i + 3])

template <bool FIRST>
__device__ __forceinline__ void wgmma_n192(float (&d)[96], uint32_t a0, uint32_t a1, uint32_t a2, uint32_t a3, uint64_t descb) {
    if constexpr (FIRST) {
        asm volatile(
            "wgmma.mma_async.sync.aligned.m64n192k16.f32.bf16.bf16 "
            "{%0, %1, %2, %3, %4, %5, %6, %7, %8, %9, %10, %11, %12, %13, %14, %15, %16, %17, %18, %19, %20, %21, %22, %23, "
            "%24, %25, %26, %27, %28, %29, %30, %31, %32, %33, %34, %35, %36, %37, %38, %39, %40, %41, %42, %43, %44, %45, %46, %47, "
            "%48, %49, %50, %51, %52, %53, %54, %55, %56, %57, %58, %59, %60, %61, %62, %63, %64, %65, %66, %67, %68, %69, %70, %71, "
            "%72, %73, %74, %75, %76, %77, %78, %79, %80, %81, %82, %83, %84, %85, %86, %87, %88, %89, %90, %91, %92, %93, %94, %95}, "
            "{%96, %97, %98, %99}, %100, 0, 1, 1, 0;"
            : WO4(0), WO4(4), WO4(8), WO4(12), WO4(16), WO4(20), WO4(24), WO4(28), WO4(32), WO4(36), WO4(40), WO4(44),
              WO4(48), WO4(52), WO4(56), WO4(60), WO4(64), WO4(68), WO4(72), WO4(76), WO4(80), WO4(84), WO4(88), WO4(92)
            : "r"(a0), "r"(a1), "r"(a2), "r"(a3), "l"(descb));
    } else {
        asm volatile(
            "wgmma.mma_async.sync.aligned.m64n192k16.f32.bf16.bf16 "
            "{%0, %1, %2, %3, %4, %5, %6, %7, %8, %9, %10, %11, %12, %13, %14, %15, %16, %17, %18, %19, %20, %21, %22, %23, "
            "%24, %25, %26, %27, %28, %29, %30, %31, %32, %33, %34, %35, %36, %37, %38, %39, %40, %41, %42, %43, %44, %45, %46, %47, "
            "%48, %49, %50, %51, %52, %53, %54, %55, %56, %57, %58, %59, %60, %61, %62, %63, %64, %65, %66, %67, %68, %69, %70, %71, "
            "%72, %73, %74, %75, %76, %77, %78, %79, %80, %81, %82, %83, %84, %85, %86, %87, %88, %89, %90, %91, %92, %93, %94, %95}, "
            "{%96, %97, %98, %99}, %100, 1, 1, 1, 0;"
            : RW4(0), RW4(4), RW4(8), RW4(12), RW4(16), RW4(20), RW4(24), RW4(28), RW4(32), RW4(36), RW4(40), RW4(44),
              RW4(48), RW4(52), RW4(56), RW4(60), RW4(64), RW4(68), RW4(72), RW4(76), RW4(80), RW4(84), RW4(88), RW4(92)
            : "r"(a0), "r"(a1), "r"(a2), "r"(a3), "l"(descb));
    }
}

template <bool FIRST>
__device__ __forceinline__ void wgmma_n64(float (&d)[32], uint32_t a0, uint32_t a1, uint32_t a2, uint32_t a3, uint64_t descb) {
    if constexpr (FIRST) {
        asm volatile(
            "wgmma.mma_async.sync.aligned.m64n64k16.f32.bf16.bf16 "
            "{%0, %1, %2, %3, %4, %5, %6, %7, %8, %9, %10, %11, %12, %13, %14, %15, %16, %17, %18, %19, %20, %21, %22, %23, "
            "%24, %25, %26, %27, %28, %29, %30, %31}, "
            "{%32, %33, %34, %35}, %36, 0, 1, 1, 0;"
            : WO4(0), WO4(4), WO4(8), WO4(12), WO4(16), WO4(20), WO4(24), WO4(28)
            : "r"(a0), "r"(a1), "r"(a2), "r"(a3), "l"(descb));
    } else {
        asm volatile(
            "wgmma.mma_async.sync.aligned.m64n64k16.f32.bf16.bf16 "
            "{%0, %1, %2, %3, %4, %5, %6, %7, %8, %9, %10, %11, %12, %13, %14, %15, %16, %17, %18, %19, %20, %21, %22, %23, "
            "%24, %25, %26, %27, %28, %29, %30, %31}, "
            "{%32, %33, %34, %35}, %36, 1, 1, 1, 0;"
            : RW4(0), RW4(4), RW4(8), RW4(12), RW4(16), RW4(20), RW4(24), RW4(28)
            : "r"(a0), "r"(a1), "r"(a2), "r"(a3), "l"(descb));
    }
}

template <bool FIRST>
__device__ __forceinline__ void wgmma_n88(float (&d)[44], uint32_t a0, uint32_t a1, uint32_t a2, uint32_t a3, uint64_t descb) {
    if constexpr (FIRST) {
        asm volatile(
            "wgmma.mma_async.sync.aligned.m64n88k16.f32.bf16.bf16 "
            "{%0, %1, %2, %3, %4, %5, %6, %7, %8, %9, %10, %11, %12, %13, %14, %15, %16, %17, %18, %19, %20, %21, %22, %23, "
            "%24, %25, %26, %27, %28, %29, %30, %31, %32, %33, %34, %35, %36, %37, %38, %39, %40, %41, %42, %43}, "
            "{%44, %45, %46, %47}, %48, 0, 1, 1, 0;"
            : WO4(0), WO4(4), WO4(8), WO4(12), WO4(16), WO4(20), WO4(24), WO4(28), WO4(32), WO4(36), WO4(40)
            : "r"(a0), "r"(a1), "r"(a2), "r"(a3), "l"(descb));
    } else {
        asm volatile(
            "wgmma.mma_async.sync.aligned.m64n88k16.f32.bf16.bf16 "
            "{%0, %1, %2, %3, %4, %5, %6, %7, %8, %9, %10, %11, %12, %13, %14, %15, %16, %17, %18, %19, %20, %21, %22, %23, "
            "%24, %25, %26, %27, %28, %29, %30, %31, %32, %33, %34, %35, %36, %37, %38, %39, %40, %41, %42, %43}, "
            "{%44, %45, %46, %47}, %48, 1, 1, 1, 0;"
            : RW4(0), RW4(4), RW4(8), RW4(12), RW4(16), RW4(20), RW4(24), RW4(28), RW4(32), RW4(36), RW4(40)
            : "r"(a0), "r"(a1), "r"(a2), "r"(a3), "l"(descb));
    }
}

template <bool FIRST>
__device__ __forceinline__ void wgmma_n32(float (&d)[16], uint32_t a0, uint32_t a1, uint32_t a2, uint32_t a3, uint64_t descb) {
    if constexpr (FIRST) {
        asm volatile(
            "wgmma.mma_async.sync.aligned.m64n32k16.f32.bf16.bf16 "
            "{%0, %1, %2, %3, %4, %5, %6, %7, %8, %9, %10, %11, %12, %13, %14, %15}, "
            "{%16, %17, %18, %19}, %20, 0, 1, 1, 0;"
            : WO4(0), WO4(4), WO4(8), WO4(12)
            : "r"(a0), "r"(a1), "r"(a2), "r"(a3), "l"(descb));
    } else {
        asm volatile(
            "wgmma.mma_async.sync.aligned.m64n32k16.f32.bf16.bf16 "
            "{%0, %1, %2, %3, %4, %5, %6, %7, %8, %9, %10, %11, %12, %13, %14, %15}, "
            "{%16, %17, %18, %19}, %20, 1, 1, 1, 0;"
            : RW4(0), RW4(4), RW4(8), RW4(12)
            : "r"(a0), "r"(a1), "r"(a2), "r"(a3), "l"(descb));
    }
}

template <bool FIRST, int SEL>
__device__ __forceinline__ void wgmma_sp_n192_tb(float (&d)[96], uint32_t a0, uint32_t a1, uint32_t a2, uint32_t a3, uint64_t descb, uint32_t meta) {
    if constexpr (FIRST) {
        asm volatile(
            "wgmma.mma_async.sp.sync.aligned.m64n192k32.f32.bf16.bf16 "
            "{%0, %1, %2, %3, %4, %5, %6, %7, %8, %9, %10, %11, %12, %13, %14, %15, %16, %17, %18, %19, %20, %21, %22, %23, "
            "%24, %25, %26, %27, %28, %29, %30, %31, %32, %33, %34, %35, %36, %37, %38, %39, %40, %41, %42, %43, %44, %45, %46, %47, "
            "%48, %49, %50, %51, %52, %53, %54, %55, %56, %57, %58, %59, %60, %61, %62, %63, %64, %65, %66, %67, %68, %69, %70, %71, "
            "%72, %73, %74, %75, %76, %77, %78, %79, %80, %81, %82, %83, %84, %85, %86, %87, %88, %89, %90, %91, %92, %93, %94, %95}, "
            "{%96, %97, %98, %99}, %100, %101, %102, 0, 1, 1, 1;"
            : WO4(0), WO4(4), WO4(8), WO4(12), WO4(16), WO4(20), WO4(24), WO4(28), WO4(32), WO4(36), WO4(40), WO4(44),
              WO4(48), WO4(52), WO4(56), WO4(60), WO4(64), WO4(68), WO4(72), WO4(76), WO4(80), WO4(84), WO4(88), WO4(92)
            : "r"(a0), "r"(a1), "r"(a2), "r"(a3), "l"(descb), "r"(meta), "n"(SEL));
    } else {
        asm volatile(
            "wgmma.mma_async.sp.sync.aligned.m64n192k32.f32.bf16.bf16 "
            "{%0, %1, %2, %3, %4, %5, %6, %7, %8, %9, %10, %11, %12, %13, %14, %15, %16, %17, %18, %19, %20, %21, %22, %23, "
            "%24, %25, %26, %27, %28, %29, %30, %31, %32, %33, %34, %35, %36, %37, %38, %39, %40, %41, %42, %43, %44, %45, %46, %47, "
            "%48, %49, %50, %51, %52, %53, %54, %55, %56, %57, %58, %59, %60, %61, %62, %63, %64, %65, %66, %67, %68, %69, %70, %71, "
            "%72, %73, %74, %75, %76, %77, %78, %79, %80, %81, %82, %83, %84, %85, %86, %87, %88, %89, %90, %91, %92, %93, %94, %95}, "
            "{%96, %97, %98, %99}, %100, %101, %102, 1, 1, 1, 1;"
            : RW4(0), RW4(4), RW4(8), RW4(12), RW4(16), RW4(20), RW4(24), RW4(28), RW4(32), RW4(36), RW4(40), RW4(44),
              RW4(48), RW4(52), RW4(56), RW4(60), RW4(64), RW4(68), RW4(72), RW4(76), RW4(80), RW4(84), RW4(88), RW4(92)
            : "r"(a0), "r"(a1), "r"(a2), "r"(a3), "l"(descb), "r"(meta), "n"(SEL));
    }
}

#define TR(slot)
#define TRX(slot)
#define TRE(slot)
#define TRT(slot)
#define TRF(slot)
#define TRW(slot)
#define TRG(slot)
#define TRDUMP()

__device__ __forceinline__ void wg_fence() { asm volatile("wgmma.fence.sync.aligned;" ::: "memory"); }
__device__ __forceinline__ void wg_commit() { asm volatile("wgmma.commit_group.sync.aligned;" ::: "memory"); }
template <int N>
__device__ __forceinline__ void wg_wait() { asm volatile("wgmma.wait_group.sync.aligned %0;" ::"n"(N) : "memory"); }

template <int N>
__device__ __forceinline__ void pin(float (&d)[N]) {
#pragma unroll
    for (int i = 0; i < N; i++) asm volatile("" : "+f"(d[i])::"memory");
}
template <int N>
__device__ __forceinline__ void pin(uint32_t (&d)[N]) {
#pragma unroll
    for (int i = 0; i < N; i++) asm volatile("" : "+r"(d[i])::"memory");
}

constexpr uint64_t kDescRing = ((uint64_t)((1u << 30) | (1024u >> 4)) << 32) | (1u << 16) | (s_ring >> 4);
constexpr uint32_t kToV = ((kRingChunk >> 4) - 1) << 20;
__device__ __forceinline__ uint64_t desc_at(uint64_t base, uint32_t byte_off) {
    uint64_t d;
    asm volatile("add.s64 %0, %1, %2;" : "=l"(d) : "l"(base), "l"((uint64_t)(byte_off >> 4)));
    return d;
}

__device__ __forceinline__ void mbar_init(uint32_t bar, uint32_t count) {
    asm volatile("mbarrier.init.shared::cta.b64 [%0], %1;" ::"r"(bar), "r"(count) : "memory");
}
__device__ __forceinline__ void mbar_expect_tx(uint32_t bar, uint32_t bytes) {
    asm volatile("mbarrier.arrive.expect_tx.shared::cta.b64 _, [%0], %1;" ::"r"(bar), "r"(bytes) : "memory");
}
__device__ __forceinline__ void expect_tx_only(uint32_t bar, uint32_t bytes) {
    asm volatile("mbarrier.expect_tx.relaxed.cta.shared::cta.b64 [%0], %1;" ::"r"(bar), "r"(bytes) : "memory");
}
__device__ __forceinline__ void mbar_arrive(uint32_t bar) {
    asm volatile("mbarrier.arrive.shared::cta.b64 _, [%0];" ::"r"(bar) : "memory");
}
__device__ __forceinline__ void mbar_wait(uint32_t bar, uint32_t parity) {
    asm volatile(
        "{\n.reg .pred p;\n"
        "W: mbarrier.try_wait.parity.shared::cta.b64 p, [%0], %1;\n"
        "@!p bra W;\n}\n"
        ::"r"(bar), "r"(parity) : "memory");
}
__device__ __forceinline__ uint32_t clock_now() {
    uint32_t c;
    asm volatile("mov.u32 %0, %%clock;" : "=r"(c)::"memory");
    return c;
}
__device__ __forceinline__ void wait_until(uint32_t t0, int t) {
    if (t == 0) return;
    while ((int)(clock_now() - t0) < t) {}
}
__device__ __forceinline__ bool elect() {
    uint32_t ok;
    asm volatile("{\n.reg .pred p;\nelect.sync _|p, 0xffffffff;\nselp.u32 %0, 1, 0, p;\n}\n" : "=r"(ok));
    return ok != 0;
}
__device__ __forceinline__ void turn_wait(int wg) { asm volatile("bar.sync %0, 256;" ::"r"(1 + wg) : "memory"); }
__device__ __forceinline__ void turn_pass(int wg) { asm volatile("bar.arrive %0, 256;" ::"r"(2 - wg) : "memory"); }

__device__ __forceinline__ void tma_box(uint32_t dst, const CUtensorMap* map, uint32_t bar, int c0, int c2, int c3, int c4) {
    asm volatile(
        "cp.async.bulk.tensor.5d.shared::cluster.global.mbarrier::complete_tx::bytes [%0], [%1, {%3, %4, %5, %6, %7}], [%2];"
        ::"r"(dst), "l"(map), "r"(bar), "r"(c0), "r"(0), "r"(c2), "r"(c3), "r"(c4)
        : "memory");
}
__device__ __forceinline__ void tma_3d(uint32_t dst, const CUtensorMap* map, uint32_t bar, int c1, int c2) {
    asm volatile("cp.async.bulk.tensor.3d.shared::cluster.global.mbarrier::complete_tx::bytes [%0], [%1, {%3, %4, %5}], [%2];"
                 ::"r"(dst), "l"(map), "r"(bar), "r"(0), "r"(c1), "r"(c2)
                 : "memory");
}
__device__ __forceinline__ void prefetch_map(const CUtensorMap* map) {
    asm volatile("prefetch.tensormap [%0];" ::"l"(map) : "memory");
}
__device__ __forceinline__ uint4 ldg(const void* p) {
    uint4 v;
    asm volatile("ld.global.v4.u32 {%0, %1, %2, %3}, [%4];" : "=r"(v.x), "=r"(v.y), "=r"(v.z), "=r"(v.w) : "l"(p) : "memory");
    return v;
}
__device__ __forceinline__ uint32_t pack_bf16(float lo, float hi) {
    uint32_t r;
    asm("cvt.rn.bf16x2.f32 %0, %1, %2;" : "=r"(r) : "f"(hi), "f"(lo));
    return r;
}
__device__ __forceinline__ float ex2(float x) {
    float y;
    asm("ex2.approx.ftz.f32 %0, %1;" : "=f"(y) : "f"(x));
    return y;
}
__device__ __forceinline__ float rcp(float x) {
    float y;
    asm("rcp.approx.ftz.f32 %0, %1;" : "=f"(y) : "f"(x));
    return y;
}
__device__ __forceinline__ void mma16816(float (&d)[4], uint32_t a0, uint32_t a1, uint32_t a2, uint32_t a3, uint32_t b0, uint32_t b1) {
    asm volatile("mma.sync.aligned.m16n8k16.row.col.f32.bf16.bf16.f32 {%0, %1, %2, %3}, {%4, %5, %6, %7}, {%8, %9}, {%0, %1, %2, %3};"
                 : "+f"(d[0]), "+f"(d[1]), "+f"(d[2]), "+f"(d[3])
                 : "r"(a0), "r"(a1), "r"(a2), "r"(a3), "r"(b0), "r"(b1));
}
__device__ __forceinline__ uint4 lds128(uint32_t addr) {
    uint4 v;
    asm volatile("ld.volatile.shared.v4.u32 {%0, %1, %2, %3}, [%4];" : "=r"(v.x), "=r"(v.y), "=r"(v.z), "=r"(v.w) : "r"(addr) : "memory");
    return v;
}
__device__ __forceinline__ uint32_t lds_volatile(uint32_t addr) {
    uint32_t v;
    asm volatile("ld.volatile.shared.u32 %0, [%1];" : "=r"(v) : "r"(addr) : "memory");
    return v;
}

__device__ __forceinline__ int window_start(int n) { return min(max(n, 0), 105); }
__device__ __forceinline__ int origin_u(int u) { return min(max(u, 0), 98); }

struct Work {
    int u, v;
    int step;
    uint32_t su, sv;
    uint32_t base;
    bool corner;
    int ntiles;
    __device__ __forceinline__ void pixel_offsets(int qu, int qv, int j, uint32_t& o0, uint32_t& o1) const {
        const uint32_t b = (qu + window_start(qu)) * su + j * 16 + base;
        o0 = b + (qv + window_start(qv)) * sv;
        o1 = b + (qv + 1 + window_start(qv + 1)) * sv;
    }
};

__device__ __forceinline__ Work decode_work(int c) {
    Work w;
    const bool transposed = (c >> 4) == 7;
    const int px = 6 * (c & 1), py = 3 * (c & 2);
    w.corner = c >= 128;
    w.step = 8 - 4 * (c & 4);
    w.u = (c < 112 ? c & ~7 : 96 + (c & 8)) + (transposed ? py : px) - 6;
    w.v = (w.corner ? 96 : 48 - 2 * (c & 4)) + (transposed ? px : py) - 6;
    w.su = transposed ? kHW * kPixBytes : kPixBytes;
    w.sv = transposed ? kPixBytes : kHW * kPixBytes;
    w.base = px * (kPixBytes / 6) + py * (kHW * kPixBytes / 6) + 6 * (kHW + 1) * kPixBytes;
    w.ntiles = w.corner ? 4 : 6;
    return w;
}

struct RawX { uint4 a[6], b[6]; };
__device__ __forceinline__ void load_raw(RawX& r, const uint8_t* base, uint32_t o0, uint32_t o1) {
    __syncwarp();
#pragma unroll
    for (int c = 0; c < 6; c++) { r.a[c] = ldg(base + o0 + c * 64); r.b[c] = ldg(base + o1 + c * 64); }
    __syncwarp();
}
__device__ __forceinline__ void raw_to_frags(const RawX& r, uint32_t zero, uint32_t (&f)[48]) {
#pragma unroll
    for (int c = 0; c < 6; c++) {
        asm volatile("{\n.reg .b32 t, u;\nadd.u32 t, %4, %8;\nadd.u32 u, %5, %8;\nxor.b32 %0, %6, %8;\nxor.b32 %1, %7, %8;\n"
                     "xor.b32 %2, t, %8;\nxor.b32 %3, u, %8;\n}\n"
                     : "=&r"(f[8 * c + 1]), "=&r"(f[8 * c + 3]), "=&r"(f[8 * c + 4]), "=&r"(f[8 * c + 6])
                     : "r"(r.a[c].y), "r"(r.a[c].w), "r"(r.b[c].x), "r"(r.b[c].z), "r"(zero));
        f[8 * c + 0] = r.a[c].x; f[8 * c + 2] = r.a[c].z; f[8 * c + 5] = r.b[c].y; f[8 * c + 7] = r.b[c].w;
    }
}
__device__ __forceinline__ void acc_to_frags(const float (&d)[96], uint32_t (&f)[48]) {
#pragma unroll
    for (int i = 0; i < 48; i++) f[i] = pack_bf16(d[2 * i], d[2 * i + 1]);
}

template <class F>
__device__ __forceinline__ void proj_gemm(float (&d)[96], const uint32_t (&a)[48], uint64_t dsc, uint32_t img, F after) {
#pragma unroll
    for (int s = 0; s < 12; s++) {
        if (s == 0) wgmma_n192<true>(d, a[4 * s], a[4 * s + 1], a[4 * s + 2], a[4 * s + 3], desc_at(dsc, img - s_ring + (s >> 2) * kWChunk + (s & 3) * 32));
        else wgmma_n192<false>(d, a[4 * s], a[4 * s + 1], a[4 * s + 2], a[4 * s + 3], desc_at(dsc, img - s_ring + (s >> 2) * kWChunk + (s & 3) * 32));
        if (s == 11) wg_commit();
        after(s);
    }
}
__device__ __forceinline__ void pack_out(const float (&acc)[96], uint32_t (&po)[48]) {
#pragma unroll
    for (int g = 0; g < 6; g++)
#pragma unroll
        for (int q = 0; q < 4; q++) {
            po[8 * g + q] = pack_bf16(acc[16 * g + 4 * q], acc[16 * g + 4 * q + 1]);
            po[8 * g + 4 + q] = pack_bf16(acc[16 * g + 4 * q + 2], acc[16 * g + 4 * q + 3]);
        }
}
template <bool PINNED = true>
__device__ __forceinline__ void store_one(bool on, uint8_t* p0, uint8_t* p1, const uint32_t (&po)[48], int n) {
    if (PINNED) __syncwarp();
    asm volatile("{\n.reg .pred p;\nsetp.ne.u32 p, %5, 0;\n@p st.global.v4.u32 [%0], {%1, %2, %3, %4};\n}\n"
                 ::"l"(((n & 1) ? p1 : p0) + (n >> 1) * 64), "r"(po[4 * n]), "r"(po[4 * n + 1]), "r"(po[4 * n + 2]), "r"(po[4 * n + 3]), "r"((uint32_t)on) : "memory");
}

template <int N>
__device__ __forceinline__ float tree_max(const float (&v)[N]) {
    float t[N];
#pragma unroll
    for (int i = 0; i < N; i++) t[i] = v[i];
#pragma unroll
    for (int w = 1; w < N; w *= 2)
#pragma unroll
        for (int i = 0; i + w < N; i += 2 * w) t[i] = fmaxf(t[i], t[i + w]);
    return t[0];
}
template <int N>
__device__ __forceinline__ float tree_sum(const float (&v)[N]) {
    float t[N];
#pragma unroll
    for (int i = 0; i < N; i++) t[i] = v[i];
#pragma unroll
    for (int w = 1; w < N; w *= 2)
#pragma unroll
        for (int i = 0; i + w < N; i += 2 * w) t[i] += t[i + w];
    return t[0];
}

template <int T, class F>
__device__ __forceinline__ void third_gemm(float (&d)[32], const uint32_t (&a)[48], uint64_t dsc, F after) {
#pragma unroll
    for (int s = 0; s < 12; s++) {
        if (s == 0) wgmma_n64<true>(d, a[4 * s], a[4 * s + 1], a[4 * s + 2], a[4 * s + 3], desc_at(dsc, s_wv - s_ring + T * 8192 + (s >> 2) * kWChunk + (s & 3) * 32));
        else wgmma_n64<false>(d, a[4 * s], a[4 * s + 1], a[4 * s + 2], a[4 * s + 3], desc_at(dsc, s_wv - s_ring + T * 8192 + (s >> 2) * kWChunk + (s & 3) * 32));
        if (s == 11) wg_commit();
        after(s);
    }
}
template <int T>
__device__ __forceinline__ void third_pack(float (&d)[32], float i0, float i1, uint32_t (&po)[48]) {
    pin(d);
#pragma unroll
    for (int g = 0; g < 2; g++)
#pragma unroll
        for (int q = 0; q < 4; q++) {
            po[16 * T + 8 * g + q] = pack_bf16(d[16 * g + 4 * q] * i0, d[16 * g + 4 * q + 1] * i0);
            po[16 * T + 8 * g + 4 + q] = pack_bf16(d[16 * g + 4 * q + 2] * i1, d[16 * g + 4 * q + 3] * i1);
        }
}

template <int K>
__device__ __forceinline__ void pick(uint32_t m0, uint32_t m1, const float* s, float& v0, float& v1) {
    asm("{\n.reg .pred p, q0, q1;\n.reg .b32 t;\nand.b32 t, %6, %7;\nsetp.ne.u32 p, t, 0;\n"
        "and.b32 t, %6, %8;\nsetp.ne.u32 q0, t, 0;\nand.b32 t, %6, %9;\nsetp.ne.u32 q1, t, 0;\n"
        "@q0 selp.f32 %0, %3, %2, p;\n@q1 selp.f32 %1, %5, %4, p;\n}\n"
        : "+f"(v0), "+f"(v1)
        : "f"(s[0]), "f"(s[1]), "f"(s[2]), "f"(s[3]), "r"(K < 8 ? m0 : m1), "n"(1 << entry_bit(K)), "n"(2 << entry_bit(K)), "n"(4 << entry_bit(K)));
}
template <int B, class F>
__device__ __forceinline__ void for_blocks(F f) {
    if constexpr (B > 0) { for_blocks<B - 1>(f); f(std::integral_constant<int, B - 1>{}); }
}
__device__ __forceinline__ void gather_outer(const float (&s)[44], uint32_t m0, uint32_t m1, float (&v0)[14], float (&v1)[14]) {
    for_blocks<11>([&](auto B) {
        constexpr int b = B.value;
        pick<b>(m0, m1, &s[4 * b], v0[b], v1[b]);
    });
}
__device__ __forceinline__ void gather_mid(const float (&sE)[16], uint32_t m1, float (&v0)[14], float (&v1)[14]) {
    for_blocks<4>([&](auto B) {
        constexpr int b = B.value;
        pick<12 + b>(0, m1, &sE[4 * b], v0[10 + b], v1[10 + b]);
    });
}
__device__ __forceinline__ float quad_max(float m) {
    m = fmaxf(m, __shfl_xor_sync(0xffffffffu, m, 1));
    return fmaxf(m, __shfl_xor_sync(0xffffffffu, m, 2));
}
__device__ __forceinline__ float quad_sum(float s) {
    s += __shfl_xor_sync(0xffffffffu, s, 1);
    return s + __shfl_xor_sync(0xffffffffu, s, 2);
}
template <int B0, int B1>
__device__ __forceinline__ void exp_route(float (&v0)[14], float (&v1)[14], float m0, float m1, const uint4& r, bool even, uint32_t (&y)[14]) {
#pragma unroll
    for (int b = B0; b < B1; b++) { v0[b] = ex2(v0[b] - m0); v1[b] = ex2(v1[b] - m1); }
#pragma unroll
    for (int b = B0; b < B1; b += 2) {
        const uint32_t x0 = pack_bf16(v0[b], v1[b]), x1 = pack_bf16(v0[b + 1], v1[b + 1]);
        const uint32_t u = __shfl_sync(0xffffffffu, even ? x0 : x1, r.x);
        const uint32_t w = __shfl_sync(0xffffffffu, even ? x1 : x0, r.y);
        y[b] = __byte_perm(u, w, r.z); y[b + 1] = __byte_perm(u, w, r.w);
    }
}
template <int BIT0, int N0, int N1>
__device__ __forceinline__ void unfold(const uint32_t (&y)[14], uint32_t fold, uint32_t (&p)[12]) {
    for_blocks<N1 - N0>([&](auto N) {
        constexpr int n = N0 + N.value;
        asm("{\n.reg .pred p;\n.reg .b32 t;\nand.b32 t, %4, %5;\nsetp.ne.u32 p, t, 0;\nselp.b32 %0, %2, 0, p;\nselp.b32 %1, %3, 0, p;\n}\n"
            : "=r"(p[2 * n]), "=r"(p[2 * n + 1]) : "r"(y[2 * n]), "r"(y[2 * n + 1]), "r"(fold), "n"(1 << (BIT0 + n)));
    });
}
__device__ __forceinline__ void keep(bool never, uint32_t a, uint32_t b, uint32_t c, uint32_t d) {
    asm volatile("{\n.reg .pred p;\nsetp.ne.u32 p, %4, 0;\n@p st.volatile.shared.v4.u32 [%5], {%0, %1, %2, %3};\n}\n"
                 ::"r"(a), "r"(b), "r"(c), "r"(d), "r"((uint32_t)never), "r"(s_trace) : "memory");
}

__device__ __forceinline__ uint32_t wimg_offset(uint32_t row, uint32_t s, uint32_t j) {
    return (s >> 2) * kWChunk + row * 128 + (((2 * (s & 3) + (j >> 1)) ^ (row & 7)) << 4) + (j & 1) * 8;
}

__device__ __forceinline__ void ldsm4(uint32_t (&r)[4], uint32_t addr) {
    asm volatile("ldmatrix.sync.aligned.m8n8.x4.shared.b16 {%0, %1, %2, %3}, [%4];" : "=r"(r[0]), "=r"(r[1]), "=r"(r[2]), "=r"(r[3]) : "r"(addr) : "memory");
}
__device__ __forceinline__ void ldsm4_t(uint32_t (&r)[4], uint32_t addr) {
    asm volatile("ldmatrix.sync.aligned.m8n8.x4.trans.shared.b16 {%0, %1, %2, %3}, [%4];" : "=r"(r[0]), "=r"(r[1]), "=r"(r[2]), "=r"(r[3]) : "r"(addr) : "memory");
}
struct MOperands { uint4 A[2][2], B[4][2]; };
__device__ __forceinline__ void m_load(MOperands& m, const uint8_t* wqkv, uint32_t mt, uint32_t s, uint32_t q, uint32_t lane) {
    const uint32_t r8 = lane >> 2, col = q * 128 + (lane & 3) * 16;
    const uint8_t* pa = wqkv + (16 * mt + r8) * 1152 + col;
    const uint8_t* pb = wqkv + (16 * s + 8 * (r8 & 2) + (r8 & 5)) * 1152 + col;
#pragma unroll
    for (int c = 0; c < 2; c++) {
#pragma unroll
        for (int h = 0; h < 2; h++) m.A[h][c] = ldg(pa + 384 + h * 8 * 1152 + c * 64);
#pragma unroll
        for (int n = 0; n < 4; n++) m.B[n][c] = ldg(pb + ((n & 1) * 8 + (n & 2)) * 1152 + c * 64);
    }
}
__device__ __forceinline__ void m_partial(MOperands& m, uint32_t q, uint32_t lane, uint32_t zero) {
    auto& A = m.A;
    auto& B = m.B;
#pragma unroll
    for (int i = 0; i < 4; i++) { uint4& a = A[i >> 1][i & 1]; a.x ^= zero; a.y ^= zero; a.z ^= zero; a.w ^= zero; }
#pragma unroll
    for (int n = 0; n < 4; n++) {
        float d[4] = {0.f, 0.f, 0.f, 0.f};
#pragma unroll
        for (int c = 0; c < 2; c++) {
            mma16816(d, A[0][c].x, A[1][c].x, A[0][c].y, A[1][c].y, B[n][c].x, B[n][c].y);
            mma16816(d, A[0][c].z, A[1][c].z, A[0][c].w, A[1][c].w, B[n][c].z, B[n][c].w);
        }
        asm volatile("st.shared.v4.f32 [%0], {%1, %2, %3, %4};" ::"r"(s_wv + q * 2048 + n * 512 + lane * 16), "f"(d[0]), "f"(d[1]), "f"(d[2]), "f"(d[3]) : "memory");
    }
}
__device__ __forceinline__ void m_reduce(uint32_t e, uint32_t lane, float (&d)[2][4]) {
#pragma unroll
    for (int n = 0; n < 2; n++) {
        float t[3][4];
#pragma unroll
        for (int q = 0; q < 3; q++)
            asm volatile("ld.shared.v4.f32 {%0, %1, %2, %3}, [%4];" : "=f"(t[q][0]), "=f"(t[q][1]), "=f"(t[q][2]), "=f"(t[q][3]) : "r"(s_wv + q * 2048 + e * 1024 + n * 512 + lane * 16) : "memory");
#pragma unroll
        for (int i = 0; i < 4; i++) d[n][i] = (t[0][i] + t[1][i] + t[2][i]) * kScaleLog2e;
    }
}
__device__ __forceinline__ void w_piece(uint32_t q, uint32_t lane, float (&d)[2][4]) {
    const uint32_t rr = lane & 7, mi = lane >> 3, kr = 4 * (rr >> 1) + (mi & 2) + (rr & 1);
    const uint32_t pa = s_wv + q * 32 + (4 * (mi & 2) + rr) * 96 + ((mi & 1) << 4);
    const uint32_t pb = s_wv + 3 * 6144 + kr * 128 + (((mi & 1) ^ (kr & 7)) << 4);
    float e[2][4];
#pragma unroll
    for (int i = 0; i < 8; i++) (&d[0][0])[i] = (&e[0][0])[i] = 0.f;
#pragma unroll
    for (int k = 0; k < 12; k++) {
        uint32_t aq[4], bq[4];
        ldsm4_t(aq, pa + k * 1536);
        ldsm4(bq, (pb ^ ((k & 3) << 5)) + (k >> 2) * 2048);
        mma16816(k & 1 ? e[0] : d[0], aq[0], aq[1], aq[2], aq[3], bq[0], bq[1]);
        mma16816(k & 1 ? e[1] : d[1], aq[0], aq[1], aq[2], aq[3], bq[2], bq[3]);
    }
#pragma unroll
    for (int i = 0; i < 8; i++) (&d[0][0])[i] += (&e[0][0])[i];
}
__device__ __forceinline__ uint32_t piece_offset(uint32_t which, uint32_t s, uint32_t mt, uint32_t lane) {
    const uint32_t r8 = lane >> 2;
    return which * kWBytes + wimg_offset(which ? 32 * (mt >> 1) + 8 * (r8 >> 1) + 4 * (mt & 1) + (r8 & 1) : 16 * mt + r8, s, lane & 3);
}
__device__ __forceinline__ void piece_store(Scratch* g, uint32_t par, uint32_t off0, uint32_t which, const float (&d)[2][4]) {
#pragma unroll
    for (int hf = 0; hf < 2; hf++) {
        const uint32_t off = off0 ^ (hf ? which ? 288 : 1024 : 0);
        const uint32_t a = pack_bf16(d[0][2 * hf], d[0][2 * hf + 1]), b = pack_bf16(d[1][2 * hf], d[1][2 * hf + 1]);
        asm volatile("st.relaxed.gpu.global.v2.u32 [%0], {%1, %2};" ::"l"(g->img[0][0] + (par + off)), "r"(a ? a : 0x8000u), "r"(b) : "memory");
    }
}
__device__ __forceinline__ void piece_clear(Scratch* g, uint32_t par, uint32_t off0, uint32_t which) {
#pragma unroll
    for (int hf = 0; hf < 2; hf++)
        asm volatile("st.relaxed.gpu.global.v2.u32 [%0], {%1, %1};" ::"l"(g->img[0][0] + (par + (off0 ^ (hf ? which ? 288 : 1024 : 0)))), "r"(0) : "memory");
}

__device__ __forceinline__ uint32_t ld_relaxed(const uint32_t* p) {
    uint32_t v;
    asm volatile("ld.relaxed.gpu.global.u32 %0, [%1];" : "=r"(v) : "l"(p) : "memory");
    return v;
}
__device__ __forceinline__ void count_up(uint32_t* p) {
    asm volatile("red.relaxed.gpu.global.add.u32 [%0], %1;" ::"l"(p), "r"(1) : "memory");
}
__device__ __forceinline__ void bulk_g2s(uint32_t dst, const void* src, uint32_t bytes, uint32_t bar) {
    asm volatile("cp.async.bulk.shared::cluster.global.mbarrier::complete_tx::bytes [%0], [%1], %2, [%3];"
                 ::"r"(dst), "l"(src), "r"(bytes), "r"(bar)
                 : "memory");
}

__global__ void __launch_bounds__(kThreads, 1)
nat_fused_kernel(const uint8_t* __restrict__ x, const uint8_t* __restrict__ wqkv, uint8_t* __restrict__ out, Scratch* g,
                 const uint8_t* wo, uint64_t dsc, const __grid_constant__ Maps maps) {
    const int tid = threadIdx.x, lane = tid & 31;
    const int warp = __shfl_sync(0xffffffffu, tid >> 5, 0);
    const int wg = warp >> 2, wq = warp & 3, r8 = lane >> 2, j = lane & 3;
    const int cta = blockIdx.x;
    const Work w = decode_work(cta);
    const uint32_t jq = (cta < 124 ? cta + 8 : cta - 124) / 11u, jr = (cta < 124 ? cta + 8 : cta - 124) - 11 * jq;
    const uint32_t which = jr >= 6, jhi = which ? jr - 6 : jq, jlo = which ? jq : 2 * jr;
    const bool has_job = jr < 10;
    if (wg == 2 && wq < 3) {
#pragma unroll
        for (int r = 0; r < 3; r++)
            asm volatile("st.shared.v4.u32 [%0], {%1, %1, %1, %1};" ::"r"(s_ring + wq * kRingChunk + (r == 0 ? 84 : r == 1 ? 88 : 204) * 128 + lane * 16), "r"(0) : "memory");
        asm volatile("fence.proxy.async.shared::cta;" ::: "memory");
    }
    MOperands mo;
    uint32_t launch = 0;
    if (wg == 1 && wq < 3 && !which) m_load(mo, wqkv, jhi, jlo, wq, lane);
    if (warp == 7) launch = ld_relaxed(g->launches[cta]);
    if (x == nullptr) return;
    const uint32_t t_start = clock_now();
    if (wg == 2) {
        asm volatile("setmaxnreg.dec.sync.aligned.u32 24;");
        if (wq < 3) {
            if (lane < 3 && cta < 128) {
                const uint32_t row = 3 * (cta >> 1) + wq;
                asm volatile("prefetch.global.L2 [%0];" ::"l"((cta & 1 ? wo + row * 384 : wqkv + row * 1152 + 768) + lane * 128));
            }
            asm volatile("bar.sync 7, 192;" ::: "memory");
            const uint32_t par = lds_volatile(s_par);
            uint32_t phase = 0;
#pragma unroll 1
            for (uint32_t c = 0; c < 6; c++) {
                const uint32_t part = c * kWChunk + wq * (kWChunk / 3);
                mbar_wait(bar_img + 8 * c, 0);
                if (c == 0 && lane == 0) mbar_arrive(bar_ok);
                if (wq == 0) TRW(10 + c);
#pragma unroll 1
                while (true) {
                    uint32_t lo = ~0u;
#pragma unroll
                    for (int q = 0; q < 8; q++) lo = min(lo, lds_volatile(s_m + part + lane * 32 + (lane & 12) * 2 + q * 1024));
                    if (__all_sync(0xffffffffu, lo) || phase > 65535) break;
                    if (elect()) {
                        mbar_expect_tx(bar_redo + 8 * wq, kWChunk / 3);
                        bulk_g2s(s_m + part, g->img[0][0] + par + part, kWChunk / 3, bar_redo + 8 * wq);
                    }
                    mbar_wait(bar_redo + 8 * wq, phase++ & 1);
                }
                if (c == 2 && phase) asm volatile("st.shared.u32 [%0], %1;" ::"r"(s_again), "r"(1) : "memory");
                if (c >= 2 && lane == 0) mbar_arrive(bar_ok + 8 * c - 8);
            }
        } else {
            const CUtensorMap* map = &maps.m[w.sv == kPixBytes ? 2 : 0];
            if (elect()) {
#pragma unroll
                for (int i = 0; i < 26; i++) mbar_init(s_bar + 8 * i, i < 15 ? 1 : i < 20 ? 3 : 4);
                asm volatile("fence.mbarrier_init.release.cluster;" ::: "memory");
                prefetch_map(map + 1);
                expect_tx_only(bar_a, sizeof(Table));
                bulk_g2s(s_tab, &maps.tables->t[w.step < 0], sizeof(Table), bar_a);
            }
            if (which && has_job && elect()) {
                mbar_expect_tx(bar_wop, 4 * 6144);
                tma_3d(s_wv, &maps.wo, bar_wop, 0, jhi);
                tma_3d(s_wv + 3 * 6144, &maps.wv, bar_wop, 16 * jlo, 6);
            }
            int u = w.u, v = w.v;
            uint32_t wait_bar = bar_use, wait_par = 1, slot = 0;
#pragma unroll 1
            for (int step = 0; step < 7 - w.corner; step++) {
                const bool first = step == 0 || (w.corner && step == 4);
                const int ou = origin_u(u);
                const bool final = step == 6 - w.corner;
                if (final) { wait_bar = bar_free; wait_par = 0; }
#pragma unroll 1
                for (uint32_t bar = first ? bar_a : bar_b; bar <= (first ? bar_a : bar_mid); bar += 8) {
                    mbar_wait(bar, first ? !step : slot != 0);
                    if (elect()) mbar_expect_tx(bar, first ? 3 * kSlotBytes : bar < bar_mid ? kSlotBytes : 3 * kMidBytes);
                }
                int row = v + 4 + (first ? -w.step : w.step) / 2;
                uint32_t dst = final ? s_m : s_ring + (first ? 0 : slot), bar = first ? bar_a : bar_b, dbar = first ? 0 : 8;
#pragma unroll 1
                for (int r = 0; r < 2 - first; r++) {
                    mbar_wait(wait_bar, wait_par);
                    if (r == 0) TRW(24 + step);
#pragma unroll
                    for (int n = 0; n < 3; n++) {
                        if (n && final) mbar_wait(bar_free + 8 * n, 0);
                        if (elect()) tma_box(dst + n * kRingChunk, map + r, bar + n * dbar, (cta & 1) * kC + 64 * n, ou, (cta >> 1) & 1, row);
                    }
                    row = v + 6; bar = bar_mid; dbar = 0;
                    dst = (final ? s_m : s_ring) + kOffMid + 512;
                    if (wait_bar == bar_use) wait_bar = bar_use + 16;
                }
                TRW(32 + 8 * step + 4);
                if (step == 0) {
                    asm volatile("st.shared.v2.u32 [%0], {%1, %1};" ::"r"(s_late), "r"(0) : "memory");
                    asm volatile("bar.arrive 3, 160;\nbar.arrive 4, 160;\nbar.arrive 8, 128;\nbar.sync 9, 64;" ::: "memory");
                }
                if (step < 2) {
                    if (step) {
                        asm volatile("bar.sync 6, 128;" ::: "memory");
                    }
                    const uint32_t par = __shfl_sync(0xffffffffu, lds_volatile(s_par), 0);
                    wait_until(t_start, step ? TN(5, kTimeW) : TN(6, kTimeM));
                    TRW(5 + 4 * step);
#pragma unroll 1
                    for (int c = 3 * step; c < 3 + 3 * step; c++)
                        if (elect()) {
                            mbar_expect_tx(bar_img + 8 * c, kWChunk);
                            bulk_g2s(s_m + c * kWChunk, g->img[0][0] + (par + c * kWChunk), kWChunk, bar_img + 8 * c);
                        }
                }
                const bool again = w.corner && step == 3;
                wait_bar = step == 0 ? bar_img + 8 * TN(1, 1) : again ? bar_use + 8 : bar_use;
                if (!again) {
                    wait_par = slot ? 0 : step != 0;
                    slot ^= kSlotStride;
                    if (w.corner && step == 2) { u += 8; v -= 8; } else if (step) v += w.step;
                }
            }
        }
        TRDUMP();
        return;
    }
    if (warp == 7) {
        asm volatile("st.shared.u32 [%0], %1;\nbar.arrive 9, 64;" ::"r"(s_par), "r"((launch & 1) * 2 * kWBytes) : "memory");
        g->launches[cta][lane] = launch + 1;
        asm volatile("bar.arrive 5, 128;" ::: "memory");
    }
    if (wg == 1 && wq < 3) {
        if (!which) m_partial(mo, wq, lane, (uint32_t)dsc & 1);
        const uint32_t off = piece_offset(which, which ? jlo : jlo + wq, which ? 3 * jhi + wq : jhi, lane);
        asm volatile("bar.sync %0, %1;" ::"r"(5 + (off >> 31)), "n"(128) : "memory");
        const uint32_t par = lds_volatile(s_par);
        if (which) asm volatile("bar.sync 8, 128;" ::: "memory");
        if (has_job && wq < 2 + which) {
            float d[2][4];
            if (wq == 0) TRX(which ? 1 : 18);
            if (which) {
                mbar_wait(bar_wop, 0);
                if (wq == 0) TRX(2);
                w_piece(wq, lane, d);
            } else {
                m_reduce(wq, lane, d);
            }
            piece_store(g, par, off, which, d);
            __syncwarp();
            piece_clear(g, 2 * kWBytes - par, off, which);
            if (wq == 0) TRX(which ? 3 : 0);
        }
        if (!which) asm volatile("bar.sync 8, 128;" ::: "memory");
        asm volatile("bar.arrive 7, 192;\nbar.arrive 6, 128;" ::: "memory");
    }
    const int order = w.step < 0 ? warp ^ 3 : warp;
    int tu = w.u, tv = w.v + w.step * wg;
    const int du2 = w.corner ? 8 : 0, dv2 = w.corner ? 0 : 2 * w.step;
    uint32_t o0, o1;
    wait_until(t_start, START_TIME);
    asm volatile("setmaxnreg.inc.sync.aligned.u32 240;");
    w.pixel_offsets(tu + r8, tv + 2 * wq, j, o0, o1);
    uint32_t fa[48];
    {
        RawX raw;
        load_raw(raw, x, o0, o1);
        asm volatile("bar.sync %0, 160;" ::"r"(3 + wg) : "memory");
        raw_to_frags(raw, 0, fa);
        pin(fa);
    }
    mbar_wait(bar_ok, 0);
    const uint64_t dA = dsc + wg * (kSlotStride >> 4), dB = dsc + (wg ^ 1) * (kSlotStride >> 4);

    float acc[96];
    uint32_t po[48];
    uint32_t c0 = 0, c1 = 0;
#pragma unroll
    for (int q = 0; q < 48; q++) asm volatile("" : "=r"(po[q]));
#pragma unroll 1
    for (int i = wg; i < w.ntiles; i += 2) {
        const bool first = i == 0, last = i == w.ntiles - 1;

        TRF(8 + 16 * k);
        uint8_t *p0 = out + c0, *p1 = out + c1;
#pragma unroll 1
        for (uint32_t seen = 0;;) {
        wg_fence();
        if (!first) turn_wait(wg);
        proj_gemm(acc, fa, dsc, s_m, [&](int s) {
            if (s == 11 && !first) turn_pass(wg);
            const int n = __builtin_popcount(QSLOTS & ((1 << s) - 1));
            if (((QSLOTS >> s) & 1) && n < 12) store_one(i >= 2, out + c0, out + c1, po, n);
            if ((s == 5 && ((QSLOTS >> 13) & 1)) || (s == 9 && ((QSLOTS >> 16) & 1))) wg_commit();
            if (s == 3 || s == 7) { wg_commit(); mbar_wait(bar_img + 2 * s + 2, 0); wg_fence(); }
        });
        __syncwarp();
        TRF(9 + 16 * k);
            if (!first) break;
            mbar_wait(bar_ok + 8, 0);
            if (lds_volatile(s_again) == seen) break;
            wg_wait<0>();
            seen = 1;
        }
        c0 = o0; c1 = o1;
        w.pixel_offsets(tu + du2 + r8, tv + dv2 + 2 * wq, j, o0, o1);
        if (i + 2 >= w.ntiles) o0 = o1 = 0;
        mbar_wait(bar_a, w.corner ? i >> 1 : 0);
        auto slot = [&](int s) {
            if ((QSLOTS >> s) & 1) { store_one(i >= 2, p0, p1, po, __builtin_popcount(QSLOTS & ((1 << s) - 1))); __syncwarp(); }
        };
        constexpr int G5 = (QSLOTS >> 13) & 1, G9 = (QSLOTS >> 16) & 1;
        wg_wait<2 + G5 + G9>();
        if (last && lane == 0) mbar_arrive(bar_free);
        slot(12);
        if (G5) { wg_wait<2 + G9>(); slot(13); }
        wg_wait<1 + G9>();
        if (last && lane == 0) mbar_arrive(bar_free + 8);
        slot(14); slot(15);
        if (G9) { wg_wait<1>(); slot(16); slot(17); }
        wg_wait<0>();
        if (last && lane == 0) mbar_arrive(bar_free + 16);
        const uint64_t dE = last ? dsc + ((s_m - s_ring) >> 4) : dsc, dN = last ? dE : dB;
        pin(acc);
        TR(11 + 16 * k);
        TRT(80 + k);
        acc_to_frags(acc, fa);
        pin(fa);

        float sA[44], sE[16], sB[44];
        RawX nxt;
        if (!first) turn_wait(wg);
        wg_fence();
#pragma unroll
        for (int s = 0; s < 12; s++) {
            if (s == 0) wgmma_n88<true>(sA, fa[4 * s], fa[4 * s + 1], fa[4 * s + 2], fa[4 * s + 3], desc_at(dA, (s >> 2) * kRingChunk + (s & 3) * 32));
            else wgmma_n88<false>(sA, fa[4 * s], fa[4 * s + 1], fa[4 * s + 2], fa[4 * s + 3], desc_at(dA, (s >> 2) * kRingChunk + (s & 3) * 32));
            if (s == 11) { wg_commit(); if (!first) turn_pass(wg); }
        }
        TRF(12 + 16 * k);
        const int vq = tv + 2 * wq;
        const uint4 tabu = lds128(s_tab + offsetof(Table, u) + (window_start(tu + r8) - origin_u(tu)) * 64 + j * 16);
        const uint4 tabv = lds128(s_tab + offsetof(Table, v) + (window_start(vq) + window_start(vq + 1) - 2 * tv) * 64 + j * 16);
        const uint4 route = lds128(s_tab + lane * 16);
        load_raw(nxt, x, o0, o1);
        float v0[14], v1[14];
#pragma unroll
        for (int b = 0; b < 14; b++) {
            v0[b] = __uint_as_float((route.x >> (b + 6)) + 0xff800000u);
            v1[b] = __uint_as_float((route.y >> (b + 6)) + 0xff800000u);
        }
        const uint32_t m0 = tabu.x | tabv.z, m1 = tabu.y | tabv.w;
        if (!first) turn_wait(wg);
#pragma unroll
        for (int c = 0; c < 3; c++) {
            mbar_wait(bar_b + 8 * c, wg);
            TRF(64 + 4 * k + c);
            wg_fence();
#pragma unroll
            for (int s = 4 * c; s < 4 * c + 4; s++) {
                if (s == 0) wgmma_n88<true>(sB, fa[4 * s], fa[4 * s + 1], fa[4 * s + 2], fa[4 * s + 3], desc_at(dN, c * kRingChunk + (s & 3) * 32));
                else wgmma_n88<false>(sB, fa[4 * s], fa[4 * s + 1], fa[4 * s + 2], fa[4 * s + 3], desc_at(dN, c * kRingChunk + (s & 3) * 32));
                if (s == 3) {
                    wg_commit();
                    wg_wait<1>();
                    pin(sA);
                    gather_outer(sA, tabu.x | tabv.x, tabu.y | tabv.y, v0, v1);
                    pin(v0); pin(v1);
                }
            }
        }
        wg_commit();
        mbar_wait(bar_mid, wg);
        wg_fence();
#pragma unroll
        for (int s = 0; s < 12; s++)
            if (s == 0) wgmma_n32<true>(sE, fa[4 * s], fa[4 * s + 1], fa[4 * s + 2], fa[4 * s + 3], desc_at(dE, kOffMid + (s >> 2) * kRingChunk + (s & 3) * 32));
            else wgmma_n32<false>(sE, fa[4 * s], fa[4 * s + 1], fa[4 * s + 2], fa[4 * s + 3], desc_at(dE, kOffMid + (s >> 2) * kRingChunk + (s & 3) * 32));
        wg_commit();
        turn_pass(wg);
        TRF(13 + 16 * k);
        wg_wait<1>();
        pin(sB);
        gather_outer(sB, m0, m1, v0, v1);
        wg_wait<0>();
        pin(sE);
        TRF(14 + 16 * k);
        gather_mid(sE, m1, v0, v1);
        const float mx0 = quad_max(tree_max(v0)), mx1 = quad_max(tree_max(v1));

        uint32_t y[14], pa[12], pb[12];
        exp_route<0, 14>(v0, v1, mx0, mx1, route, (j & 1) == 0, y);
        float s0 = tree_sum(v0), s1 = tree_sum(v1);
        asm volatile("" : "+f"(s0), "+f"(s1));
        unfold<16, 0, 6>(y, tabv.y, pa);
        turn_wait(wg + (y[0] >> 31));
        TRF(15 + 16 * k + (y[13] >> 31));
        wg_fence();
        wgmma_sp_n192_tb<true, 0>(acc, pa[0], pa[1], pa[2], pa[3], desc_at(dA, kToV), tabu.z);
        wgmma_sp_n192_tb<false, 1>(acc, pa[4], pa[5], pa[6], pa[7], desc_at(dA, kToV + 4096), tabu.z);
        wgmma_sp_n192_tb<false, 0>(acc, pa[8], pa[9], pa[10], pa[11], desc_at(dA, kToV + 8192), tabu.w);
        wg_commit();
        wgmma_sp_n192_tb<false, 1>(acc, j == 0 ? 0u : y[10], j == 0 ? 0u : y[11], y[12], y[13], desc_at(dE, kToV + kOffMid), tabu.w);
        wg_commit();
        unfold<24, 0, 6>(y, tabv.y, pb);
        wg_fence();
        wgmma_sp_n192_tb<false, 0>(acc, pb[0], pb[1], pb[2], pb[3], desc_at(dN, kToV), tabu.z);
        wgmma_sp_n192_tb<false, 1>(acc, pb[4], pb[5], pb[6], pb[7], desc_at(dN, kToV + 4096), tabu.z);
        wgmma_sp_n192_tb<false, 0>(acc, pb[8], pb[9], pb[10], pb[11], desc_at(dN, kToV + 8192), tabu.w);
        wg_commit();
        if (!last) turn_pass(wg);
        TRF(16 + 16 * k);
        wg_wait<2>();
        if (lane == 0) mbar_arrive(bar_use);
        wg_wait<1>();
        if (lane == 0) mbar_arrive(bar_use + 16);
        TRF(17 + 16 * k);
        mbar_wait(bar_ok + 16, 0);
        wg_wait<0>();
        if (lane == 0) mbar_arrive(bar_use + 8);
        pin(acc);
        TR(18 + 16 * k);

        acc_to_frags(acc, po);
        pin(po);
        if (last) {
            const float inv0 = rcp(quad_sum(s0)), inv1 = rcp(quad_sum(s1));
            float t0[32], t1[32], t2[32];
            uint32_t pq[48];
            wg_fence();
            third_gemm<0>(t0, po, dsc, [](int) {});
            third_gemm<1>(t1, po, dsc, [&](int s) { if (s == 3) { keep(wqkv == nullptr, __float_as_uint(inv0), __float_as_uint(inv1), c0, c1); __syncwarp(); } });
            wg_wait<1>();
            third_pack<0>(t0, inv0, inv1, pq);
            store_one<false>(true, out + c0, out + c1, pq, 0);
            __syncwarp();
            third_gemm<2>(t2, po, dsc, [&](int s) { if (s == 3 || s == 7 || s == 9) store_one(true, out + c0, out + c1, pq, (s + 3) >> 2); });
            __syncwarp();
            wg_wait<1>();
            third_pack<1>(t1, inv0, inv1, pq);
#pragma unroll
            for (int n = 4; n < 8; n++) store_one<false>(true, out + c0, out + c1, pq, n);
            __syncwarp();
            wg_wait<0>();
            third_pack<2>(t2, inv0, inv1, pq);
#pragma unroll
            for (int n = 8; n < 12; n++) store_one<false>(true, out + c0, out + c1, pq, n);
            break;
        }
        turn_wait(wg);
        wg_fence();
        proj_gemm(acc, po, dsc, s_wv, [&](int s) {
            if (s == 3 || s == 7) { mbar_wait(bar_ok + 2 * s + 18, 0); wg_fence(); }
            if (s + 1 == OSPLIT && i + 2 == w.ntiles) { turn_pass(wg); turn_wait(wg); }
        });
        turn_pass(wg);
        TRF(19 + 16 * k);
        const uint32_t zero = lds_volatile(s_late);
        const float inv0 = rcp(quad_sum(s0 + __uint_as_float(zero))), inv1 = rcp(quad_sum(s1 + __uint_as_float(zero)));
        raw_to_frags(nxt, zero, fa);
        pin(fa);
#pragma unroll
        for (int q = 0; q < 48; q += 4) keep(wqkv == nullptr, fa[q], fa[q + 1], fa[q + 2], fa[q + 3]);
        keep(wqkv == nullptr, __float_as_uint(inv0), __float_as_uint(inv1), zero, lane);
        TRF(20 + 16 * k);
        tu += du2; tv += dv2;
        wg_wait<0>();
        pin(acc);
        TR(21 + 16 * k);
#pragma unroll
        for (int q = 0; q < 96; q++) acc[q] *= q & 2 ? inv1 : inv0;
        pack_out(acc, po);
#pragma unroll
        for (int n = 0; n < INL; n++) store_one<false>(i + 2 == w.ntiles, out + c0, out + c1, po, n);
        pin(po);
    }
    if (wg == 0) {
#pragma unroll
        for (int n = INL; n < 12; n++) {
            __nanosleep(NAP);
            store_one<false>(true, out + c0, out + c1, po, n);
        }
    }
    TRE(7);
    TRG(1);
    TRDUMP();
}

typedef CUresult (*EncodeTiledFn)(CUtensorMap*, CUtensorMapDataType, cuuint32_t, void*, const cuuint64_t*, const cuuint64_t*,
                                  const cuuint32_t*, const cuuint32_t*, CUtensorMapInterleave, CUtensorMapSwizzle,
                                  CUtensorMapL2promotion, CUtensorMapFloatOOBfill);

bool make_maps(EncodeTiledFn fn, Maps* maps, void* x, void* wqkv, void* wo) {
    const cuuint64_t pix2 = 2 * kPixBytes, row = (cuuint64_t)kHW * kPixBytes;
    const cuuint32_t estr[5] = {1, 1, 1, 1, 1};
    bool ok = true;
    for (int tr = 0; tr < 2; tr++)
        for (int b = 0; b < 2; b++) {
            const cuuint64_t su = tr ? 2 * row : pix2, sv = tr ? pix2 : 2 * row;
            const cuuint64_t dims[5] = {2 * kC, 2, 105, 2, 112};
            const cuuint64_t strides[4] = {7 * su, su, row, sv};
            const cuuint32_t box[5] = {64, 2, 7, 1, b ? 2u : 6u};
            ok = ok && fn(&maps->m[2 * tr + b], CU_TENSOR_MAP_DATA_TYPE_BFLOAT16, 5, x, dims, strides, box, estr,
                          CU_TENSOR_MAP_INTERLEAVE_NONE, CU_TENSOR_MAP_SWIZZLE_128B, CU_TENSOR_MAP_L2_PROMOTION_L2_128B,
                          CU_TENSOR_MAP_FLOAT_OOB_FILL_NONE) == CUDA_SUCCESS;
        }
    for (int b = 0; b < 2; b++) {
        const cuuint64_t dims[3] = {b ? 64u : 48u, kC, b ? 9u : 4u}, strides[2] = {(b ? 3u : 1u) * kPixBytes, b ? 128u : 96u};
        const cuuint32_t box[3] = {b ? 64u : 48u, b ? 16u : 192u, b ? 3u : 1u};
        ok = ok && fn(b ? &maps->wv : &maps->wo, CU_TENSOR_MAP_DATA_TYPE_BFLOAT16, 3, b ? wqkv : wo, dims, strides, box, estr,
                      CU_TENSOR_MAP_INTERLEAVE_NONE, b ? CU_TENSOR_MAP_SWIZZLE_128B : CU_TENSOR_MAP_SWIZZLE_NONE, CU_TENSOR_MAP_L2_PROMOTION_L2_128B,
                      CU_TENSOR_MAP_FLOAT_OOB_FILL_NONE) == CUDA_SUCCESS;
    }
    return ok;
}

}

extern "C" void kernel_launch(void* const* d_in, const int* in_sizes, int n_in, void* d_out, int out_size) {
    static EncodeTiledFn encode = nullptr;
    static Scratch* scratch = nullptr;
    static Tables* tables = nullptr;
    if (!encode) {
        int dev = 0, reserved = 0;
        cudaFuncAttributes attr;
        cudaGetDevice(&dev);
        cudaDeviceGetAttribute(&reserved, cudaDevAttrReservedSharedMemoryPerBlock, dev);
        cudaFuncGetAttributes(&attr, nat_fused_kernel);
        if (reserved != (int)kSmemBase || attr.sharedSizeBytes != 0) return;
        cudaGetSymbolAddress((void**)&scratch, g_scratch);
        cudaGetSymbolAddress((void**)&tables, g_tables);
        void* fn = nullptr;
        cudaDriverEntryPointQueryResult st;
        cudaGetDriverEntryPoint("cuTensorMapEncodeTiled", &fn, cudaEnableDefault, &st);
        encode = (EncodeTiledFn)fn;
        cudaFuncSetAttribute(nat_fused_kernel, cudaFuncAttributeMaxDynamicSharedMemorySize, kSmemBytes);
    }
    Maps maps;
    maps.tables = tables;
    if (!encode || !make_maps(encode, &maps, d_in[0], d_in[1], d_in[2])) return;
    nat_fused_kernel<<<kGrid, kThreads, kSmemBytes>>>((const uint8_t*)d_in[0], (const uint8_t*)d_in[1], (uint8_t*)d_out, scratch, (const uint8_t*)d_in[2],
                                                      kDescRing, maps);
}
```

```cpp
#include <cuda_runtime.h>
#include <cuda_bf16.h>
#include <cuda.h>
#include <stdint.h>
#include <type_traits>
#include <stdlib.h>
#include <stdio.h>
#include <stddef.h>

#define QSLOTS 0x16fae
#define OSPLIT 2
#define INL 1
#define TSLOTS 0x54
#define NAP 44

namespace {

constexpr int kC          = 192;
constexpr int kHW         = 224;
constexpr int kPixBytes   = kC * 2;
constexpr int kSlotBytes  = 84 * 128;
constexpr int kMidBytes   = 28 * 128;
constexpr int kOffMid     = 88 * 128;
constexpr int kSlotStride = 120 * 128;
constexpr int kRingChunk  = 208 * 128;
constexpr int kWChunk     = 192 * 128;
constexpr int kWBytes     = 3 * kWChunk;
constexpr uint32_t kSmemBase = 1024;
constexpr uint32_t s_ring = kSmemBase, s_m = s_ring + 3 * kRingChunk, s_wv = s_m + kWBytes, s_bar = s_wv + kWBytes;
constexpr uint32_t bar_b = s_bar, bar_mid = s_bar + 24, bar_a = s_bar + 32, bar_img = s_bar + 40, bar_redo = s_bar + 88,
                   bar_wop = s_bar + 112, bar_ok = s_bar + 120, bar_use = s_bar + 160, bar_free = s_bar + 184;
constexpr uint32_t s_par = s_bar + 208, s_late = s_bar + 216, s_again = s_bar + 220, s_tab = s_bar + 256, s_trace = s_tab + 2048;
constexpr int kSmemBytes  = s_trace + 2048 - kSmemBase;
constexpr int kThreads    = 384;
constexpr int kGrid       = 132;
constexpr int kTimeM = 2500, kTimeW = 5100;
constexpr float kScaleLog2e = 0.07216878364870322f * 1.4426950408889634f;

struct Maps {
    CUtensorMap m[4];
    CUtensorMap wo, wv;
    const struct Tables* tables;
};
#define TN(i, dflt) (dflt)
#define START_TIME (wg ? 900 + 450 * order : 250 + 560 * order)

struct Scratch {
    uint8_t img[2][2][kWBytes];
    uint32_t launches[kGrid][32];
};
__device__ __align__(1024) Scratch g_scratch;

__host__ __device__ constexpr int entry_bit(int k) { return 8 * ((k >> 1) & 3) + 3 * (k & 1); }
struct Table {
    uint32_t route[32][4];
    uint32_t u[8][4][4];
    uint32_t v[16][4][4];
};
struct Tables { Table t[2]; };
constexpr Tables make_tables() {
    Tables r = {};
    for (int rev = 0; rev < 2; rev++)
        for (int j = 0; j < 4; j++) {
            Table& t = r.t[rev];
            for (int q = 0; q < 8; q++) {
                uint32_t* e = t.route[4 * q + j];
                e[0] = 4 * q + 2 * (j & 1) + (j >> 1); e[1] = e[0] ^ 1;
                e[2] = j < 2 ? 0x5410u : 0x1054u; e[3] = e[2] + 0x2222u;
                e = t.u[q][j];
                for (int k = 0; k < 16; k++) e[k >> 3] |= ((4 * (k < 12 ? k : k - 2) + j) % 7 < q ? 1u : 0u) << entry_bit(k);
                for (int k = 0; k < 2; k++) {
                    const int step = 2 * k + (j >> 1), p0 = (step < 3 ? 16 * step : 40) + 8 * (j & 1);
                    uint32_t m = 0x8888u;
                    for (int n = 0; n < 8; n++) m |= ((p0 + n) % 7 < q ? 1u : 0u) << (2 * n);
                    e[2 + k] = m * 0x10001u;
                }
            }
            for (int sum = 0; sum < 15; sum++) {
                uint32_t* e = t.v[sum][j];
                for (int row = 0; row < 2; row++)
                    for (int b = 0; b < 14; b++) {
                        const int off = (sum + row) / 2, p = 4 * b + j;
                        if (p < 42 && p >= 7 * off) e[2 * rev + (b >> 3)] |= 2u << (entry_bit(b) + row);
                        if (p < 7 * off - 7) e[2 - 2 * rev + (b >> 3)] |= 2u << (entry_bit(b) + row);
                        if (p >= 42 && p >= 7 * off && p < 7 * off + 49) e[3] |= 2u << (entry_bit(b + 2) + row);
                    }
                for (int n = 0; n < 6; n++)
                    if (8 * n + 2 * j < 42) e[1] |= 0x10000u << (n + ((8 * n + 2 * j >= 7 * (sum / 2 & ~1)) != rev ? 0 : 8));
            }
        }
    return r;
}
__device__ __align__(128) const Tables g_tables = make_tables();

#define WO4(i) "=f"(d[i]), "=f"(d[i + 1]), "=f"(d[i + 2]), "=f"(d[i + 3])
#define RW4(i) "+f"(d[i]), "+f"(d[i + 1]), "+f"(d[i + 2]), "+f"(d[i + 3])

template <bool FIRST>
__device__ __forceinline__ void wgmma_n192(float (&d)[96], uint32_t a0, uint32_t a1, uint32_t a2, uint32_t a3, uint64_t descb) {
    if constexpr (FIRST) {
        asm volatile(
            "wgmma.mma_async.sync.aligned.m64n192k16.f32.bf16.bf16 "
            "{%0, %1, %2, %3, %4, %5, %6, %7, %8, %9, %10, %11, %12, %13, %14, %15, %16, %17, %18, %19, %20, %21, %22, %23, "
            "%24, %25, %26, %27, %28, %29, %30, %31, %32, %33, %34, %35, %36, %37, %38, %39, %40, %41, %42, %43, %44, %45, %46, %47, "
            "%48, %49, %50, %51, %52, %53, %54, %55, %56, %57, %58, %59, %60, %61, %62, %63, %64, %65, %66, %67, %68, %69, %70, %71, "
            "%72, %73, %74, %75, %76, %77, %78, %79, %80, %81, %82, %83, %84, %85, %86, %87, %88, %89, %90, %91, %92, %93, %94, %95}, "
            "{%96, %97, %98, %99}, %100, 0, 1, 1, 0;"
            : WO4(0), WO4(4), WO4(8), WO4(12), WO4(16), WO4(20), WO4(24), WO4(28), WO4(32), WO4(36), WO4(40), WO4(44),
              WO4(48), WO4(52), WO4(56), WO4(60), WO4(64), WO4(68), WO4(72), WO4(76), WO4(80), WO4(84), WO4(88), WO4(92)
            : "r"(a0), "r"(a1), "r"(a2), "r"(a3), "l"(descb));
    } else {
        asm volatile(
            "wgmma.mma_async.sync.aligned.m64n192k16.f32.bf16.bf16 "
            "{%0, %1, %2, %3, %4, %5, %6, %7, %8, %9, %10, %11, %12, %13, %14, %15, %16, %17, %18, %19, %20, %21, %22, %23, "
            "%24, %25, %26, %27, %28, %29, %30, %31, %32, %33, %34, %35, %36, %37, %38, %39, %40, %41, %42, %43, %44, %45, %46, %47, "
            "%48, %49, %50, %51, %52, %53, %54, %55, %56, %57, %58, %59, %60, %61, %62, %63, %64, %65, %66, %67, %68, %69, %70, %71, "
            "%72, %73, %74, %75, %76, %77, %78, %79, %80, %81, %82, %83, %84, %85, %86, %87, %88, %89, %90, %91, %92, %93, %94, %95}, "
            "{%96, %97, %98, %99}, %100, 1, 1, 1, 0;"
            : RW4(0), RW4(4), RW4(8), RW4(12), RW4(16), RW4(20), RW4(24), RW4(28), RW4(32), RW4(36), RW4(40), RW4(44),
              RW4(48), RW4(52), RW4(56), RW4(60), RW4(64), RW4(68), RW4(72), RW4(76), RW4(80), RW4(84), RW4(88), RW4(92)
            : "r"(a0), "r"(a1), "r"(a2), "r"(a3), "l"(descb));
    }
}

template <bool FIRST>
__device__ __forceinline__ void wgmma_n64(float (&d)[32], uint32_t a0, uint32_t a1, uint32_t a2, uint32_t a3, uint64_t descb) {
    if constexpr (FIRST) {
        asm volatile(
            "wgmma.mma_async.sync.aligned.m64n64k16.f32.bf16.bf16 "
            "{%0, %1, %2, %3, %4, %5, %6, %7, %8, %9, %10, %11, %12, %13, %14, %15, %16, %17, %18, %19, %20, %21, %22, %23, "
            "%24, %25, %26, %27, %28, %29, %30, %31}, "
            "{%32, %33, %34, %35}, %36, 0, 1, 1, 0;"
            : WO4(0), WO4(4), WO4(8), WO4(12), WO4(16), WO4(20), WO4(24), WO4(28)
            : "r"(a0), "r"(a1), "r"(a2), "r"(a3), "l"(descb));
    } else {
        asm volatile(
            "wgmma.mma_async.sync.aligned.m64n64k16.f32.bf16.bf16 "
            "{%0, %1, %2, %3, %4, %5, %6, %7, %8, %9, %10, %11, %12, %13, %14, %15, %16, %17, %18, %19, %20, %21, %22, %23, "
            "%24, %25, %26, %27, %28, %29, %30, %31}, "
            "{%32, %33, %34, %35}, %36, 1, 1, 1, 0;"
            : RW4(0), RW4(4), RW4(8), RW4(12), RW4(16), RW4(20), RW4(24), RW4(28)
            : "r"(a0), "r"(a1), "r"(a2), "r"(a3), "l"(descb));
    }
}

template <bool FIRST>
__device__ __forceinline__ void wgmma_n88(float (&d)[44], uint32_t a0, uint32_t a1, uint32_t a2, uint32_t a3, uint64_t descb) {
    if constexpr (FIRST) {
        asm volatile(
            "wgmma.mma_async.sync.aligned.m64n88k16.f32.bf16.bf16 "
            "{%0, %1, %2, %3, %4, %5, %6, %7, %8, %9, %10, %11, %12, %13, %14, %15, %16, %17, %18, %19, %20, %21, %22, %23, "
            "%24, %25, %26, %27, %28, %29, %30, %31, %32, %33, %34, %35, %36, %37, %38, %39, %40, %41, %42, %43}, "
            "{%44, %45, %46, %47}, %48, 0, 1, 1, 0;"
            : WO4(0), WO4(4), WO4(8), WO4(12), WO4(16), WO4(20), WO4(24), WO4(28), WO4(32), WO4(36), WO4(40)
            : "r"(a0), "r"(a1), "r"(a2), "r"(a3), "l"(descb));
    } else {
        asm volatile(
            "wgmma.mma_async.sync.aligned.m64n88k16.f32.bf16.bf16 "
            "{%0, %1, %2, %3, %4, %5, %6, %7, %8, %9, %10, %11, %12, %13, %14, %15, %16, %17, %18, %19, %20, %21, %22, %23, "
            "%24, %25, %26, %27, %28, %29, %30, %31, %32, %33, %34, %35, %36, %37, %38, %39, %40, %41, %42, %43}, "
            "{%44, %45, %46, %47}, %48, 1, 1, 1, 0;"
            : RW4(0), RW4(4), RW4(8), RW4(12), RW4(16), RW4(20), RW4(24), RW4(28), RW4(32), RW4(36), RW4(40)
            : "r"(a0), "r"(a1), "r"(a2), "r"(a3), "l"(descb));
    }
}

template <bool FIRST>
__device__ __forceinline__ void wgmma_n32(float (&d)[16], uint32_t a0, uint32_t a1, uint32_t a2, uint32_t a3, uint64_t descb) {
    if constexpr (FIRST) {
        asm volatile(
            "wgmma.mma_async.sync.aligned.m64n32k16.f32.bf16.bf16 "
            "{%0, %1, %2, %3, %4, %5, %6, %7, %8, %9, %10, %11, %12, %13, %14, %15}, "
            "{%16, %17, %18, %19}, %20, 0, 1, 1, 0;"
            : WO4(0), WO4(4), WO4(8), WO4(12)
            : "r"(a0), "r"(a1), "r"(a2), "r"(a3), "l"(descb));
    } else {
        asm volatile(
            "wgmma.mma_async.sync.aligned.m64n32k16.f32.bf16.bf16 "
            "{%0, %1, %2, %3, %4, %5, %6, %7, %8, %9, %10, %11, %12, %13, %14, %15}, "
            "{%16, %17, %18, %19}, %20, 1, 1, 1, 0;"
            : RW4(0), RW4(4), RW4(8), RW4(12)
            : "r"(a0), "r"(a1), "r"(a2), "r"(a3), "l"(descb));
    }
}

template <bool FIRST, int SEL>
__device__ __forceinline__ void wgmma_sp_n192_tb(float (&d)[96], uint32_t a0, uint32_t a1, uint32_t a2, uint32_t a3, uint64_t descb, uint32_t meta) {
    if constexpr (FIRST) {
        asm volatile(
            "wgmma.mma_async.sp.sync.aligned.m64n192k32.f32.bf16.bf16 "
            "{%0, %1, %2, %3, %4, %5, %6, %7, %8, %9, %10, %11, %12, %13, %14, %15, %16, %17, %18, %19, %20, %21, %22, %23, "
            "%24, %25, %26, %27, %28, %29, %30, %31, %32, %33, %34, %35, %36, %37, %38, %39, %40, %41, %42, %43, %44, %45, %46, %47, "
            "%48, %49, %50, %51, %52, %53, %54, %55, %56, %57, %58, %59, %60, %61, %62, %63, %64, %65, %66, %67, %68, %69, %70, %71, "
            "%72, %73, %74, %75, %76, %77, %78, %79, %80, %81, %82, %83, %84, %85, %86, %87, %88, %89, %90, %91, %92, %93, %94, %95}, "
            "{%96, %97, %98, %99}, %100, %101, %102, 0, 1, 1, 1;"
            : WO4(0), WO4(4), WO4(8), WO4(12), WO4(16), WO4(20), WO4(24), WO4(28), WO4(32), WO4(36), WO4(40), WO4(44),
              WO4(48), WO4(52), WO4(56), WO4(60), WO4(64), WO4(68), WO4(72), WO4(76), WO4(80), WO4(84), WO4(88), WO4(92)
            : "r"(a0), "r"(a1), "r"(a2), "r"(a3), "l"(descb), "r"(meta), "n"(SEL));
    } else {
        asm volatile(
            "wgmma.mma_async.sp.sync.aligned.m64n192k32.f32.bf16.bf16 "
            "{%0, %1, %2, %3, %4, %5, %6, %7, %8, %9, %10, %11, %12, %13, %14, %15, %16, %17, %18, %19, %20, %21, %22, %23, "
            "%24, %25, %26, %27, %28, %29, %30, %31, %32, %33, %34, %35, %36, %37, %38, %39, %40, %41, %42, %43, %44, %45, %46, %47, "
            "%48, %49, %50, %51, %52, %53, %54, %55, %56, %57, %58, %59, %60, %61, %62, %63, %64, %65, %66, %67, %68, %69, %70, %71, "
            "%72, %73, %74, %75, %76, %77, %78, %79, %80, %81, %82, %83, %84, %85, %86, %87, %88, %89, %90, %91, %92, %93, %94, %95}, "
            "{%96, %97, %98, %99}, %100, %101, %102, 1, 1, 1, 1;"
            : RW4(0), RW4(4), RW4(8), RW4(12), RW4(16), RW4(20), RW4(24), RW4(28), RW4(32), RW4(36), RW4(40), RW4(44),
              RW4(48), RW4(52), RW4(56), RW4(60), RW4(64), RW4(68), RW4(72), RW4(76), RW4(80), RW4(84), RW4(88), RW4(92)
            : "r"(a0), "r"(a1), "r"(a2), "r"(a3), "l"(descb), "r"(meta), "n"(SEL));
    }
}

#define TR(slot)
#define TRX(slot)
#define TRE(slot)
#define TRT(slot)
#define TRF(slot)
#define TRW(slot)
#define TRG(slot)
#define TRDUMP()

__device__ __forceinline__ void wg_fence() { asm volatile("wgmma.fence.sync.aligned;" ::: "memory"); }
__device__ __forceinline__ void wg_commit() { asm volatile("wgmma.commit_group.sync.aligned;" ::: "memory"); }
template <int N>
__device__ __forceinline__ void wg_wait() { asm volatile("wgmma.wait_group.sync.aligned %0;" ::"n"(N) : "memory"); }

template <int N>
__device__ __forceinline__ void pin(float (&d)[N]) {
#pragma unroll
    for (int i = 0; i < N; i++) asm volatile("" : "+f"(d[i])::"memory");
}
template <int N>
__device__ __forceinline__ void pin(uint32_t (&d)[N]) {
#pragma unroll
    for (int i = 0; i < N; i++) asm volatile("" : "+r"(d[i])::"memory");
}

constexpr uint64_t kDescRing = ((uint64_t)((1u << 30) | (1024u >> 4)) << 32) | (1u << 16) | (s_ring >> 4);
constexpr uint32_t kToV = ((kRingChunk >> 4) - 1) << 20;
__device__ __forceinline__ uint64_t desc_at(uint64_t base, uint32_t byte_off) {
    uint64_t d;
    asm volatile("add.s64 %0, %1, %2;" : "=l"(d) : "l"(base), "l"((uint64_t)(byte_off >> 4)));
    return d;
}

__device__ __forceinline__ void mbar_init(uint32_t bar, uint32_t count) {
    asm volatile("mbarrier.init.shared::cta.b64 [%0], %1;" ::"r"(bar), "r"(count) : "memory");
}
__device__ __forceinline__ void mbar_expect_tx(uint32_t bar, uint32_t bytes) {
    asm volatile("mbarrier.arrive.expect_tx.shared::cta.b64 _, [%0], %1;" ::"r"(bar), "r"(bytes) : "memory");
}
__device__ __forceinline__ void expect_tx_only(uint32_t bar, uint32_t bytes) {
    asm volatile("mbarrier.expect_tx.relaxed.cta.shared::cta.b64 [%0], %1;" ::"r"(bar), "r"(bytes) : "memory");
}
__device__ __forceinline__ void mbar_arrive(uint32_t bar) {
    asm volatile("mbarrier.arrive.shared::cta.b64 _, [%0];" ::"r"(bar) : "memory");
}
__device__ __forceinline__ void mbar_wait(uint32_t bar, uint32_t parity) {
    asm volatile(
        "{\n.reg .pred p;\n"
        "W: mbarrier.try_wait.parity.shared::cta.b64 p, [%0], %1;\n"
        "@!p bra W;\n}\n"
        ::"r"(bar), "r"(parity) : "memory");
}
__device__ __forceinline__ uint32_t clock_now() {
    uint32_t c;
    asm volatile("mov.u32 %0, %%clock;" : "=r"(c)::"memory");
    return c;
}
__device__ __forceinline__ void wait_until(uint32_t t0, int t) {
    if (t == 0) return;
    while ((int)(clock_now() - t0) < t) {}
}
__device__ __forceinline__ bool elect() {
    uint32_t ok;
    asm volatile("{\n.reg .pred p;\nelect.sync _|p, 0xffffffff;\nselp.u32 %0, 1, 0, p;\n}\n" : "=r"(ok));
    return ok != 0;
}
__device__ __forceinline__ void turn_wait(int wg) { asm volatile("bar.sync %0, 256;" ::"r"(1 + wg) : "memory"); }
__device__ __forceinline__ void turn_pass(int wg) { asm volatile("bar.arrive %0, 256;" ::"r"(2 - wg) : "memory"); }

__device__ __forceinline__ void tma_box(uint32_t dst, const CUtensorMap* map, uint32_t bar, int c0, int c2, int c3, int c4) {
    asm volatile(
        "cp.async.bulk.tensor.5d.shared::cluster.global.mbarrier::complete_tx::bytes [%0], [%1, {%3, %4, %5, %6, %7}], [%2];"
        ::"r"(dst), "l"(map), "r"(bar), "r"(c0), "r"(0), "r"(c2), "r"(c3), "r"(c4)
        : "memory");
}
__device__ __forceinline__ void tma_3d(uint32_t dst, const CUtensorMap* map, uint32_t bar, int c1, int c2) {
    asm volatile("cp.async.bulk.tensor.3d.shared::cluster.global.mbarrier::complete_tx::bytes [%0], [%1, {%3, %4, %5}], [%2];"
                 ::"r"(dst), "l"(map), "r"(bar), "r"(0), "r"(c1), "r"(c2)
                 : "memory");
}
__device__ __forceinline__ void prefetch_map(const CUtensorMap* map) {
    asm volatile("prefetch.tensormap [%0];" ::"l"(map) : "memory");
}
__device__ __forceinline__ uint4 ldg(const void* p) {
    uint4 v;
    asm volatile("ld.global.v4.u32 {%0, %1, %2, %3}, [%4];" : "=r"(v.x), "=r"(v.y), "=r"(v.z), "=r"(v.w) : "l"(p) : "memory");
    return v;
}
__device__ __forceinline__ uint32_t pack_bf16(float lo, float hi) {
    uint32_t r;
    asm("cvt.rn.bf16x2.f32 %0, %1, %2;" : "=r"(r) : "f"(hi), "f"(lo));
    return r;
}
__device__ __forceinline__ float ex2(float x) {
    float y;
    asm("ex2.approx.ftz.f32 %0, %1;" : "=f"(y) : "f"(x));
    return y;
}
__device__ __forceinline__ float rcp(float x) {
    float y;
    asm("rcp.approx.ftz.f32 %0, %1;" : "=f"(y) : "f"(x));
    return y;
}
__device__ __forceinline__ void mma16816(float (&d)[4], uint32_t a0, uint32_t a1, uint32_t a2, uint32_t a3, uint32_t b0, uint32_t b1) {
    asm volatile("mma.sync.aligned.m16n8k16.row.col.f32.bf16.bf16.f32 {%0, %1, %2, %3}, {%4, %5, %6, %7}, {%8, %9}, {%0, %1, %2, %3};"
                 : "+f"(d[0]), "+f"(d[1]), "+f"(d[2]), "+f"(d[3])
                 : "r"(a0), "r"(a1), "r"(a2), "r"(a3), "r"(b0), "r"(b1));
}
__device__ __forceinline__ uint4 lds128(uint32_t addr) {
    uint4 v;
    asm volatile("ld.volatile.shared.v4.u32 {%0, %1, %2, %3}, [%4];" : "=r"(v.x), "=r"(v.y), "=r"(v.z), "=r"(v.w) : "r"(addr) : "memory");
    return v;
}
__device__ __forceinline__ uint32_t lds_volatile(uint32_t addr) {
    uint32_t v;
    asm volatile("ld.volatile.shared.u32 %0, [%1];" : "=r"(v) : "r"(addr) : "memory");
    return v;
}

__device__ __forceinline__ int window_start(int n) { return min(max(n, 0), 105); }
__device__ __forceinline__ int origin_u(int u) { return min(max(u, 0), 98); }

struct Work {
    int u, v;
    int step;
    uint32_t su, sv;
    uint32_t base;
    bool corner;
    int ntiles;
    __device__ __forceinline__ void pixel_offsets(int qu, int qv, int j, uint32_t& o0, uint32_t& o1) const {
        const uint32_t b = (qu + window_start(qu)) * su + j * 16 + base;
        o0 = b + (qv + window_start(qv)) * sv;
        o1 = b + (qv + 1 + window_start(qv + 1)) * sv;
    }
};

__device__ __forceinline__ Work decode_work(int c) {
    Work w;
    const bool transposed = (c >> 4) == 7;
    const int px = 6 * (c & 1), py = 3 * (c & 2);
    w.corner = c >= 128;
    w.step = 8 - 4 * (c & 4);
    w.u = (c < 112 ? c & ~7 : 96 + (c & 8)) + (transposed ? py : px) - 6;
    w.v = (w.corner ? 96 : 48 - 2 * (c & 4)) + (transposed ? px : py) - 6;
    w.su = transposed ? kHW * kPixBytes : kPixBytes;
    w.sv = transposed ? kPixBytes : kHW * kPixBytes;
    w.base = px * (kPixBytes / 6) + py * (kHW * kPixBytes / 6) + 6 * (kHW + 1) * kPixBytes;
    w.ntiles = w.corner ? 4 : 6;
    return w;
}

struct RawX { uint4 a[6], b[6]; };
__device__ __forceinline__ void load_raw(RawX& r, const uint8_t* base, uint32_t o0, uint32_t o1) {
    __syncwarp();
#pragma unroll
    for (int c = 0; c < 6; c++) { r.a[c] = ldg(base + o0 + c * 64); r.b[c] = ldg(base + o1 + c * 64); }
    __syncwarp();
}
__device__ __forceinline__ void raw_to_frags(const RawX& r, uint32_t zero, uint32_t (&f)[48]) {
#pragma unroll
    for (int c = 0; c < 6; c++) {
        asm volatile("{\n.reg .b32 t, u;\nadd.u32 t, %4, %8;\nadd.u32 u, %5, %8;\nxor.b32 %0, %6, %8;\nxor.b32 %1, %7, %8;\n"
                     "xor.b32 %2, t, %8;\nxor.b32 %3, u, %8;\n}\n"
                     : "=&r"(f[8 * c + 1]), "=&r"(f[8 * c + 3]), "=&r"(f[8 * c + 4]), "=&r"(f[8 * c + 6])
                     : "r"(r.a[c].y), "r"(r.a[c].w), "r"(r.b[c].x), "r"(r.b[c].z), "r"(zero));
        f[8 * c + 0] = r.a[c].x; f[8 * c + 2] = r.a[c].z; f[8 * c + 5] = r.b[c].y; f[8 * c + 7] = r.b[c].w;
    }
}
__device__ __forceinline__ void acc_to_frags(const float (&d)[96], uint32_t (&f)[48]) {
#pragma unroll
    for (int i = 0; i < 48; i++) f[i] = pack_bf16(d[2 * i], d[2 * i + 1]);
}

template <class F>
__device__ __forceinline__ void proj_gemm(float (&d)[96], const uint32_t (&a)[48], uint64_t dsc, uint32_t img, F after) {
#pragma unroll
    for (int s = 0; s < 12; s++) {
        if (s == 0) wgmma_n192<true>(d, a[4 * s], a[4 * s + 1], a[4 * s + 2], a[4 * s + 3], desc_at(dsc, img - s_ring + (s >> 2) * kWChunk + (s & 3) * 32));
        else wgmma_n192<false>(d, a[4 * s], a[4 * s + 1], a[4 * s + 2], a[4 * s + 3], desc_at(dsc, img - s_ring + (s >> 2) * kWChunk + (s & 3) * 32));
        if (s == 11) wg_commit();
        after(s);
    }
}
__device__ __forceinline__ void pack_out(const float (&acc)[96], uint32_t (&po)[48]) {
#pragma unroll
    for (int g = 0; g < 6; g++)
#pragma unroll
        for (int q = 0; q < 4; q++) {
            po[8 * g + q] = pack_bf16(acc[16 * g + 4 * q], acc[16 * g + 4 * q + 1]);
            po[8 * g + 4 + q] = pack_bf16(acc[16 * g + 4 * q + 2], acc[16 * g + 4 * q + 3]);
        }
}
template <bool PINNED = true>
__device__ __forceinline__ void store_one(bool on, uint8_t* p0, uint8_t* p1, const uint32_t (&po)[48], int n) {
    if (PINNED) __syncwarp();
    asm volatile("{\n.reg .pred p;\nsetp.ne.u32 p, %5, 0;\n@p st.global.v4.u32 [%0], {%1, %2, %3, %4};\n}\n"
                 ::"l"(((n & 1) ? p1 : p0) + (n >> 1) * 64), "r"(po[4 * n]), "r"(po[4 * n + 1]), "r"(po[4 * n + 2]), "r"(po[4 * n + 3]), "r"((uint32_t)on) : "memory");
}

template <int N>
__device__ __forceinline__ float tree_max(const float (&v)[N]) {
    float t[N];
#pragma unroll
    for (int i = 0; i < N; i++) t[i] = v[i];
#pragma unroll
    for (int w = 1; w < N; w *= 2)
#pragma unroll
        for (int i = 0; i + w < N; i += 2 * w) t[i] = fmaxf(t[i], t[i + w]);
    return t[0];
}
template <int N>
__device__ __forceinline__ float tree_sum(const float (&v)[N]) {
    float t[N];
#pragma unroll
    for (int i = 0; i < N; i++) t[i] = v[i];
#pragma unroll
    for (int w = 1; w < N; w *= 2)
#pragma unroll
        for (int i = 0; i + w < N; i += 2 * w) t[i] += t[i + w];
    return t[0];
}

template <int T, class F>
__device__ __forceinline__ void third_gemm(float (&d)[32], const uint32_t (&a)[48], uint64_t dsc, F after) {
#pragma unroll
    for (int s = 0; s < 12; s++) {
        if (s == 0) wgmma_n64<true>(d, a[4 * s], a[4 * s + 1], a[4 * s + 2], a[4 * s + 3], desc_at(dsc, s_wv - s_ring + T * 8192 + (s >> 2) * kWChunk + (s & 3) * 32));
        else wgmma_n64<false>(d, a[4 * s], a[4 * s + 1], a[4 * s + 2], a[4 * s + 3], desc_at(dsc, s_wv - s_ring + T * 8192 + (s >> 2) * kWChunk + (s & 3) * 32));
        if (s == 11) wg_commit();
        after(s);
    }
}
template <int T>
__device__ __forceinline__ void third_pack(float (&d)[32], float i0, float i1, uint32_t (&po)[48]) {
    pin(d);
#pragma unroll
    for (int g = 0; g < 2; g++)
#pragma unroll
        for (int q = 0; q < 4; q++) {
            po[16 * T + 8 * g + q] = pack_bf16(d[16 * g + 4 * q] * i0, d[16 * g + 4 * q + 1] * i0);
            po[16 * T + 8 * g + 4 + q] = pack_bf16(d[16 * g + 4 * q + 2] * i1, d[16 * g + 4 * q + 3] * i1);
        }
}

template <int K>
__device__ __forceinline__ void pick(uint32_t m0, uint32_t m1, const float* s, float& v0, float& v1) {
    asm("{\n.reg .pred p, q0, q1;\n.reg .b32 t;\nand.b32 t, %6, %7;\nsetp.ne.u32 p, t, 0;\n"
        "and.b32 t, %6, %8;\nsetp.ne.u32 q0, t, 0;\nand.b32 t, %6, %9;\nsetp.ne.u32 q1, t, 0;\n"
        "@q0 selp.f32 %0, %3, %2, p;\n@q1 selp.f32 %1, %5, %4, p;\n}\n"
        : "+f"(v0), "+f"(v1)
        : "f"(s[0]), "f"(s[1]), "f"(s[2]), "f"(s[3]), "r"(K < 8 ? m0 : m1), "n"(1 << entry_bit(K)), "n"(2 << entry_bit(K)), "n"(4 << entry_bit(K)));
}
template <int B, class F>
__device__ __forceinline__ void for_blocks(F f) {
    if constexpr (B > 0) { for_blocks<B - 1>(f); f(std::integral_constant<int, B - 1>{}); }
}
__device__ __forceinline__ void gather_outer(const float (&s)[44], uint32_t m0, uint32_t m1, float (&v0)[14], float (&v1)[14]) {
    for_blocks<11>([&](auto B) {
        constexpr int b = B.value;
        pick<b>(m0, m1, &s[4 * b], v0[b], v1[b]);
    });
}
__device__ __forceinline__ void gather_mid(const float (&sE)[16], uint32_t m1, float (&v0)[14], float (&v1)[14]) {
    for_blocks<4>([&](auto B) {
        constexpr int b = B.value;
        pick<12 + b>(0, m1, &sE[4 * b], v0[10 + b], v1[10 + b]);
    });
}
__device__ __forceinline__ float quad_max(float m) {
    m = fmaxf(m, __shfl_xor_sync(0xffffffffu, m, 1));
    return fmaxf(m, __shfl_xor_sync(0xffffffffu, m, 2));
}
__device__ __forceinline__ float quad_sum(float s) {
    s += __shfl_xor_sync(0xffffffffu, s, 1);
    return s + __shfl_xor_sync(0xffffffffu, s, 2);
}
template <int B0, int B1>
__device__ __forceinline__ void exp_route(float (&v0)[14], float (&v1)[14], float m0, float m1, const uint4& r, bool even, uint32_t (&y)[14]) {
#pragma unroll
    for (int b = B0; b < B1; b++) { v0[b] = ex2(v0[b] - m0); v1[b] = ex2(v1[b] - m1); }
#pragma unroll
    for (int b = B0; b < B1; b += 2) {
        const uint32_t x0 = pack_bf16(v0[b], v1[b]), x1 = pack_bf16(v0[b + 1], v1[b + 1]);
        const uint32_t u = __shfl_sync(0xffffffffu, even ? x0 : x1, r.x);
        const uint32_t w = __shfl_sync(0xffffffffu, even ? x1 : x0, r.y);
        y[b] = __byte_perm(u, w, r.z); y[b + 1] = __byte_perm(u, w, r.w);
    }
}
template <int BIT0, int N0, int N1>
__device__ __forceinline__ void unfold(const uint32_t (&y)[14], uint32_t fold, uint32_t (&p)[12]) {
    for_blocks<N1 - N0>([&](auto N) {
        constexpr int n = N0 + N.value;
        asm("{\n.reg .pred p;\n.reg .b32 t;\nand.b32 t, %4, %5;\nsetp.ne.u32 p, t, 0;\nselp.b32 %0, %2, 0, p;\nselp.b32 %1, %3, 0, p;\n}\n"
            : "=r"(p[2 * n]), "=r"(p[2 * n + 1]) : "r"(y[2 * n]), "r"(y[2 * n + 1]), "r"(fold), "n"(1 << (BIT0 + n)));
    });
}
__device__ __forceinline__ void keep(bool never, uint32_t a, uint32_t b, uint32_t c, uint32_t d) {
    asm volatile("{\n.reg .pred p;\nsetp.ne.u32 p, %4, 0;\n@p st.volatile.shared.v4.u32 [%5], {%0, %1, %2, %3};\n}\n"
                 ::"r"(a), "r"(b), "r"(c), "r"(d), "r"((uint32_t)never), "r"(s_trace) : "memory");
}

__device__ __forceinline__ uint32_t wimg_offset(uint32_t row, uint32_t s, uint32_t j) {
    return (s >> 2) * kWChunk + row * 128 + (((2 * (s & 3) + (j >> 1)) ^ (row & 7)) << 4) + (j & 1) * 8;
}

__device__ __forceinline__ void ldsm4(uint32_t (&r)[4], uint32_t addr) {
    asm volatile("ldmatrix.sync.aligned.m8n8.x4.shared.b16 {%0, %1, %2, %3}, [%4];" : "=r"(r[0]), "=r"(r[1]), "=r"(r[2]), "=r"(r[3]) : "r"(addr) : "memory");
}
__device__ __forceinline__ void ldsm4_t(uint32_t (&r)[4], uint32_t addr) {
    asm volatile("ldmatrix.sync.aligned.m8n8.x4.trans.shared.b16 {%0, %1, %2, %3}, [%4];" : "=r"(r[0]), "=r"(r[1]), "=r"(r[2]), "=r"(r[3]) : "r"(addr) : "memory");
}
struct MOperands { uint4 A[2][2], B[4][2]; };
__device__ __forceinline__ void m_load(MOperands& m, const uint8_t* wqkv, uint32_t mt, uint32_t s, uint32_t q, uint32_t lane) {
    const uint32_t r8 = lane >> 2, col = q * 128 + (lane & 3) * 16;
    const uint8_t* pa = wqkv + (16 * mt + r8) * 1152 + col;
    const uint8_t* pb = wqkv + (16 * s + 8 * (r8 & 2) + (r8 & 5)) * 1152 + col;
#pragma unroll
    for (int c = 0; c < 2; c++) {
#pragma unroll
        for (int h = 0; h < 2; h++) m.A[h][c] = ldg(pa + 384 + h * 8 * 1152 + c * 64);
#pragma unroll
        for (int n = 0; n < 4; n++) m.B[n][c] = ldg(pb + ((n & 1) * 8 + (n & 2)) * 1152 + c * 64);
    }
}
__device__ __forceinline__ void m_partial(MOperands& m, uint32_t q, uint32_t lane, uint32_t zero) {
    auto& A = m.A;
    auto& B = m.B;
#pragma unroll
    for (int i = 0; i < 4; i++) { uint4& a = A[i >> 1][i & 1]; a.x ^= zero; a.y ^= zero; a.z ^= zero; a.w ^= zero; }
#pragma unroll
    for (int n = 0; n < 4; n++) {
        float d[4] = {0.f, 0.f, 0.f, 0.f};
#pragma unroll
        for (int c = 0; c < 2; c++) {
            mma16816(d, A[0][c].x, A[1][c].x, A[0][c].y, A[1][c].y, B[n][c].x, B[n][c].y);
            mma16816(d, A[0][c].z, A[1][c].z, A[0][c].w, A[1][c].w, B[n][c].z, B[n][c].w);
        }
        asm volatile("st.shared.v4.f32 [%0], {%1, %2, %3, %4};" ::"r"(s_wv + q * 2048 + n * 512 + lane * 16), "f"(d[0]), "f"(d[1]), "f"(d[2]), "f"(d[3]) : "memory");
    }
}
__device__ __forceinline__ void m_reduce(uint32_t e, uint32_t lane, float (&d)[2][4]) {
#pragma unroll
    for (int n = 0; n < 2; n++) {
        float t[3][4];
#pragma unroll
        for (int q = 0; q < 3; q++)
            asm volatile("ld.shared.v4.f32 {%0, %1, %2, %3}, [%4];" : "=f"(t[q][0]), "=f"(t[q][1]), "=f"(t[q][2]), "=f"(t[q][3]) : "r"(s_wv + q * 2048 + e * 1024 + n * 512 + lane * 16) : "memory");
#pragma unroll
        for (int i = 0; i < 4; i++) d[n][i] = (t[0][i] + t[1][i] + t[2][i]) * kScaleLog2e;
    }
}
__device__ __forceinline__ void w_piece(uint32_t q, uint32_t lane, float (&d)[2][4]) {
    const uint32_t rr = lane & 7, mi = lane >> 3, kr = 4 * (rr >> 1) + (mi & 2) + (rr & 1);
    const uint32_t pa = s_wv + q * 32 + (4 * (mi & 2) + rr) * 96 + ((mi & 1) << 4);
    const uint32_t pb = s_wv + 3 * 6144 + kr * 128 + (((mi & 1) ^ (kr & 7)) << 4);
    float e[2][4];
#pragma unroll
    for (int i = 0; i < 8; i++) (&d[0][0])[i] = (&e[0][0])[i] = 0.f;
#pragma unroll
    for (int k = 0; k < 12; k++) {
        uint32_t aq[4], bq[4];
        ldsm4_t(aq, pa + k * 1536);
        ldsm4(bq, (pb ^ ((k & 3) << 5)) + (k >> 2) * 2048);
        mma16816(k & 1 ? e[0] : d[0], aq[0], aq[1], aq[2], aq[3], bq[0], bq[1]);
        mma16816(k & 1 ? e[1] : d[1], aq[0], aq[1], aq[2], aq[3], bq[2], bq[3]);
    }
#pragma unroll
    for (int i = 0; i < 8; i++) (&d[0][0])[i] += (&e[0][0])[i];
}
__device__ __forceinline__ uint32_t piece_offset(uint32_t which, uint32_t s, uint32_t mt, uint32_t lane) {
    const uint32_t r8 = lane >> 2;
    return which * kWBytes + wimg_offset(which ? 32 * (mt >> 1) + 8 * (r8 >> 1) + 4 * (mt & 1) + (r8 & 1) : 16 * mt + r8, s, lane & 3);
}
__device__ __forceinline__ void piece_store(Scratch* g, uint32_t par, uint32_t off0, uint32_t which, const float (&d)[2][4]) {
#pragma unroll
    for (int hf = 0; hf < 2; hf++) {
        const uint32_t off = off0 ^ (hf ? which ? 288 : 1024 : 0);
        const uint32_t a = pack_bf16(d[0][2 * hf], d[0][2 * hf + 1]), b = pack_bf16(d[1][2 * hf], d[1][2 * hf + 1]);
        asm volatile("st.relaxed.gpu.global.v2.u32 [%0], {%1, %2};" ::"l"(g->img[0][0] + (par + off)), "r"(a ? a : 0x8000u), "r"(b) : "memory");
    }
}
__device__ __forceinline__ void piece_clear(Scratch* g, uint32_t par, uint32_t off0, uint32_t which) {
#pragma unroll
    for (int hf = 0; hf < 2; hf++)
        asm volatile("st.relaxed.gpu.global.v2.u32 [%0], {%1, %1};" ::"l"(g->img[0][0] + (par + (off0 ^ (hf ? which ? 288 : 1024 : 0)))), "r"(0) : "memory");
}

__device__ __forceinline__ uint32_t ld_relaxed(const uint32_t* p) {
    uint32_t v;
    asm volatile("ld.relaxed.gpu.global.u32 %0, [%1];" : "=r"(v) : "l"(p) : "memory");
    return v;
}
__device__ __forceinline__ void count_up(uint32_t* p) {
    asm volatile("red.relaxed.gpu.global.add.u32 [%0], %1;" ::"l"(p), "r"(1) : "memory");
}
__device__ __forceinline__ void bulk_g2s(uint32_t dst, const void* src, uint32_t bytes, uint32_t bar) {
    asm volatile("cp.async.bulk.shared::cluster.global.mbarrier::complete_tx::bytes [%0], [%1], %2, [%3];"
                 ::"r"(dst), "l"(src), "r"(bytes), "r"(bar)
                 : "memory");
}

__global__ void __launch_bounds__(kThreads, 1)
nat_fused_kernel(const uint8_t* __restrict__ x, const uint8_t* __restrict__ wqkv, uint8_t* __restrict__ out, Scratch* g,
                 const uint8_t* wo, uint64_t dsc, const __grid_constant__ Maps maps) {
    const int tid = threadIdx.x, lane = tid & 31;
    const int warp = __shfl_sync(0xffffffffu, tid >> 5, 0);
    const int wg = warp >> 2, wq = warp & 3, r8 = lane >> 2, j = lane & 3;
    const int cta = blockIdx.x;
    const Work w = decode_work(cta);
    const uint32_t jq = (cta < 124 ? cta + 8 : cta - 124) / 11u, jr = (cta < 124 ? cta + 8 : cta - 124) - 11 * jq;
    const uint32_t which = jr >= 6, jhi = which ? jr - 6 : jq, jlo = which ? jq : 2 * jr;
    const bool has_job = jr < 10;
    if (wg == 2 && wq < 3) {
#pragma unroll
        for (int r = 0; r < 3; r++)
            asm volatile("st.shared.v4.u32 [%0], {%1, %1, %1, %1};" ::"r"(s_ring + wq * kRingChunk + (r == 0 ? 84 : r == 1 ? 88 : 204) * 128 + lane * 16), "r"(0) : "memory");
        asm volatile("fence.proxy.async.shared::cta;" ::: "memory");
    }
    MOperands mo;
    uint32_t launch = 0;
    if (wg == 1 && wq < 3 && !which) m_load(mo, wqkv, jhi, jlo, wq, lane);
    if (warp == 7) launch = ld_relaxed(g->launches[cta]);
    if (x == nullptr) return;
    const uint32_t t_start = clock_now();
    if (wg == 2) {
        asm volatile("setmaxnreg.dec.sync.aligned.u32 24;");
        if (wq < 3) {
            if (lane < 3 && cta < 128) {
                const uint32_t row = 3 * (cta >> 1) + wq;
                asm volatile("prefetch.global.L2 [%0];" ::"l"((cta & 1 ? wo + row * 384 : wqkv + row * 1152 + 768) + lane * 128));
            }
            asm volatile("bar.sync 7, 192;" ::: "memory");
            const uint32_t par = lds_volatile(s_par);
            uint32_t phase = 0;
#pragma unroll 1
            for (uint32_t c = 0; c < 6; c++) {
                const uint32_t part = c * kWChunk + wq * (kWChunk / 3);
                mbar_wait(bar_img + 8 * c, 0);
                if (c == 0 && lane == 0) mbar_arrive(bar_ok);
                if (wq == 0) TRW(10 + c);
#pragma unroll 1
                while (true) {
                    uint32_t lo = ~0u;
#pragma unroll
                    for (int q = 0; q < 8; q++) lo = min(lo, lds_volatile(s_m + part + lane * 32 + (lane & 12) * 2 + q * 1024));
                    if (__all_sync(0xffffffffu, lo) || phase > 65535) break;
                    if (elect()) {
                        mbar_expect_tx(bar_redo + 8 * wq, kWChunk / 3);
                        bulk_g2s(s_m + part, g->img[0][0] + par + part, kWChunk / 3, bar_redo + 8 * wq);
                    }
                    mbar_wait(bar_redo + 8 * wq, phase++ & 1);
                }
                if (c == 2 && phase) asm volatile("st.shared.u32 [%0], %1;" ::"r"(s_again), "r"(1) : "memory");
                if (c >= 2 && lane == 0) mbar_arrive(bar_ok + 8 * c - 8);
            }
        } else {
            const CUtensorMap* map = &maps.m[w.sv == kPixBytes ? 2 : 0];
            if (elect()) {
#pragma unroll
                for (int i = 0; i < 26; i++) mbar_init(s_bar + 8 * i, i < 15 ? 1 : i < 20 ? 3 : 4);
                asm volatile("fence.mbarrier_init.release.cluster;" ::: "memory");
                prefetch_map(map + 1);
                expect_tx_only(bar_a, sizeof(Table));
                bulk_g2s(s_tab, &maps.tables->t[w.step < 0], sizeof(Table), bar_a);
            }
            if (which && has_job && elect()) {
                mbar_expect_tx(bar_wop, 4 * 6144);
                tma_3d(s_wv, &maps.wo, bar_wop, 0, jhi);
                tma_3d(s_wv + 3 * 6144, &maps.wv, bar_wop, 16 * jlo, 6);
            }
            int u = w.u, v = w.v;
            uint32_t wait_bar = bar_use, wait_par = 1, slot = 0;
#pragma unroll 1
            for (int step = 0; step < 7 - w.corner; step++) {
                const bool first = step == 0 || (w.corner && step == 4);
                const int ou = origin_u(u);
                const bool final = step == 6 - w.corner;
                if (final) { wait_bar = bar_free; wait_par = 0; }
#pragma unroll 1
                for (uint32_t bar = first ? bar_a : bar_b; bar <= (first ? bar_a : bar_mid); bar += 8) {
                    mbar_wait(bar, first ? !step : slot != 0);
                    if (elect()) mbar_expect_tx(bar, first ? 3 * kSlotBytes : bar < bar_mid ? kSlotBytes : 3 * kMidBytes);
                }
                int row = v + 4 + (first ? -w.step : w.step) / 2;
                uint32_t dst = final ? s_m : s_ring + (first ? 0 : slot), bar = first ? bar_a : bar_b, dbar = first ? 0 : 8;
#pragma unroll 1
                for (int r = 0; r < 2 - first; r++) {
                    mbar_wait(wait_bar, wait_par);
                    if (r == 0) TRW(24 + step);
#pragma unroll
                    for (int n = 0; n < 3; n++) {
                        if (n && final) mbar_wait(bar_free + 8 * n, 0);
                        if (elect()) tma_box(dst + n * kRingChunk, map + r, bar + n * dbar, (cta & 1) * kC + 64 * n, ou, (cta >> 1) & 1, row);
                    }
                    row = v + 6; bar = bar_mid; dbar = 0;
                    dst = (final ? s_m : s_ring) + kOffMid + 512;
                    if (wait_bar == bar_use) wait_bar = bar_use + 16;
                }
                TRW(32 + 8 * step + 4);
                if (step == 0) {
                    asm volatile("st.shared.v2.u32 [%0], {%1, %1};" ::"r"(s_late), "r"(0) : "memory");
                    asm volatile("bar.arrive 3, 160;\nbar.arrive 4, 160;\nbar.arrive 8, 128;\nbar.sync 9, 64;" ::: "memory");
                }
                if (step < 2) {
                    if (step) {
                        asm volatile("bar.sync 6, 128;" ::: "memory");
                    }
                    const uint32_t par = __shfl_sync(0xffffffffu, lds_volatile(s_par), 0);
                    wait_until(t_start, step ? TN(5, kTimeW) : TN(6, kTimeM));
                    TRW(5 + 4 * step);
#pragma unroll 1
                    for (int c = 3 * step; c < 3 + 3 * step; c++)
                        if (elect()) {
                            mbar_expect_tx(bar_img + 8 * c, kWChunk);
                            bulk_g2s(s_m + c * kWChunk, g->img[0][0] + (par + c * kWChunk), kWChunk, bar_img + 8 * c);
                        }
                }
                const bool again = w.corner && step == 3;
                wait_bar = step == 0 ? bar_img + 8 * TN(1, 1) : again ? bar_use + 8 : bar_use;
                if (!again) {
                    wait_par = slot ? 0 : step != 0;
                    slot ^= kSlotStride;
                    if (w.corner && step == 2) { u += 8; v -= 8; } else if (step) v += w.step;
                }
            }
        }
        TRDUMP();
        return;
    }
    if (warp == 7) {
        asm volatile("st.shared.u32 [%0], %1;\nbar.arrive 9, 64;" ::"r"(s_par), "r"((launch & 1) * 2 * kWBytes) : "memory");
        g->launches[cta][lane] = launch + 1;
        asm volatile("bar.arrive 5, 128;" ::: "memory");
    }
    if (wg == 1 && wq < 3) {
        if (!which) m_partial(mo, wq, lane, (uint32_t)dsc & 1);
        const uint32_t off = piece_offset(which, which ? jlo : jlo + wq, which ? 3 * jhi + wq : jhi, lane);
        asm volatile("bar.sync %0, %1;" ::"r"(5 + (off >> 31)), "n"(128) : "memory");
        const uint32_t par = lds_volatile(s_par);
        if (which) asm volatile("bar.sync 8, 128;" ::: "memory");
        if (has_job && wq < 2 + which) {
            float d[2][4];
            if (wq == 0) TRX(which ? 1 : 18);
            if (which) {
                mbar_wait(bar_wop, 0);
                if (wq == 0) TRX(2);
                w_piece(wq, lane, d);
            } else {
                m_reduce(wq, lane, d);
            }
            piece_store(g, par, off, which, d);
            __syncwarp();
            piece_clear(g, 2 * kWBytes - par, off, which);
            if (wq == 0) TRX(which ? 3 : 0);
        }
        if (!which) asm volatile("bar.sync 8, 128;" ::: "memory");
        asm volatile("bar.arrive 7, 192;\nbar.arrive 6, 128;" ::: "memory");
    }
    const int order = w.step < 0 ? warp ^ 3 : warp;
    int tu = w.u, tv = w.v + w.step * wg;
    const int du2 = w.corner ? 8 : 0, dv2 = w.corner ? 0 : 2 * w.step;
    uint32_t o0, o1;
    wait_until(t_start, START_TIME);
    asm volatile("setmaxnreg.inc.sync.aligned.u32 240;");
    w.pixel_offsets(tu + r8, tv + 2 * wq, j, o0, o1);
    uint32_t fa[48];
    {
        RawX raw;
        load_raw(raw, x, o0, o1);
        asm volatile("bar.sync %0, 160;" ::"r"(3 + wg) : "memory");
        raw_to_frags(raw, 0, fa);
        pin(fa);
    }
    mbar_wait(bar_ok, 0);
    const uint64_t dA = dsc + wg * (kSlotStride >> 4), dB = dsc + (wg ^ 1) * (kSlotStride >> 4);

    float acc[96];
    uint32_t po[48];
    uint32_t c0 = 0, c1 = 0;
#pragma unroll
    for (int q = 0; q < 48; q++) asm volatile("" : "=r"(po[q]));
#pragma unroll 1
    for (int i = wg; i < w.ntiles; i += 2) {
        const bool first = i == 0, last = i == w.ntiles - 1;

        TRF(8 + 16 * k);
        uint8_t *p0 = out + c0, *p1 = out + c1;
#pragma unroll 1
        for (uint32_t seen = 0;;) {
        wg_fence();
        if (!first) turn_wait(wg);
        proj_gemm(acc, fa, dsc, s_m, [&](int s) {
            if (s == 11 && !first) turn_pass(wg);
            const int n = __builtin_popcount(QSLOTS & ((1 << s) - 1));
            if (((QSLOTS >> s) & 1) && n < 12) store_one(i >= 2, out + c0, out + c1, po, n);
            if ((s == 5 && ((QSLOTS >> 13) & 1)) || (s == 9 && ((QSLOTS >> 16) & 1))) wg_commit();
            if (s == 3 || s == 7) { wg_commit(); mbar_wait(bar_img + 2 * s + 2, 0); wg_fence(); }
        });
        __syncwarp();
        TRF(9 + 16 * k);
            if (!first) break;
            mbar_wait(bar_ok + 8, 0);
            if (lds_volatile(s_again) == seen) break;
            wg_wait<0>();
            seen = 1;
        }
        c0 = o0; c1 = o1;
        w.pixel_offsets(tu + du2 + r8, tv + dv2 + 2 * wq, j, o0, o1);
        if (i + 2 >= w.ntiles) o0 = o1 = 0;
        mbar_wait(bar_a, w.corner ? i >> 1 : 0);
        auto slot = [&](int s) {
            if ((QSLOTS >> s) & 1) { store_one(i >= 2, p0, p1, po, __builtin_popcount(QSLOTS & ((1 << s) - 1))); __syncwarp(); }
        };
        constexpr int G5 = (QSLOTS >> 13) & 1, G9 = (QSLOTS >> 16) & 1;
        wg_wait<2 + G5 + G9>();
        if (last && lane == 0) mbar_arrive(bar_free);
        slot(12);
        if (G5) { wg_wait<2 + G9>(); slot(13); }
        wg_wait<1 + G9>();
        if (last && lane == 0) mbar_arrive(bar_free + 8);
        slot(14); slot(15);
        if (G9) { wg_wait<1>(); slot(16); slot(17); }
        if (!first) turn_wait(wg);
        wg_wait<0>();
        if (last && lane == 0) mbar_arrive(bar_free + 16);
        const uint64_t dE = last ? dsc + ((s_m - s_ring) >> 4) : dsc, dN = last ? dE : dB;
        pin(acc);
        TR(11 + 16 * k);
        TRT(80 + k);
        acc_to_frags(acc, fa);
        pin(fa);

        float sA[44], sE[16], sB[44];
        RawX nxt;
        wg_fence();
#pragma unroll
        for (int s = 0; s < 12; s++) {
            if (s == 0) wgmma_n88<true>(sA, fa[4 * s], fa[4 * s + 1], fa[4 * s + 2], fa[4 * s + 3], desc_at(dA, (s >> 2) * kRingChunk + (s & 3) * 32));
            else wgmma_n88<false>(sA, fa[4 * s], fa[4 * s + 1], fa[4 * s + 2], fa[4 * s + 3], desc_at(dA, (s >> 2) * kRingChunk + (s & 3) * 32));
            if (s == 11) { wg_commit(); if (!first) turn_pass(wg); }
        }
        TRF(12 + 16 * k);
        const int vq = tv + 2 * wq;
        const uint4 tabu = lds128(s_tab + offsetof(Table, u) + (window_start(tu + r8) - origin_u(tu)) * 64 + j * 16);
        const uint4 tabv = lds128(s_tab + offsetof(Table, v) + (window_start(vq) + window_start(vq + 1) - 2 * tv) * 64 + j * 16);
        const uint4 route = lds128(s_tab + lane * 16);
        load_raw(nxt, x, o0, o1);
        float v0[14], v1[14];
#pragma unroll
        for (int b = 0; b < 14; b++) {
            v0[b] = __uint_as_float((route.x >> (b + 6)) + 0xff800000u);
            v1[b] = __uint_as_float((route.y >> (b + 6)) + 0xff800000u);
        }
        const uint32_t m0 = tabu.x | tabv.z, m1 = tabu.y | tabv.w;
        if (!first) turn_wait(wg);
#pragma unroll
        for (int c = 0; c < 3; c++) {
            mbar_wait(bar_b + 8 * c, wg);
            TRF(64 + 4 * k + c);
            wg_fence();
#pragma unroll
            for (int s = 4 * c; s < 4 * c + 4; s++) {
                if (s == 0) wgmma_n88<true>(sB, fa[4 * s], fa[4 * s + 1], fa[4 * s + 2], fa[4 * s + 3], desc_at(dN, c * kRingChunk + (s & 3) * 32));
                else wgmma_n88<false>(sB, fa[4 * s], fa[4 * s + 1], fa[4 * s + 2], fa[4 * s + 3], desc_at(dN, c * kRingChunk + (s & 3) * 32));
                if (s == 3) {
                    wg_commit();
                    wg_wait<1>();
                    pin(sA);
                    gather_outer(sA, tabu.x | tabv.x, tabu.y | tabv.y, v0, v1);
                    pin(v0); pin(v1);
                }
            }
        }
        wg_commit();
        mbar_wait(bar_mid, wg);
        wg_fence();
#pragma unroll
        for (int s = 0; s < 12; s++)
            if (s == 0) wgmma_n32<true>(sE, fa[4 * s], fa[4 * s + 1], fa[4 * s + 2], fa[4 * s + 3], desc_at(dE, kOffMid + (s >> 2) * kRingChunk + (s & 3) * 32));
            else wgmma_n32<false>(sE, fa[4 * s], fa[4 * s + 1], fa[4 * s + 2], fa[4 * s + 3], desc_at(dE, kOffMid + (s >> 2) * kRingChunk + (s & 3) * 32));
        wg_commit();
        turn_pass(wg);
        TRF(13 + 16 * k);
        wg_wait<1>();
        pin(sB);
        gather_outer(sB, m0, m1, v0, v1);
        wg_wait<0>();
        pin(sE);
        TRF(14 + 16 * k);
        gather_mid(sE, m1, v0, v1);
        const float mx0 = quad_max(tree_max(v0)), mx1 = quad_max(tree_max(v1));

        uint32_t y[14], pa[12], pb[12];
        exp_route<0, 14>(v0, v1, mx0, mx1, route, (j & 1) == 0, y);
        float s0 = tree_sum(v0), s1 = tree_sum(v1);
        asm volatile("" : "+f"(s0), "+f"(s1));
        unfold<16, 0, 6>(y, tabv.y, pa);
        turn_wait(wg + (y[0] >> 31));
        TRF(15 + 16 * k + (y[13] >> 31));
        wg_fence();
        wgmma_sp_n192_tb<true, 0>(acc, pa[0], pa[1], pa[2], pa[3], desc_at(dA, kToV), tabu.z);
        wgmma_sp_n192_tb<false, 1>(acc, pa[4], pa[5], pa[6], pa[7], desc_at(dA, kToV + 4096), tabu.z);
        wgmma_sp_n192_tb<false, 0>(acc, pa[8], pa[9], pa[10], pa[11], desc_at(dA, kToV + 8192), tabu.w);
        wg_commit();
        wgmma_sp_n192_tb<false, 1>(acc, j == 0 ? 0u : y[10], j == 0 ? 0u : y[11], y[12], y[13], desc_at(dE, kToV + kOffMid), tabu.w);
        wg_commit();
        unfold<24, 0, 6>(y, tabv.y, pb);
        wg_fence();
        wgmma_sp_n192_tb<false, 0>(acc, pb[0], pb[1], pb[2], pb[3], desc_at(dN, kToV), tabu.z);
        wgmma_sp_n192_tb<false, 1>(acc, pb[4], pb[5], pb[6], pb[7], desc_at(dN, kToV + 4096), tabu.z);
        wgmma_sp_n192_tb<false, 0>(acc, pb[8], pb[9], pb[10], pb[11], desc_at(dN, kToV + 8192), tabu.w);
        wg_commit();
        if (!last) turn_pass(wg);
        TRF(16 + 16 * k);
        wg_wait<2>();
        if (lane == 0) mbar_arrive(bar_use);
        wg_wait<1>();
        if (lane == 0) mbar_arrive(bar_use + 16);
        TRF(17 + 16 * k);
        mbar_wait(bar_ok + 16, 0);
        wg_wait<0>();
        if (lane == 0) mbar_arrive(bar_use + 8);
        pin(acc);
        TR(18 + 16 * k);

        acc_to_frags(acc, po);
        pin(po);
        if (last) {
            const float inv0 = rcp(quad_sum(s0)), inv1 = rcp(quad_sum(s1));
            float t0[32], t1[32], t2[32];
            uint32_t pq[48];
            wg_fence();
            third_gemm<0>(t0, po, dsc, [](int) {});
            third_gemm<1>(t1, po, dsc, [&](int s) { if (s == 3) { keep(wqkv == nullptr, __float_as_uint(inv0), __float_as_uint(inv1), c0, c1); __syncwarp(); } });
            wg_wait<1>();
            third_pack<0>(t0, inv0, inv1, pq);
#pragma unroll
            for (int n = 0; n < 4 - __builtin_popcount(TSLOTS); n++) store_one<false>(true, out + c0, out + c1, pq, n);
            __syncwarp();
            third_gemm<2>(t2, po, dsc, [&](int s) { if ((TSLOTS >> s) & 1) store_one(true, out + c0, out + c1, pq, 4 - __builtin_popcount(TSLOTS >> s)); });
            __syncwarp();
            wg_wait<1>();
            third_pack<1>(t1, inv0, inv1, pq);
#pragma unroll
            for (int n = 4; n < 8; n++) store_one<false>(true, out + c0, out + c1, pq, n);
            __syncwarp();
            wg_wait<0>();
            third_pack<2>(t2, inv0, inv1, pq);
#pragma unroll
            for (int n = 8; n < 12; n++) store_one<false>(true, out + c0, out + c1, pq, n);
            break;
        }
        turn_wait(wg);
        wg_fence();
        proj_gemm(acc, po, dsc, s_wv, [&](int s) {
            if (s == 3 || s == 7) { mbar_wait(bar_ok + 2 * s + 18, 0); wg_fence(); }
            if (s + 1 == OSPLIT && i + 2 == w.ntiles) { turn_pass(wg); turn_wait(wg); }
        });
        turn_pass(wg);
        TRF(19 + 16 * k);
        const uint32_t zero = lds_volatile(s_late);
        const float inv0 = rcp(quad_sum(s0 + __uint_as_float(zero))), inv1 = rcp(quad_sum(s1 + __uint_as_float(zero)));
        raw_to_frags(nxt, zero, fa);
        pin(fa);
#pragma unroll
        for (int q = 0; q < 48; q += 4) keep(wqkv == nullptr, fa[q], fa[q + 1], fa[q + 2], fa[q + 3]);
        keep(wqkv == nullptr, __float_as_uint(inv0), __float_as_uint(inv1), zero, lane);
        TRF(20 + 16 * k);
        tu += du2; tv += dv2;
        wg_wait<0>();
        pin(acc);
        TR(21 + 16 * k);
#pragma unroll
        for (int q = 0; q < 96; q++) acc[q] *= q & 2 ? inv1 : inv0;
        pack_out(acc, po);
#pragma unroll
        for (int n = 0; n < INL; n++) store_one<false>(i + 2 == w.ntiles, out + c0, out + c1, po, n);
        pin(po);
    }
    if (wg == 0) {
#pragma unroll
        for (int n = INL; n < 12; n++) {
            __nanosleep(NAP);
            store_one<false>(true, out + c0, out + c1, po, n);
        }
    }
    TRE(7);
    TRG(1);
    TRDUMP();
}

typedef CUresult (*EncodeTiledFn)(CUtensorMap*, CUtensorMapDataType, cuuint32_t, void*, const cuuint64_t*, const cuuint64_t*,
                                  const cuuint32_t*, const cuuint32_t*, CUtensorMapInterleave, CUtensorMapSwizzle,
                                  CUtensorMapL2promotion, CUtensorMapFloatOOBfill);

bool make_maps(EncodeTiledFn fn, Maps* maps, void* x, void* wqkv, void* wo) {
    const cuuint64_t pix2 = 2 * kPixBytes, row = (cuuint64_t)kHW * kPixBytes;
    const cuuint32_t estr[5] = {1, 1, 1, 1, 1};
    bool ok = true;
    for (int tr = 0; tr < 2; tr++)
        for (int b = 0; b < 2; b++) {
            const cuuint64_t su = tr ? 2 * row : pix2, sv = tr ? pix2 : 2 * row;
            const cuuint64_t dims[5] = {2 * kC, 2, 105, 2, 112};
            const cuuint64_t strides[4] = {7 * su, su, row, sv};
            const cuuint32_t box[5] = {64, 2, 7, 1, b ? 2u : 6u};
            ok = ok && fn(&maps->m[2 * tr + b], CU_TENSOR_MAP_DATA_TYPE_BFLOAT16, 5, x, dims, strides, box, estr,
                          CU_TENSOR_MAP_INTERLEAVE_NONE, CU_TENSOR_MAP_SWIZZLE_128B, CU_TENSOR_MAP_L2_PROMOTION_L2_128B,
                          CU_TENSOR_MAP_FLOAT_OOB_FILL_NONE) == CUDA_SUCCESS;
        }
    for (int b = 0; b < 2; b++) {
        const cuuint64_t dims[3] = {b ? 64u : 48u, kC, b ? 9u : 4u}, strides[2] = {(b ? 3u : 1u) * kPixBytes, b ? 128u : 96u};
        const cuuint32_t box[3] = {b ? 64u : 48u, b ? 16u : 192u, b ? 3u : 1u};
        ok = ok && fn(b ? &maps->wv : &maps->wo, CU_TENSOR_MAP_DATA_TYPE_BFLOAT16, 3, b ? wqkv : wo, dims, strides, box, estr,
                      CU_TENSOR_MAP_INTERLEAVE_NONE, b ? CU_TENSOR_MAP_SWIZZLE_128B : CU_TENSOR_MAP_SWIZZLE_NONE, CU_TENSOR_MAP_L2_PROMOTION_L2_128B,
                      CU_TENSOR_MAP_FLOAT_OOB_FILL_NONE) == CUDA_SUCCESS;
    }
    return ok;
}

}

extern "C" void kernel_launch(void* const* d_in, const int* in_sizes, int n_in, void* d_out, int out_size) {
    static EncodeTiledFn encode = nullptr;
    static Scratch* scratch = nullptr;
    static Tables* tables = nullptr;
    if (!encode) {
        int dev = 0, reserved = 0;
        cudaFuncAttributes attr;
        cudaGetDevice(&dev);
        cudaDeviceGetAttribute(&reserved, cudaDevAttrReservedSharedMemoryPerBlock, dev);
        cudaFuncGetAttributes(&attr, nat_fused_kernel);
        if (reserved != (int)kSmemBase || attr.sharedSizeBytes != 0) return;
        cudaGetSymbolAddress((void**)&scratch, g_scratch);
        cudaGetSymbolAddress((void**)&tables, g_tables);
        void* fn = nullptr;
        cudaDriverEntryPointQueryResult st;
        cudaGetDriverEntryPoint("cuTensorMapEncodeTiled", &fn, cudaEnableDefault, &st);
        encode = (EncodeTiledFn)fn;
        cudaFuncSetAttribute(nat_fused_kernel, cudaFuncAttributeMaxDynamicSharedMemorySize, kSmemBytes);
    }
    Maps maps;
    maps.tables = tables;
    if (!encode || !make_maps(encode, &maps, d_in[0], d_in[1], d_in[2])) return;
    nat_fused_kernel<<<kGrid, kThreads, kSmemBytes>>>((const uint8_t*)d_in[0], (const uint8_t*)d_in[1], (uint8_t*)d_out, scratch, (const uint8_t*)d_in[2],
                                                      kDescRing, maps);
}
```
